```python
import torch

def _softmax(x, axis=-1):
    return torch.softmax(x, dim=axis)
def _gelu(x):
    return torch.nn.functional.gelu(x, approximate="tanh")
def _silu(x):
    return torch.nn.functional.silu(x)
def _sigmoid(x):
    return torch.sigmoid(x)
def _layernorm(x, axis=-1, eps=1e-5):
    m = x.mean(dim=axis, keepdim=True)
    v = x.var(dim=axis, keepdim=True, unbiased=False)
    return (x - m) / torch.sqrt(v + eps)
def _scatter_add(tgt, idx, src, axis=0):
    return tgt.clone().index_add_(axis, idx, src)
def _segment_sum(src, seg, n):
    out = torch.zeros((n,) + src.shape[1:], dtype=src.dtype)
    return out.index_add_(0, seg, src)
def _pad(x, pw):
    flat = tuple(v for pair in reversed(pw) for v in pair)
    return torch.nn.functional.pad(x, flat)

kernel_name = 'sequential_preLN__spectral_gfnet__mixer_token_mlp__prompt'

def setup_inputs():

    _w = (lambda a: (lambda t: t.to(torch.bfloat16) if t.is_floating_point() else t)(torch.as_tensor(a)))
    def _A_setup():
        B, S, D = 1, 2048, 512
        Df = D // 2 + 1
        return {
            "x": _w((lambda *s: torch.randn(*s, dtype=torch.bfloat16) * 0.05)(B, S, D)),
            "w_r": _w((lambda *s: torch.randn(*s, dtype=torch.bfloat16) * 0.2)(S, Df) * 0.02),
            "w_i": _w((lambda *s: torch.randn(*s, dtype=torch.bfloat16) * 0.2)(S, Df) * 0.02),
        }
    _A_in = _A_setup()

    def _B_setup():
        B, S, D, F = 1, 2048, 512, 1376
        return {
            "x": _w((lambda *s: torch.randn(*s, dtype=torch.bfloat16) * 0.05)(B, S, D)),
            "w1": _w((lambda *s: torch.randn(*s, dtype=torch.bfloat16) * 0.4)(S, F) * (S ** -0.5)),
            "b1": _w((lambda *s: torch.randn(*s, dtype=torch.bfloat16) * 3.2)(F) * 0.02),
            "w2": _w((lambda *s: torch.randn(*s, dtype=torch.bfloat16) * 0.2)(F, S) * (F ** -0.5)),
            "b2": _w((lambda *s: torch.randn(*s, dtype=torch.bfloat16) * 0.4)(S) * 0.02),
        }
    _B_in = _B_setup()

    return {
        "A_x": _A_in["x"],
        "A_w_r": _A_in["w_r"],
        "A_w_i": _A_in["w_i"],
        "B_x": _B_in["x"],
        "B_w1": _B_in["w1"],
        "B_b1": _B_in["b1"],
        "B_w2": _B_in["w2"],
        "B_b2": _B_in["b2"],
    }

def reference(A_x, A_w_r, A_w_i, B_x, B_w1, B_b1, B_w2, B_b2):
    def _A_ref(x, w_r, w_i):
        B, S, D = x.shape
        X = (lambda x, axes=(-2,-1): torch.fft.rfft2(x.float(), dim=axes))(x, axes=(-2, -1))
        W = w_r + 1j * w_i
        X = X * W
        y = (lambda x, s, axes=(-2,-1): torch.fft.irfft2(x, s=s, dim=axes).to(torch.bfloat16))(X, (S, D), axes=(-2, -1))
        return y

    def _B_ref(x, w1, b1, w2, b2):
        B, S, D = x.shape
        h = _layernorm(x, axis=-1)
        u = torch.einsum("bsd,sf->bdf", h, w1) + b1
        u = _gelu(u)
        y = torch.einsum("bdf,fs->bds", u, w2) + b2
        return (lambda x, *d: x.permute(*d))(y, 0, 2, 1)

    x = A_x
    h = x + _A_ref(_layernorm(x, axis=-1), A_w_r, A_w_i)
    h2 = h + _B_ref(_layernorm(h, axis=-1), B_w1, B_b1, B_w2, B_b2)
    return h2
```

```cpp
#include <cuda_runtime.h>
#include <cuda.h>
#include <cuda_bf16.h>
#include <stdint.h>
#define W1_INFLIGHT 6
#define W2_RATE 1
template<int TA, int TB> __device__ __forceinline__ void wgmma_n88_ss(float (&d)[44], uint64_t da, uint64_t db, int sd) {
  asm volatile("{\n.reg .pred p;\nsetp.ne.b32 p, %46, 0;\n"
    "wgmma.mma_async.sync.aligned.m64n88k16.f32.bf16.bf16 {%0, %1, %2, %3, %4, %5, %6, %7, %8, %9, %10, %11, %12, %13, %14, %15, %16, %17, %18, %19, %20, %21, %22, %23, %24, %25, %26, %27, %28, %29, %30, %31, %32, %33, %34, %35, %36, %37, %38, %39, %40, %41, %42, %43}, %44, %45, p, 1, 1, %47, %48;\n}\n"
    : "+f"(d[0]), "+f"(d[1]), "+f"(d[2]), "+f"(d[3]), "+f"(d[4]), "+f"(d[5]), "+f"(d[6]), "+f"(d[7]), "+f"(d[8]), "+f"(d[9]), "+f"(d[10]), "+f"(d[11]), "+f"(d[12]), "+f"(d[13]), "+f"(d[14]), "+f"(d[15]), "+f"(d[16]), "+f"(d[17]), "+f"(d[18]), "+f"(d[19]), "+f"(d[20]), "+f"(d[21]), "+f"(d[22]), "+f"(d[23]), "+f"(d[24]), "+f"(d[25]), "+f"(d[26]), "+f"(d[27]), "+f"(d[28]), "+f"(d[29]), "+f"(d[30]), "+f"(d[31]), "+f"(d[32]), "+f"(d[33]), "+f"(d[34]), "+f"(d[35]), "+f"(d[36]), "+f"(d[37]), "+f"(d[38]), "+f"(d[39]), "+f"(d[40]), "+f"(d[41]), "+f"(d[42]), "+f"(d[43]) : "l"(da), "l"(db), "r"(sd), "n"(TA), "n"(TB));
}
template<int TA, int TB> __device__ __forceinline__ void wgmma_n128_ss(float (&d)[64], uint64_t da, uint64_t db, int sd) {
  asm volatile("{\n.reg .pred p;\nsetp.ne.b32 p, %66, 0;\n"
    "wgmma.mma_async.sync.aligned.m64n128k16.f32.bf16.bf16 {%0, %1, %2, %3, %4, %5, %6, %7, %8, %9, %10, %11, %12, %13, %14, %15, %16, %17, %18, %19, %20, %21, %22, %23, %24, %25, %26, %27, %28, %29, %30, %31, %32, %33, %34, %35, %36, %37, %38, %39, %40, %41, %42, %43, %44, %45, %46, %47, %48, %49, %50, %51, %52, %53, %54, %55, %56, %57, %58, %59, %60, %61, %62, %63}, %64, %65, p, 1, 1, %67, %68;\n}\n"
    : "+f"(d[0]), "+f"(d[1]), "+f"(d[2]), "+f"(d[3]), "+f"(d[4]), "+f"(d[5]), "+f"(d[6]), "+f"(d[7]), "+f"(d[8]), "+f"(d[9]), "+f"(d[10]), "+f"(d[11]), "+f"(d[12]), "+f"(d[13]), "+f"(d[14]), "+f"(d[15]), "+f"(d[16]), "+f"(d[17]), "+f"(d[18]), "+f"(d[19]), "+f"(d[20]), "+f"(d[21]), "+f"(d[22]), "+f"(d[23]), "+f"(d[24]), "+f"(d[25]), "+f"(d[26]), "+f"(d[27]), "+f"(d[28]), "+f"(d[29]), "+f"(d[30]), "+f"(d[31]), "+f"(d[32]), "+f"(d[33]), "+f"(d[34]), "+f"(d[35]), "+f"(d[36]), "+f"(d[37]), "+f"(d[38]), "+f"(d[39]), "+f"(d[40]), "+f"(d[41]), "+f"(d[42]), "+f"(d[43]), "+f"(d[44]), "+f"(d[45]), "+f"(d[46]), "+f"(d[47]), "+f"(d[48]), "+f"(d[49]), "+f"(d[50]), "+f"(d[51]), "+f"(d[52]), "+f"(d[53]), "+f"(d[54]), "+f"(d[55]), "+f"(d[56]), "+f"(d[57]), "+f"(d[58]), "+f"(d[59]), "+f"(d[60]), "+f"(d[61]), "+f"(d[62]), "+f"(d[63]) : "l"(da), "l"(db), "r"(sd), "n"(TA), "n"(TB));
}

constexpr int S_ = 2048, D_ = 512, F_ = 1376, DF = 257;
constexpr int NCTA = 128;
constexpr int W_BYTES = 180224;
constexpr int RING_OFF = W_BYTES;
constexpr int NST = 6;
constexpr int BAR_OFF = RING_OFF + NST * 8192;
constexpr int SMEM_BYTES = BAR_OFF + 512;
constexpr int FILT_OFF = RING_OFF;
constexpr int XCH_OFF = RING_OFF + 16384;
constexpr int ZROW = 328;
constexpr int MB_FULL = 0, MB_EMPTY = 6, MB_W2 = 12, MB_P2IN = 34, MB_FILT = 35, MB_W1 = 36, MB_PEER1 = 37, MB_X1 = 38,
              MB_X1DONE = 39, MB_PEER2 = 40, MB_X2 = 41, MB_P3DONE = 42;
constexpr int BASE_OFF = BAR_OFF + 448;
#define W2_START 18

__device__ uint4 g_T1[NCTA * 1024];
__device__ uint4 g_T2[NCTA * 1024];
__device__ uint4 g_h[S_ * D_ / 8];
__device__ uint4 g_Hn[4 * 128 * 256];
__device__ uint4 g_U[4 * 172 * 128];
__device__ unsigned g_cnt[8 * 64];
#define STAMP(i)

__device__ __forceinline__ void mbar_init(uint32_t b, int c) { asm volatile("mbarrier.init.shared::cta.b64 [%0], %1;" :: "r"(b), "r"(c) : "memory"); }
__device__ __forceinline__ void mbar_expect(uint32_t b, int bytes) { asm volatile("mbarrier.arrive.expect_tx.shared::cta.b64 _, [%0], %1;" :: "r"(b), "r"(bytes) : "memory"); }
__device__ __forceinline__ void mbar_arrive(uint32_t b) { asm volatile("mbarrier.arrive.shared::cta.b64 _, [%0];" :: "r"(b) : "memory"); }
__device__ __forceinline__ void mbar_arrive_cluster(uint32_t remote) { asm volatile("mbarrier.arrive.release.cluster.shared::cluster.b64 _, [%0];" :: "r"(remote) : "memory"); }
__device__ __forceinline__ uint32_t mapa(uint32_t a, uint32_t cta) { uint32_t r; asm("mapa.shared::cluster.u32 %0, %1, %2;" : "=r"(r) : "r"(a), "r"(cta)); return r; }
__device__ __forceinline__ void mbar_wait(uint32_t b, int ph) {
  asm volatile("{\n.reg .pred p;\n.reg .u32 n;\nmov.u32 n, 0;\nL_W:\n"
               "mbarrier.try_wait.parity.shared::cta.b64 p, [%0], %1;\n@p bra L_D;\n"
               "add.u32 n, n, 1;\nsetp.lt.u32 p, n, 4000000;\n@p bra L_W;\ntrap;\nL_D:\n}" :: "r"(b), "r"(ph) : "memory");
}
__device__ __forceinline__ void mbar_wait_cluster(uint32_t b, int ph) {
  asm volatile("{\n.reg .pred p;\n.reg .u32 n;\nmov.u32 n, 0;\nL_W:\n"
               "mbarrier.try_wait.parity.acquire.cluster.shared::cta.b64 p, [%0], %1;\n@p bra L_D;\n"
               "add.u32 n, n, 1;\nsetp.lt.u32 p, n, 4000000;\n@p bra L_W;\ntrap;\nL_D:\n}" :: "r"(b), "r"(ph) : "memory");
}
__device__ __forceinline__ void bulk_ld(uint32_t dst, const void* src, int bytes, uint32_t bar) {
  asm volatile("cp.async.bulk.shared::cluster.global.mbarrier::complete_tx::bytes [%0], [%1], %2, [%3];" :: "r"(dst), "l"(src), "r"(bytes), "r"(bar) : "memory");
}
__device__ __forceinline__ void tma3d(uint32_t dst, const CUtensorMap* tm, int c0, int c1, int c2, uint32_t bar) {
  asm volatile("cp.async.bulk.tensor.3d.shared::cluster.global.mbarrier::complete_tx::bytes [%0], [%1, {%3, %4, %5}], [%2];"
               :: "r"(dst), "l"(tm), "r"(bar), "r"(c0), "r"(c1), "r"(c2) : "memory");
}
__device__ __forceinline__ bool elect() { uint32_t p; asm volatile("{.reg .pred p; elect.sync _|p, 0xffffffff; selp.b32 %0, 1, 0, p;}" : "=r"(p)); return p; }
__device__ __forceinline__ uint64_t mkdesc(uint32_t addr, uint32_t lbo, uint32_t sbo, uint32_t sw) {
  return (uint64_t)((addr & 0x3FFFF) >> 4) | ((uint64_t)(lbo >> 4) << 16) | ((uint64_t)(sbo >> 4) << 32) | ((uint64_t)sw << 62);
}
__device__ __forceinline__ uint32_t pk(float lo, float hi) { uint32_t r; asm("cvt.rn.bf16x2.f32 %0, %1, %2;" : "=r"(r) : "f"(hi), "f"(lo)); return r; }
__device__ __forceinline__ float blo(uint32_t w) { return __uint_as_float(w << 16); }
__device__ __forceinline__ float bhi(uint32_t w) { return __uint_as_float(w & 0xffff0000u); }
__device__ __forceinline__ void mma(float (&c)[4], uint32_t a0, uint32_t a1, uint32_t a2, uint32_t a3, uint32_t b0, uint32_t b1) {
  asm("mma.sync.aligned.m16n8k16.row.col.f32.bf16.bf16.f32 {%0,%1,%2,%3}, {%4,%5,%6,%7}, {%8,%9}, {%0,%1,%2,%3};"
      : "+f"(c[0]), "+f"(c[1]), "+f"(c[2]), "+f"(c[3]) : "r"(a0), "r"(a1), "r"(a2), "r"(a3), "r"(b0), "r"(b1));
}
__device__ __forceinline__ void mma0(float (&c)[4], uint32_t a0, uint32_t a1, uint32_t a2, uint32_t a3, uint32_t b0, uint32_t b1) {
  asm("mma.sync.aligned.m16n8k16.row.col.f32.bf16.bf16.f32 {%0,%1,%2,%3}, {%4,%5,%6,%7}, {%8,%9}, {%10,%10,%10,%10};"
      : "=f"(c[0]), "=f"(c[1]), "=f"(c[2]), "=f"(c[3]) : "r"(a0), "r"(a1), "r"(a2), "r"(a3), "r"(b0), "r"(b1), "f"(0.f));
}
__device__ __forceinline__ void wbar() { asm volatile("bar.sync 1, 256;" ::: "memory"); }
__device__ __forceinline__ void sts32(uint32_t a, uint32_t v) { asm volatile("st.shared.b32 [%0], %1;" :: "r"(a), "r"(v) : "memory"); }
__device__ __forceinline__ void sts64(uint32_t a, uint32_t x, uint32_t y) { asm volatile("st.shared.v2.b32 [%0], {%1,%2};" :: "r"(a), "r"(x), "r"(y) : "memory"); }
__device__ __forceinline__ void sts128(uint32_t a, uint4 v) { asm volatile("st.shared.v4.b32 [%0], {%1,%2,%3,%4};" :: "r"(a), "r"(v.x), "r"(v.y), "r"(v.z), "r"(v.w) : "memory"); }
__device__ __forceinline__ uint32_t lds32(uint32_t a) { uint32_t v; asm volatile("ld.shared.b32 %0, [%1];" : "=r"(v) : "r"(a) : "memory"); return v; }
__device__ __forceinline__ uint2 lds64(uint32_t a) { uint2 v; asm volatile("ld.shared.v2.b32 {%0,%1}, [%2];" : "=r"(v.x), "=r"(v.y) : "r"(a) : "memory"); return v; }
__device__ __forceinline__ uint4 lds128(uint32_t a) { uint4 v; asm volatile("ld.shared.v4.b32 {%0,%1,%2,%3}, [%4];" : "=r"(v.x), "=r"(v.y), "=r"(v.z), "=r"(v.w) : "r"(a) : "memory"); return v; }
__device__ __forceinline__ uint4 ldcg128(const void* p) { uint4 v; asm volatile("ld.global.cg.v4.b32 {%0,%1,%2,%3}, [%4];" : "=r"(v.x), "=r"(v.y), "=r"(v.z), "=r"(v.w) : "l"(p) : "memory"); return v; }
__device__ __forceinline__ void st_async4(uint32_t a, float x, float y, float z, float w, uint32_t bar) {
  asm volatile("st.async.weak.shared::cluster.mbarrier::complete_tx::bytes.v4.f32 [%0], {%1,%2,%3,%4}, [%5];" :: "r"(a), "f"(x), "f"(y), "f"(z), "f"(w), "r"(bar) : "memory");
}
__device__ __forceinline__ void st_async2(uint32_t a, float x, float y, uint32_t bar) {
  asm volatile("st.async.weak.shared::cluster.mbarrier::complete_tx::bytes.v2.f32 [%0], {%1,%2}, [%3];" :: "r"(a), "f"(x), "f"(y), "r"(bar) : "memory");
}
__device__ __forceinline__ void cnt_arrive(int i) { asm volatile("red.release.gpu.global.add.u32 [%0], 1;" :: "l"(&g_cnt[i * 64]) : "memory"); }
__device__ __forceinline__ void cnt_wait(int i, unsigned target) {
  unsigned v; int n = 0;
  do { asm volatile("ld.acquire.gpu.global.u32 %0, [%1];" : "=r"(v) : "l"(&g_cnt[i * 64]) : "memory"); if (++n > 2000000) __trap(); } while ((int)(v - target) < 0);
}
template <int N> __device__ __forceinline__ void cs(int n, float& c, float& s) {
  n = ((n + N / 2) & (N - 1)) - N / 2;
  float a = (float)n * (6.283185307179586f / N);
  c = __cosf(a); s = __sinf(a);
}
constexpr float ALPHA = 1.13288f;
struct FftC { uint32_t ar[2][2], ai[2][2], p[4], q1, q3; float tc[2][4], ts[2][4]; };
constexpr uint32_t NEG = 0x80008000u;

__device__ __forceinline__ void fft_s1(const FftC& K, const uint32_t (&in)[4][2], float (&cr)[2][4], float (&ci)[2][4]) {
#pragma unroll
  for (int h = 0; h < 2; h++) {
    mma0(cr[h], K.ar[0][0], K.ar[1][0], K.ar[0][1], K.ar[1][1], in[0][h], in[1][h]);
    mma0(ci[h], K.ai[0][0], K.ai[1][0], K.ai[0][1], K.ai[1][1], in[0][h], in[1][h]);
  }
#pragma unroll
  for (int h = 0; h < 2; h++) {
    mma(cr[h], K.ar[0][0], K.ar[1][0] ^ NEG, K.ar[0][1], K.ar[1][1] ^ NEG, in[2][h], in[3][h]);
    mma(ci[h], K.ai[0][0], K.ai[1][0] ^ NEG, K.ai[0][1], K.ai[1][1] ^ NEG, in[2][h], in[3][h]);
  }
}
__device__ __forceinline__ void fft_s2(const FftC& K, const float (&cr)[2][4], const float (&ci)[2][4], float (&o)[4][4]) {
  uint32_t a[2][4];
#pragma unroll
  for (int h = 0; h < 2; h++)
#pragma unroll
    for (int i = 0; i < 4; i++) {
      float xr = cr[i & 1][2 * h + (i >> 1)], xi = ci[i & 1][2 * h + (i >> 1)];
      a[h][i] = pk(xr * K.tc[h][i] + xi * K.ts[h][i], xi * K.tc[h][i] - xr * K.ts[h][i]);
    }
  mma0(o[0], a[0][0], a[1][0], a[0][1], a[1][1], K.p[0], K.p[1]);
  mma0(o[1], a[0][0], a[1][0], a[0][1], a[1][1], K.p[0], K.q1);
  mma0(o[2], a[0][0], a[1][0], a[0][1], a[1][1], K.p[0], K.p[1] ^ NEG);
  mma0(o[3], a[0][0], a[1][0], a[0][1], a[1][1], K.p[0], K.q1 ^ NEG);
  mma(o[0], a[0][2], a[1][2], a[0][3], a[1][3], K.p[2], K.p[3]);
  mma(o[1], a[0][2], a[1][2], a[0][3], a[1][3], K.p[2] ^ NEG, K.q3 ^ NEG);
  mma(o[2], a[0][2], a[1][2], a[0][3], a[1][3], K.p[2], K.p[3] ^ NEG);
  mma(o[3], a[0][2], a[1][2], a[0][3], a[1][3], K.p[2] ^ NEG, K.q3);
}
__device__ __forceinline__ int zphys(int k) { return k + 8 * (k >> 5); }
__device__ __forceinline__ float gelu(float u) {
  float z = u * (0.7978845608028654f + 0.035677408136300125f * u * u), th;
  asm("tanh.approx.f32 %0, %1;" : "=f"(th) : "f"(z));
  float hu = 0.5f * u;
  return fmaf(hu, th, hu);
}

__global__ void __cluster_dims__(2, 1, 1) __launch_bounds__(384, 1)
fused_kernel(const __grid_constant__ CUtensorMap tmW2, const uint2* __restrict__ x, const unsigned short* __restrict__ wr,
             const unsigned short* __restrict__ wi, const char* __restrict__ w1, const uint32_t* __restrict__ b1,
             const char* __restrict__ w2, const unsigned short* __restrict__ b2, uint4* __restrict__ out) {
  extern __shared__ __align__(1024) char smem[];
  const uint32_t sb = (uint32_t)__cvta_generic_to_shared(smem);
  const uint32_t mb = sb + BAR_OFF;
  const int b = blockIdx.x, rank = b & 1, pr = b >> 1, dt = pr & 3, ot = pr >> 2;
  const int warp = __shfl_sync(0xffffffffu, threadIdx.x >> 5, 0), lane = threadIdx.x & 31;
  const int g = lane >> 2, t = lane & 3;

  if (warp < 8) {
    const int tid = threadIdx.x;
    uint32_t xw[2][4][2];
    {
      const uint2* xp = x + (size_t)(256 * warp + 2 * b) * 128 + 8 * t + g;
#pragma unroll
      for (int a = 0; a < 2; a++)
#pragma unroll
        for (int j = 0; j < 4; j++) { uint2 v = __ldg(xp + a * 128 + 32 * j); xw[a][j][0] = v.x; xw[a][j][1] = v.y; }
    }
    STAMP(0);
    asm volatile("barrier.cluster.arrive.relaxed.aligned;" ::: "memory");
    unsigned base = 0;
    if (tid == 0) base = __ldcg(&g_cnt[1 * 64]);
    FftC K;
    {
      float c, s;
#pragma unroll
      for (int h = 0; h < 2; h++)
#pragma unroll
        for (int j = 0; j < 2; j++) {
          cs<16>((2 * g + h) * (t + 4 * j), c, s);
          K.ar[h][j] = pk(ALPHA * c, ALPHA * s); K.ai[h][j] = pk(-ALPHA * s, ALPHA * c);
        }
#pragma unroll
      for (int i = 0; i < 4; i++) {
        cs<16>((4 * t + i) * (g >> 1) + 4 * (g & 1), c, s);
        K.p[i] = pk(ALPHA * c, ALPHA * s);
        if (i == 1) K.q1 = pk(-ALPHA * s, ALPHA * c);
        if (i == 3) K.q3 = pk(-ALPHA * s, ALPHA * c);
      }
#pragma unroll
      for (int h = 0; h < 2; h++)
#pragma unroll
        for (int i = 0; i < 4; i++) {
          cs<256>((2 * g + h) * (4 * t + i), c, s);
          K.tc[h][i] = c * (1.f / (ALPHA * ALPHA)); K.ts[h][i] = s * (1.f / (ALPHA * ALPHA));
        }
    }
    const int key = ((b >> 3) & 3) * 2 + (b & 1);
    const uint32_t zb = sb + XCH_OFF;
    float mean[2];
    {
      uint32_t a8[2][4]; float vc[4], vs[4];
#pragma unroll
      for (int a = 0; a < 2; a++)
#pragma unroll
        for (int u = 0; u < 2; u++) {
          float c, s; cs<2048>(g * (256 * (t + 4 * u) + 2 * b + a), c, s);
          a8[a][2 * u] = pk(c, s); a8[a][2 * u + 1] = pk(-s, c);
        }
#pragma unroll
      for (int i = 0; i < 4; i++) cs<512>(16 * warp + 8 * (i >> 1) + 2 * t + (i & 1) + 128, vc[i], vs[i]);
      asm volatile("barrier.cluster.wait.aligned;" ::: "memory");
#pragma unroll
      for (int a = 0; a < 2; a++) {
        float cr[2][4], ci[2][4], o[4][4];
        fft_s1(K, xw[a], cr, ci);
        float sm = ((cr[0][0] + cr[0][1]) + (cr[1][0] + cr[1][1])) + ((ci[0][0] + ci[0][1]) + (ci[1][0] + ci[1][1]));
        sm += __shfl_xor_sync(0xffffffffu, sm, 1); sm += __shfl_xor_sync(0xffffffffu, sm, 2);
        sm = g == 0 ? sm * (1.f / 32.f) : 0.f;
#pragma unroll
        for (int h = 0; h < 2; h++) { cr[h][0] -= sm; cr[h][1] -= sm; ci[h][0] -= sm; ci[h][1] -= sm; }
        mean[a] = __shfl_sync(0xffffffffu, sm, 0) * (1.f / (16.f * 1.1328125f));
        float q = 0.f, q2 = 0.f;
#pragma unroll
        for (int i = 0; i < 4; i++) { q = fmaf(cr[0][i], cr[0][i], q); q2 = fmaf(cr[1][i], cr[1][i], q2); q = fmaf(ci[0][i], ci[0][i], q); q2 = fmaf(ci[1][i], ci[1][i], q2); }
        q += q2;
#pragma unroll
        for (int m = 1; m < 32; m <<= 1) q += __shfl_xor_sync(0xffffffffu, q, m);
        float r = rsqrtf(q * (1.f / (512.f * 16.f * ALPHA * ALPHA)) + 1e-5f) * 4.76837158203125e-7f;
        fft_s2(K, cr, ci, o);
#pragma unroll
        for (int j = 0; j < 4; j++)
          sts64(zb + ((a * 8 + warp) * ZROW + zphys(16 * t + 64 * j) + 2 * g) * 4, pk(o[j][0] * r, o[j][1] * r), pk(o[j][2] * r, o[j][3] * r));
      }
      wbar();
      uint4* tp = g_T1 + (size_t)(g * 16 + warp) * 1024 + b * 8;
#pragma unroll
      for (int nt = 0; nt < 2; nt++) {
        const int k = 16 * warp + 8 * nt + g, km = k == 0 ? 128 : 256 - k;
        uint32_t lo[4], hi[4];
#pragma unroll
        for (int a = 0; a < 2; a++) {
          const uint32_t rb = zb + (a * 8 + t) * ZROW * 4;
          float A[4], B[4];
          mma0(A, a8[a][0], a8[a][1], a8[a][2], a8[a][3], lds32(rb + zphys(k) * 4), lds32(rb + (4 * ZROW + zphys(k)) * 4));
          mma0(B, a8[a][0] ^ 0x80000000u, a8[a][1] ^ 0x80000000u, a8[a][2] ^ 0x80000000u, a8[a][3] ^ 0x80000000u,
               lds32(rb + zphys(km) * 4), lds32(rb + (4 * ZROW + zphys(km)) * 4));
#pragma unroll
          for (int e = 0; e < 2; e++) {
            float sr = A[e] + B[e], si = A[2 + e] + B[2 + e], dr = A[e] - B[e], di = A[2 + e] - B[2 + e];
            float c = vc[2 * nt + e], s = vs[2 * nt + e];
            float gr = dr * c + di * s, gi = di * c - dr * s;
            float lr = sr + gr, li = si + gi, hr = sr - gr, hii = si - gi;
            if (nt == 0 && e == 0) {
              const bool sp = warp == 0 && t == 0;
              lr = sp ? 2.f * B[0] : lr; li = sp ? 2.f * B[2] : li;
              hr = sp ? 2.f * (A[0] - A[2]) : hr; hii = sp ? 2.f * (A[0] + A[2]) : hii;
            }
            lo[2 * a + e] = pk(lr, li); hi[2 * a + e] = pk(hr, hii);
          }
        }
        const int w = (t + 4 * nt) ^ key;
        tp[w] = make_uint4(lo[0], lo[1], lo[2], lo[3]);
        tp[8 * 1024 + w] = make_uint4(hi[0], hi[1], hi[2], hi[3]);
      }
      asm volatile("fence.proxy.async.shared::cta;" ::: "memory");
      wbar();
      STAMP(1);
      if (tid == 0) {
        cnt_arrive(0);
        cnt_wait(0, base + NCTA);
        asm volatile("fence.proxy.async.global;" ::: "memory");
        mbar_expect(mb + MB_P2IN * 8, 16384);
#pragma unroll
        for (int j = 0; j < 4; j++) bulk_ld(zb + j * 4096, g_T1 + (size_t)b * 1024 + j * 256, 4096, mb + MB_P2IN * 8);
      }
      __syncwarp();
      STAMP(2);
    }
    {
      const uint32_t off = (8 * t + g) * 128 + ((warp ^ (2 * t + (g & 1))) << 4);
      mbar_wait(mb + MB_FILT * 8, 0);
      mbar_wait(mb + MB_P2IN * 8, 0);
      STAMP(3);
      uint32_t in[2][4][2], fw[2][4][2];
#pragma unroll
      for (int j = 0; j < 4; j++) {
        uint4 v = lds128(zb + off + j * 4096);
        in[0][j][0] = v.x; in[1][j][0] = v.y; in[0][j][1] = v.z; in[1][j][1] = v.w;
      }
#pragma unroll
      for (int j = 0; j < 4; j++) {
        uint4 v = lds128(sb + FILT_OFF + off + j * 4096);
        fw[0][j][0] = v.x; fw[1][j][0] = v.y; fw[0][j][1] = v.z; fw[1][j][1] = v.w;
      }
#pragma unroll
      for (int sg = 0; sg < 2; sg++) {
        float cr[2][4], ci[2][4], o[4][4];
        fft_s1(K, in[sg], cr, ci);
        fft_s2(K, cr, ci, o);
#pragma unroll
        for (int j = 0; j < 4; j++)
#pragma unroll
          for (int h = 0; h < 2; h++) {
            float fr = blo(fw[sg][j][h]), fi = bhi(fw[sg][j][h]), xr = o[j][2 * h], xi = o[j][2 * h + 1];
            in[sg][j][h] = pk(xr * fi + xi * fr, xr * fr - xi * fi);
          }
        fft_s1(K, in[sg], cr, ci);
        fft_s2(K, cr, ci, o);
#pragma unroll
        for (int j = 0; j < 4; j++) { in[sg][j][0] = pk(o[j][0], o[j][1]); in[sg][j][1] = pk(o[j][2], o[j][3]); }
      }
#pragma unroll
      for (int j = 0; j < 4; j++) sts128(zb + off + j * 4096, make_uint4(in[0][j][0], in[1][j][0], in[0][j][1], in[1][j][1]));
      wbar();
#pragma unroll
      for (int j = 0; j < 4; j++) g_T2[(size_t)b * 1024 + j * 256 + tid] = lds128(zb + j * 4096 + tid * 16);
      wbar();
      STAMP(4);
      if (tid == 0) cnt_arrive(1);
    }
    {
      uint32_t a8[2][4]; float vc[4], vs[4];
#pragma unroll
      for (int a = 0; a < 2; a++)
#pragma unroll
        for (int u = 0; u < 2; u++) {
          float c, s; cs<2048>((t + 4 * u) * (256 * g + 2 * b + a), c, s);
          a8[a][2 * u] = pk(c, s); a8[a][2 * u + 1] = pk(-s, c);
        }
#pragma unroll
      for (int i = 0; i < 4; i++) cs<512>(16 * warp + 4 * t + i + 128, vc[i], vs[i]);
      if (tid == 0) cnt_wait(1, base + NCTA);
      wbar();
      STAMP(5);
      const uint4* tp = g_T2 + (size_t)(t * 16 + warp) * 1024 + b * 8 + (g ^ key);
      uint4 L0 = ldcg128(tp), L1 = ldcg128(tp + 64 * 1024), H0 = ldcg128(tp + 8 * 1024), H1 = ldcg128(tp + 72 * 1024);
      const uint32_t l0[4] = {L0.x, L0.y, L0.z, L0.w}, l1[4] = {L1.x, L1.y, L1.z, L1.w}, h0[4] = {H0.x, H0.y, H0.z, H0.w}, h1[4] = {H1.x, H1.y, H1.z, H1.w};
#pragma unroll
      for (int a = 0; a < 2; a++) {
        uint32_t zf[4], zm[4];
#pragma unroll
        for (int sg = 0; sg < 2; sg++) {
          float A[4], B[4];
          mma0(A, a8[a][0], a8[a][1], a8[a][2], a8[a][3], l0[2 * a + sg], l1[2 * a + sg]);
          mma0(B, a8[a][0], a8[a][1], a8[a][2], a8[a][3], h0[2 * a + sg], h1[2 * a + sg]);
#pragma unroll
          for (int e = 0; e < 2; e++) {
            const int i = 2 * e + sg;
            float sr = A[2 + e] + B[2 + e], si = A[e] + B[e], dr = A[2 + e] - B[2 + e], di = A[e] - B[e];
            float gr = dr * vc[i] - di * vs[i], gi = di * vc[i] + dr * vs[i];
            float fr = sr + gr, fi = si + gi, mr = sr - gr, mi = gi - si;
            if (i == 0) {
              const bool sp = warp == 0 && t == 0;
              fr = sp ? B[2] : fr; fi = sp ? -B[2] : fi;
              mr = sp ? 2.f * A[2] : mr; mi = sp ? -2.f * A[0] : mi;
            }
            zf[i] = pk(fi, fr); zm[i] = pk(mi, mr);
          }
        }
        const uint32_t rb = zb + (a * 8 + g) * ZROW * 4;
        const int k0 = 16 * warp + 4 * t;
        sts128(rb + zphys(k0) * 4, make_uint4(zf[0], zf[1], zf[2], zf[3]));
        sts32(rb + zphys(k0 == 0 ? 128 : 256 - k0) * 4, zm[0]);
        sts32(rb + zphys(255 - k0) * 4, zm[1]);
        sts32(rb + zphys(254 - k0) * 4, zm[2]);
        sts32(rb + zphys(253 - k0) * 4, zm[3]);
      }
      wbar();
#pragma unroll
      for (int a = 0; a < 2; a++) {
        uint32_t in[4][2];
#pragma unroll
        for (int j = 0; j < 4; j++) { uint2 v = lds64(zb + ((a * 8 + warp) * ZROW + zphys(16 * t + 64 * j) + 2 * g) * 4); in[j][0] = v.x; in[j][1] = v.y; }
        float cr[2][4], ci[2][4], o[4][4];
        fft_s1(K, in, cr, ci);
        fft_s2(K, cr, ci, o);
        float s1 = 0.f, s2 = 0.f;
        uint2* hp = (uint2*)g_h + (size_t)(256 * warp + 2 * b + a) * 128 + 8 * t + g;
#pragma unroll
        for (int j = 0; j < 4; j++) {
          uint32_t hw[2];
#pragma unroll
          for (int h = 0; h < 2; h++) {
            uint32_t y = pk(o[j][2 * h + 1], o[j][2 * h]);
            hw[h] = pk(blo(xw[a][j][h]) + blo(y), bhi(xw[a][j][h]) + bhi(y));
            float u0 = blo(hw[h]) - mean[a], u1 = bhi(hw[h]) - mean[a];
            o[j][2 * h] = u0; o[j][2 * h + 1] = u1;
            s1 += u0 + u1; s2 = fmaf(u0, u0, fmaf(u1, u1, s2));
          }
          hp[32 * j] = make_uint2(hw[0], hw[1]);
        }
#pragma unroll
        for (int m = 1; m < 32; m <<= 1) { s1 += __shfl_xor_sync(0xffffffffu, s1, m); s2 += __shfl_xor_sync(0xffffffffu, s2, m); }
        const float mu = s1 * (1.f / 512.f), var = fmaxf(s2 * (1.f / 512.f) - mu * mu, 0.f);
        const float r1 = rsqrtf(var + 1e-5f);
        const float r = r1 * rsqrtf(var * r1 * r1 + 1e-5f);
        char* np = (char*)g_Hn + (size_t)b * 4096 + (t >> 1) * 2048 + a * 1024 + warp * 128 + ((((t & 1) * 4 + (g >> 1)) ^ warp) << 4) + (g & 1) * 8;
#pragma unroll
        for (int j = 0; j < 4; j++)
          *(uint2*)(np + (size_t)j * 128 * 4096) = make_uint2(pk((o[j][0] - mu) * r, (o[j][1] - mu) * r), pk((o[j][2] - mu) * r, (o[j][3] - mu) * r));
      }
      asm volatile("fence.proxy.async.shared::cta;" ::: "memory");
      wbar();
      STAMP(6);
      if (tid == 0) { cnt_arrive(2 + (b >> 6)); sts32(sb + BASE_OFF, base); mbar_arrive(mb + MB_P3DONE * 8); }
    }
    const int wg = warp >> 2;
    const uint32_t peer_sb = mapa(sb, rank ^ 1);
    {
      uint32_t bias[11];
#pragma unroll
      for (int j = 0; j < 11; j++) bias[j] = (11 * ot + j < 172) ? __ldg(b1 + (11 * ot + j) * 4 + t) : 0u;
      float acc[44];
      const uint64_t da0 = mkdesc(sb + RING_OFF + wg * 2048, 0, 1024, 1), db0 = mkdesc(sb, 1408, 128, 0);
      mbar_wait(mb + MB_W1 * 8, 0);
#pragma unroll
      for (int i = 0; i < 32; i++) {
        mbar_wait(mb + (MB_FULL + i % NST) * 8, (i / NST) & 1);
        if (i == 0) STAMP(7);
        asm volatile("wgmma.fence.sync.aligned;" ::: "memory");
        wgmma_n88_ss<1, 1>(acc, da0 + (((i % NST) * 8192) >> 4), db0 + ((2 * i * 2816) >> 4), i > 0);
        wgmma_n88_ss<1, 1>(acc, da0 + (((i % NST) * 8192 + 4096) >> 4), db0 + (((2 * i + 1) * 2816) >> 4), 1);
        asm volatile("wgmma.commit_group.sync.aligned;" ::: "memory");
        if (i > 0) {
          asm volatile("wgmma.wait_group.sync.aligned 1;" ::: "memory");
          if ((tid & 127) == 0) { mbar_arrive(mb + (MB_EMPTY + (i - 1) % NST) * 8); if (i == 4) mbar_arrive_cluster(peer_sb + BAR_OFF + MB_PEER1 * 8); }
        }
      }
      asm volatile("wgmma.wait_group.sync.aligned 0;" ::: "memory");
#pragma unroll
      for (int i = 0; i < 44; i++) asm volatile("" : "+f"(acc[i]) :: "memory");
      if ((tid & 127) == 0) mbar_arrive(mb + (MB_EMPTY + 31 % NST) * 8);
      STAMP(8);
      float keep[22], send[22];
#pragma unroll
      for (int j = 0; j < 11; j++) {
        keep[2 * j] = rank ? acc[4 * j + 2] : acc[4 * j]; keep[2 * j + 1] = rank ? acc[4 * j + 3] : acc[4 * j + 1];
        send[2 * j] = rank ? acc[4 * j] : acc[4 * j + 2]; send[2 * j + 1] = rank ? acc[4 * j + 1] : acc[4 * j + 3];
      }
      mbar_wait_cluster(mb + MB_PEER1 * 8, 0);
#pragma unroll
      for (int j = 0; j < 5; j++) st_async4(peer_sb + j * 4096 + tid * 16, send[4 * j], send[4 * j + 1], send[4 * j + 2], send[4 * j + 3], peer_sb + BAR_OFF + MB_X1 * 8);
      st_async2(peer_sb + 5 * 4096 + tid * 8, send[20], send[21], peer_sb + BAR_OFF + MB_X1 * 8);
      mbar_wait_cluster(mb + MB_X1 * 8, 0);
#pragma unroll
      for (int j = 0; j < 5; j++) {
        uint4 v = lds128(sb + j * 4096 + tid * 16);
        keep[4 * j] += __uint_as_float(v.x); keep[4 * j + 1] += __uint_as_float(v.y); keep[4 * j + 2] += __uint_as_float(v.z); keep[4 * j + 3] += __uint_as_float(v.w);
      }
      { uint2 v = lds64(sb + 5 * 4096 + tid * 8); keep[20] += __uint_as_float(v.x); keep[21] += __uint_as_float(v.y); }
      uint32_t* up = (uint32_t*)g_U + ((size_t)dt * 172 + 11 * ot) * 512 + (4 * (warp >> 1) + (g >> 1)) * 32 + (2 * (2 * (warp & 1) + rank) + (g & 1)) * 4 + t;
#pragma unroll
      for (int j = 0; j < 11; j++) {
        uint32_t v = pk(gelu(keep[2 * j] + blo(bias[j])), gelu(keep[2 * j + 1] + bhi(bias[j])));
        if (11 * ot + j < 172) up[j * 512] = v;
      }
      asm volatile("fence.proxy.async.shared::cta;" ::: "memory");
      wbar();
      STAMP(9);
      if (tid == 0) { cnt_arrive(4 + dt); mbar_arrive(mb + MB_X1DONE * 8); }
    }
    {
      const int srow = 128 * ot + 16 * warp + 8 * rank + g;
      float acc[64];
      const uint64_t da0 = mkdesc(sb + wg * 4096, 0, 1024, 1), db0 = mkdesc(sb + RING_OFF, 2048, 128, 0);
      uint4 hv[4]; float bias2 = 0.f;
#pragma unroll
      for (int i = 0; i < 22; i++) {
        mbar_wait(mb + (MB_W2 + i) * 8, 0);
        mbar_wait(mb + (MB_FULL + (32 + i) % NST) * 8, ((32 + i) / NST) & 1);
        if (i == 0) STAMP(10);
        asm volatile("wgmma.fence.sync.aligned;" ::: "memory");
        wgmma_n128_ss<1, 0>(acc, da0 + ((((i + 3) % 22) * 8192) >> 4), db0 + ((((32 + i) % NST) * 8192) >> 4), i > 0);
        if (i < 21) wgmma_n128_ss<1, 0>(acc, da0 + ((((i + 3) % 22) * 8192 + 2048) >> 4), db0 + ((((32 + i) % NST) * 8192 + 4096) >> 4), 1);
        asm volatile("wgmma.commit_group.sync.aligned;" ::: "memory");
        if (i == 8) {
#pragma unroll
          for (int j = 0; j < 4; j++) hv[j] = ldcg128(g_h + (size_t)srow * 64 + dt * 16 + 4 * j + t);
          bias2 = __uint_as_float((uint32_t)__ldg(b2 + srow) << 16);
        }
        if (i > 0) {
          asm volatile("wgmma.wait_group.sync.aligned 1;" ::: "memory");
          if ((tid & 127) == 0) { if (i < 22 - NST + 1) mbar_arrive(mb + (MB_EMPTY + (32 + i - 1) % NST) * 8); if (i == 4) mbar_arrive_cluster(peer_sb + BAR_OFF + MB_PEER2 * 8); }
        }
      }
      asm volatile("wgmma.wait_group.sync.aligned 0;" ::: "memory");
#pragma unroll
      for (int i = 0; i < 64; i++) asm volatile("" : "+f"(acc[i]) :: "memory");
      STAMP(11);
      mbar_wait_cluster(mb + MB_PEER2 * 8, 0);
#pragma unroll
      for (int j = 0; j < 8; j++)
        st_async4(peer_sb + 3 * 8192 + j * 4096 + tid * 16, rank ? acc[8 * j] : acc[8 * j + 2], rank ? acc[8 * j + 1] : acc[8 * j + 3],
                  rank ? acc[8 * j + 4] : acc[8 * j + 6], rank ? acc[8 * j + 5] : acc[8 * j + 7], peer_sb + BAR_OFF + MB_X2 * 8);
      float keep[32];
#pragma unroll
      for (int j = 0; j < 16; j++) {
        const uint32_t hw = j % 4 == 0 ? hv[j / 4].x : j % 4 == 1 ? hv[j / 4].y : j % 4 == 2 ? hv[j / 4].z : hv[j / 4].w;
        keep[2 * j] = (rank ? acc[4 * j + 2] : acc[4 * j]) + (bias2 + blo(hw));
        keep[2 * j + 1] = (rank ? acc[4 * j + 3] : acc[4 * j + 1]) + (bias2 + bhi(hw));
      }
      mbar_wait_cluster(mb + MB_X2 * 8, 0);
#pragma unroll
      for (int j = 0; j < 4; j++) {
        uint4 v = lds128(sb + 3 * 8192 + (2 * j) * 4096 + tid * 16), w = lds128(sb + 3 * 8192 + (2 * j + 1) * 4096 + tid * 16);
        out[(size_t)srow * 64 + dt * 16 + 4 * j + t] =
            make_uint4(pk(keep[8 * j] + __uint_as_float(v.x), keep[8 * j + 1] + __uint_as_float(v.y)), pk(keep[8 * j + 2] + __uint_as_float(v.z), keep[8 * j + 3] + __uint_as_float(v.w)),
                       pk(keep[8 * j + 4] + __uint_as_float(w.x), keep[8 * j + 5] + __uint_as_float(w.y)), pk(keep[8 * j + 6] + __uint_as_float(w.z), keep[8 * j + 7] + __uint_as_float(w.w)));
      }
      STAMP(12);
    }
  } else {
    const int pw = warp - 8;
    if (pw == 0) {
      if (lane == 0) {
        for (int i = 0; i < NST; i++) { mbar_init(mb + (MB_FULL + i) * 8, 1); mbar_init(mb + (MB_EMPTY + i) * 8, 2); }
        for (int i = 0; i < 22; i++) mbar_init(mb + (MB_W2 + i) * 8, 1);
        mbar_init(mb + MB_P2IN * 8, 1); mbar_init(mb + MB_FILT * 8, 128); mbar_init(mb + MB_W1 * 8, 128);
        mbar_init(mb + MB_PEER1 * 8, 2); mbar_init(mb + MB_X1 * 8, 1); mbar_init(mb + MB_X1DONE * 8, 1);
        mbar_init(mb + MB_PEER2 * 8, 2); mbar_init(mb + MB_X2 * 8, 1); mbar_init(mb + MB_P3DONE * 8, 1);
        mbar_expect(mb + MB_X1 * 8, 22528); mbar_expect(mb + MB_X2 * 8, 32768);
        asm volatile("fence.mbarrier_init.release.cluster;" ::: "memory");
      }
      __syncwarp();
    }
    STAMP(0);
    asm volatile("bar.sync 2, 128;" ::: "memory");
    asm volatile("barrier.cluster.arrive.relaxed.aligned;" ::: "memory");
    {
      const int j1 = b >> 4, q = b & 15, slot = lane & 15, h = lane >> 4;
      const bool hi = q >= 8;
      const int k = 16 * (q & 7) + slot, col = hi ? 256 - k : (k == 0 ? 128 : k);
#pragma unroll 1
      for (int it = 0; it < 2; it++) {
        uint32_t vr[16], vi[16];
#pragma unroll
        for (int n = 0; n < 16; n++) {
          const int c = pw * 32 + it * 16 + n;
          int j = j1 + 8 * (2 * c + h);
          if (hi) j = (2048 - j) & 2047;
          vr[n] = __ldg(wr + j * DF + col); vi[n] = __ldg(wi + j * DF + col);
        }
#pragma unroll
        for (int n = 0; n < 16; n++) {
          const int c = pw * 32 + it * 16 + n;
          sts32(sb + FILT_OFF + c * 128 + (((slot >> 1) ^ (((c >> 3) & 3) * 2 + (c & 1))) << 4) + h * 8 + (slot & 1) * 4,
                (vr[n] | (vi[n] << 16)) ^ (hi ? 0x80000000u : 0u));
        }
      }
      mbar_arrive(mb + MB_FILT * 8);
    }
    STAMP(1);
    {
      const int s1 = lane & 7, lo = lane >> 3;
      const char* src = w1 + (size_t)(256 * s1 + 128 * rank + pw) * (F_ * 2) + (11 * ot + lo) * 16;
      uint32_t dst = sb + pw * 1408 + lo * 128 + s1 * 16;
      const int n0 = 11 * ot + lo < 172 ? 16 : 0, n1 = 11 * ot + lo + 4 < 172 ? 16 : 0, n2 = 11 * ot + lo + 8 < 172 ? 16 : 0;
#pragma unroll 1
      for (int it = 0; it < 32; it++) {
        asm volatile("cp.async.cg.shared.global [%0], [%1], 16, %2;" :: "r"(dst), "l"(n0 ? src : w1), "r"(n0) : "memory");
        asm volatile("cp.async.cg.shared.global [%0], [%1], 16, %2;" :: "r"(dst + 512), "l"(n1 ? src + 64 : w1), "r"(n1) : "memory");
        if (lo < 3) asm volatile("cp.async.cg.shared.global [%0], [%1], 16, %2;" :: "r"(dst + 1024), "l"(n2 ? src + 128 : w1), "r"(n2) : "memory");
        asm volatile("cp.async.commit_group;" ::: "memory");
        asm volatile("cp.async.wait_group %0;" :: "n"(W1_INFLIGHT) : "memory");
        src += 4 * F_ * 2; dst += 4 * 1408;
      }
      if (lane == 0) asm volatile("cp.async.bulk.prefetch.L2.global [%0], %1;" :: "l"(w2 + (size_t)(b * 4 + pw) * 11008), "r"(11008) : "memory");
      asm volatile("cp.async.wait_group 0;" ::: "memory");
      asm volatile("fence.proxy.async.shared::cta;" ::: "memory");
      mbar_arrive(mb + MB_W1 * 8);
    }
    STAMP(2);
    asm volatile("barrier.cluster.wait.aligned;" ::: "memory");
    if (pw == 0) {
      mbar_wait(mb + MB_P3DONE * 8, 0);
      const unsigned base = lds32(sb + BASE_OFF);
      if (lane == 0) cnt_wait(2 + rank, (base >> 1) + 64);
      __syncwarp();
      STAMP(3);
      asm volatile("fence.proxy.async.global;" ::: "memory");
      const char* hsrc = (const char*)g_Hn + ((size_t)dt * 128 + 64 * rank) * 4096;
      int nw2 = 0;
#pragma unroll
      for (int i = 0; i < 32 + NST; i++) {
        if (i >= NST) mbar_wait(mb + (MB_EMPTY + i % NST) * 8, ((i / NST) & 1) ^ 1);
        if (elect()) {
          if (i < 32) { mbar_expect(mb + (MB_FULL + i % NST) * 8, 8192); bulk_ld(sb + RING_OFF + (i % NST) * 8192, hsrc + i * 8192, 8192, mb + (MB_FULL + i % NST) * 8); }
        }
        if (i >= W2_START) {
#pragma unroll
          for (int rep = 0; rep < 19; rep++) {
            if (nw2 < 19 && (nw2 + 4) * 8192 <= (i - NST + 1) * 5632 && (rep < W2_RATE || i == 31 + NST)) {
              if (elect()) { mbar_expect(mb + (MB_W2 + nw2) * 8, 8192); tma3d(sb + (nw2 + 3) * 8192, &tmW2, 0, 688 * rank + 32 * nw2, 2 * ot, mb + (MB_W2 + nw2) * 8); }
              nw2++;
            }
          }
        }
      }
      mbar_wait(mb + MB_X1DONE * 8, 0);
      if (elect()) {
#pragma unroll
        for (int n = 19; n < 22; n++) { mbar_expect(mb + (MB_W2 + n) * 8, 8192); tma3d(sb + (n - 19) * 8192, &tmW2, 0, 688 * rank + 32 * n, 2 * ot, mb + (MB_W2 + n) * 8); }
      }
      STAMP(4);
      if (lane == 0) cnt_wait(4 + dt, (base >> 2) + 32);
      __syncwarp();
      STAMP(5);
      asm volatile("fence.proxy.async.global;" ::: "memory");
      const char* usrc = (const char*)g_U + ((size_t)dt * 172 + 86 * rank) * 2048;
#pragma unroll
      for (int i = 0; i < 22; i++) {
        if (i >= NST) mbar_wait(mb + (MB_EMPTY + (32 + i) % NST) * 8, (((32 + i) / NST) & 1) ^ 1);
        if (elect()) {
          const int bytes = i < 21 ? 8192 : 4096;
          mbar_expect(mb + (MB_FULL + (32 + i) % NST) * 8, bytes);
          bulk_ld(sb + RING_OFF + ((32 + i) % NST) * 8192, usrc + i * 8192, bytes, mb + (MB_FULL + (32 + i) % NST) * 8);
        }
      }
      STAMP(6);
    }
  }
}

typedef CUresult (*EncodeFn)(CUtensorMap*, CUtensorMapDataType, cuuint32_t, void*, const cuuint64_t*, const cuuint64_t*, const cuuint32_t*,
                             const cuuint32_t*, CUtensorMapInterleave, CUtensorMapSwizzle, CUtensorMapL2promotion, CUtensorMapFloatOOBfill);

extern "C" void kernel_launch(void* const* d_in, const int* in_sizes, int n_in, void* d_out, int out_size) {
  static EncodeFn enc = nullptr;
  if (!enc) {
    void* fn = nullptr; cudaDriverEntryPointQueryResult st;
    cudaGetDriverEntryPoint("cuTensorMapEncodeTiled", &fn, cudaEnableDefault, &st);
    enc = (EncodeFn)fn;
    cudaFuncSetAttribute(fused_kernel, cudaFuncAttributeMaxDynamicSharedMemorySize, SMEM_BYTES);
  }
  CUtensorMap tm;
  {
    cuuint64_t dims[3] = {64, (cuuint64_t)F_, S_ / 64}, strides[2] = {S_ * 2, 128};
    cuuint32_t box[3] = {64, 32, 2}, es[3] = {1, 1, 1};
    enc(&tm, CU_TENSOR_MAP_DATA_TYPE_BFLOAT16, 3, d_in[6], dims, strides, box, es, CU_TENSOR_MAP_INTERLEAVE_NONE, CU_TENSOR_MAP_SWIZZLE_128B,
        CU_TENSOR_MAP_L2_PROMOTION_L2_256B, CU_TENSOR_MAP_FLOAT_OOB_FILL_NONE);
  }
  fused_kernel<<<NCTA, 384, SMEM_BYTES, cudaStreamPerThread>>>(tm, (const uint2*)d_in[0], (const unsigned short*)d_in[1], (const unsigned short*)d_in[2],
                                          (const char*)d_in[4], (const uint32_t*)d_in[5], (const char*)d_in[6], (const unsigned short*)d_in[7], (uint4*)d_out);
}
```

```cpp
#include <cuda_runtime.h>
#include <cuda.h>
#include <cuda_bf16.h>
#include <stdint.h>
#define W1_LATE 1
#define W1_PROMO CU_TENSOR_MAP_L2_PROMOTION_NONE
#define W2_RATE 1
template<int TA, int TB> __device__ __forceinline__ void wgmma_n88_ss(float (&d)[44], uint64_t da, uint64_t db, int sd) {
  asm volatile("{\n.reg .pred p;\nsetp.ne.b32 p, %46, 0;\n"
    "wgmma.mma_async.sync.aligned.m64n88k16.f32.bf16.bf16 {%0, %1, %2, %3, %4, %5, %6, %7, %8, %9, %10, %11, %12, %13, %14, %15, %16, %17, %18, %19, %20, %21, %22, %23, %24, %25, %26, %27, %28, %29, %30, %31, %32, %33, %34, %35, %36, %37, %38, %39, %40, %41, %42, %43}, %44, %45, p, 1, 1, %47, %48;\n}\n"
    : "+f"(d[0]), "+f"(d[1]), "+f"(d[2]), "+f"(d[3]), "+f"(d[4]), "+f"(d[5]), "+f"(d[6]), "+f"(d[7]), "+f"(d[8]), "+f"(d[9]), "+f"(d[10]), "+f"(d[11]), "+f"(d[12]), "+f"(d[13]), "+f"(d[14]), "+f"(d[15]), "+f"(d[16]), "+f"(d[17]), "+f"(d[18]), "+f"(d[19]), "+f"(d[20]), "+f"(d[21]), "+f"(d[22]), "+f"(d[23]), "+f"(d[24]), "+f"(d[25]), "+f"(d[26]), "+f"(d[27]), "+f"(d[28]), "+f"(d[29]), "+f"(d[30]), "+f"(d[31]), "+f"(d[32]), "+f"(d[33]), "+f"(d[34]), "+f"(d[35]), "+f"(d[36]), "+f"(d[37]), "+f"(d[38]), "+f"(d[39]), "+f"(d[40]), "+f"(d[41]), "+f"(d[42]), "+f"(d[43]) : "l"(da), "l"(db), "r"(sd), "n"(TA), "n"(TB));
}
template<int TA, int TB> __device__ __forceinline__ void wgmma_n128_ss(float (&d)[64], uint64_t da, uint64_t db, int sd) {
  asm volatile("{\n.reg .pred p;\nsetp.ne.b32 p, %66, 0;\n"
    "wgmma.mma_async.sync.aligned.m64n128k16.f32.bf16.bf16 {%0, %1, %2, %3, %4, %5, %6, %7, %8, %9, %10, %11, %12, %13, %14, %15, %16, %17, %18, %19, %20, %21, %22, %23, %24, %25, %26, %27, %28, %29, %30, %31, %32, %33, %34, %35, %36, %37, %38, %39, %40, %41, %42, %43, %44, %45, %46, %47, %48, %49, %50, %51, %52, %53, %54, %55, %56, %57, %58, %59, %60, %61, %62, %63}, %64, %65, p, 1, 1, %67, %68;\n}\n"
    : "+f"(d[0]), "+f"(d[1]), "+f"(d[2]), "+f"(d[3]), "+f"(d[4]), "+f"(d[5]), "+f"(d[6]), "+f"(d[7]), "+f"(d[8]), "+f"(d[9]), "+f"(d[10]), "+f"(d[11]), "+f"(d[12]), "+f"(d[13]), "+f"(d[14]), "+f"(d[15]), "+f"(d[16]), "+f"(d[17]), "+f"(d[18]), "+f"(d[19]), "+f"(d[20]), "+f"(d[21]), "+f"(d[22]), "+f"(d[23]), "+f"(d[24]), "+f"(d[25]), "+f"(d[26]), "+f"(d[27]), "+f"(d[28]), "+f"(d[29]), "+f"(d[30]), "+f"(d[31]), "+f"(d[32]), "+f"(d[33]), "+f"(d[34]), "+f"(d[35]), "+f"(d[36]), "+f"(d[37]), "+f"(d[38]), "+f"(d[39]), "+f"(d[40]), "+f"(d[41]), "+f"(d[42]), "+f"(d[43]), "+f"(d[44]), "+f"(d[45]), "+f"(d[46]), "+f"(d[47]), "+f"(d[48]), "+f"(d[49]), "+f"(d[50]), "+f"(d[51]), "+f"(d[52]), "+f"(d[53]), "+f"(d[54]), "+f"(d[55]), "+f"(d[56]), "+f"(d[57]), "+f"(d[58]), "+f"(d[59]), "+f"(d[60]), "+f"(d[61]), "+f"(d[62]), "+f"(d[63]) : "l"(da), "l"(db), "r"(sd), "n"(TA), "n"(TB));
}

constexpr int S_ = 2048, D_ = 512, F_ = 1376, DF = 257;
constexpr int NCTA = 128;
constexpr int W_BYTES = 180224;
constexpr int RING_OFF = W_BYTES;
constexpr int NST = 6;
constexpr int BAR_OFF = RING_OFF + NST * 8192;
constexpr int SMEM_BYTES = BAR_OFF + 1024;
constexpr int FILT_OFF = RING_OFF;
constexpr int XCH_OFF = RING_OFF + 16384;
constexpr int ZROW = 328;
constexpr int MB_FULL = 0, MB_EMPTY = 6, MB_W2 = 12, MB_P2IN = 34, MB_FILT = 35, MB_W1 = 36, MB_PEER1 = 37, MB_X1 = 38,
              MB_X1DONE = 39, MB_PEER2 = 40, MB_X2 = 41, MB_P3DONE = 42, MB_W1T = 43;
constexpr int BASE_OFF = BAR_OFF + 960;
#define W2_START 18

__device__ uint4 g_T1[NCTA * 1024];
__device__ uint4 g_T2[NCTA * 1024];
__device__ uint4 g_h[S_ * D_ / 8];
__device__ uint4 g_Hn[4 * 128 * 256];
__device__ uint4 g_U[4 * 172 * 128];
__device__ unsigned g_cnt[8 * 64];
#define STAMP(i)

__device__ __forceinline__ void mbar_init(uint32_t b, int c) { asm volatile("mbarrier.init.shared::cta.b64 [%0], %1;" :: "r"(b), "r"(c) : "memory"); }
__device__ __forceinline__ void mbar_expect(uint32_t b, int bytes) { asm volatile("mbarrier.arrive.expect_tx.shared::cta.b64 _, [%0], %1;" :: "r"(b), "r"(bytes) : "memory"); }
__device__ __forceinline__ void mbar_arrive(uint32_t b) { asm volatile("mbarrier.arrive.shared::cta.b64 _, [%0];" :: "r"(b) : "memory"); }
__device__ __forceinline__ void mbar_arrive_cluster(uint32_t remote) { asm volatile("mbarrier.arrive.release.cluster.shared::cluster.b64 _, [%0];" :: "r"(remote) : "memory"); }
__device__ __forceinline__ uint32_t mapa(uint32_t a, uint32_t cta) { uint32_t r; asm("mapa.shared::cluster.u32 %0, %1, %2;" : "=r"(r) : "r"(a), "r"(cta)); return r; }
__device__ __forceinline__ void mbar_wait(uint32_t b, int ph) {
  asm volatile("{\n.reg .pred p;\n.reg .u32 n;\nmov.u32 n, 0;\nL_W:\n"
               "mbarrier.try_wait.parity.shared::cta.b64 p, [%0], %1;\n@p bra L_D;\n"
               "add.u32 n, n, 1;\nsetp.lt.u32 p, n, 4000000;\n@p bra L_W;\ntrap;\nL_D:\n}" :: "r"(b), "r"(ph) : "memory");
}
__device__ __forceinline__ void mbar_wait_cluster(uint32_t b, int ph) {
  asm volatile("{\n.reg .pred p;\n.reg .u32 n;\nmov.u32 n, 0;\nL_W:\n"
               "mbarrier.try_wait.parity.acquire.cluster.shared::cta.b64 p, [%0], %1;\n@p bra L_D;\n"
               "add.u32 n, n, 1;\nsetp.lt.u32 p, n, 4000000;\n@p bra L_W;\ntrap;\nL_D:\n}" :: "r"(b), "r"(ph) : "memory");
}
__device__ __forceinline__ void bulk_ld(uint32_t dst, const void* src, int bytes, uint32_t bar) {
  asm volatile("cp.async.bulk.shared::cluster.global.mbarrier::complete_tx::bytes [%0], [%1], %2, [%3];" :: "r"(dst), "l"(src), "r"(bytes), "r"(bar) : "memory");
}
__device__ __forceinline__ void tma3d(uint32_t dst, const CUtensorMap* tm, int c0, int c1, int c2, uint32_t bar) {
  asm volatile("cp.async.bulk.tensor.3d.shared::cluster.global.mbarrier::complete_tx::bytes [%0], [%1, {%3, %4, %5}], [%2];"
               :: "r"(dst), "l"(tm), "r"(bar), "r"(c0), "r"(c1), "r"(c2) : "memory");
}
__device__ __forceinline__ bool elect() { uint32_t p; asm volatile("{.reg .pred p; elect.sync _|p, 0xffffffff; selp.b32 %0, 1, 0, p;}" : "=r"(p)); return p; }
__device__ __forceinline__ uint64_t mkdesc(uint32_t addr, uint32_t lbo, uint32_t sbo, uint32_t sw) {
  return (uint64_t)((addr & 0x3FFFF) >> 4) | ((uint64_t)(lbo >> 4) << 16) | ((uint64_t)(sbo >> 4) << 32) | ((uint64_t)sw << 62);
}
__device__ __forceinline__ uint32_t pk(float lo, float hi) { uint32_t r; asm("cvt.rn.bf16x2.f32 %0, %1, %2;" : "=r"(r) : "f"(hi), "f"(lo)); return r; }
__device__ __forceinline__ float blo(uint32_t w) { return __uint_as_float(w << 16); }
__device__ __forceinline__ float bhi(uint32_t w) { return __uint_as_float(w & 0xffff0000u); }
__device__ __forceinline__ void mma(float (&c)[4], uint32_t a0, uint32_t a1, uint32_t a2, uint32_t a3, uint32_t b0, uint32_t b1) {
  asm("mma.sync.aligned.m16n8k16.row.col.f32.bf16.bf16.f32 {%0,%1,%2,%3}, {%4,%5,%6,%7}, {%8,%9}, {%0,%1,%2,%3};"
      : "+f"(c[0]), "+f"(c[1]), "+f"(c[2]), "+f"(c[3]) : "r"(a0), "r"(a1), "r"(a2), "r"(a3), "r"(b0), "r"(b1));
}
__device__ __forceinline__ void mma0(float (&c)[4], uint32_t a0, uint32_t a1, uint32_t a2, uint32_t a3, uint32_t b0, uint32_t b1) {
  asm("mma.sync.aligned.m16n8k16.row.col.f32.bf16.bf16.f32 {%0,%1,%2,%3}, {%4,%5,%6,%7}, {%8,%9}, {%10,%10,%10,%10};"
      : "=f"(c[0]), "=f"(c[1]), "=f"(c[2]), "=f"(c[3]) : "r"(a0), "r"(a1), "r"(a2), "r"(a3), "r"(b0), "r"(b1), "f"(0.f));
}
__device__ __forceinline__ void wbar() { asm volatile("bar.sync 1, 256;" ::: "memory"); }
__device__ __forceinline__ void sts32(uint32_t a, uint32_t v) { asm volatile("st.shared.b32 [%0], %1;" :: "r"(a), "r"(v) : "memory"); }
__device__ __forceinline__ void sts64(uint32_t a, uint32_t x, uint32_t y) { asm volatile("st.shared.v2.b32 [%0], {%1,%2};" :: "r"(a), "r"(x), "r"(y) : "memory"); }
__device__ __forceinline__ void sts128(uint32_t a, uint4 v) { asm volatile("st.shared.v4.b32 [%0], {%1,%2,%3,%4};" :: "r"(a), "r"(v.x), "r"(v.y), "r"(v.z), "r"(v.w) : "memory"); }
__device__ __forceinline__ uint32_t lds32(uint32_t a) { uint32_t v; asm volatile("ld.shared.b32 %0, [%1];" : "=r"(v) : "r"(a) : "memory"); return v; }
__device__ __forceinline__ uint2 lds64(uint32_t a) { uint2 v; asm volatile("ld.shared.v2.b32 {%0,%1}, [%2];" : "=r"(v.x), "=r"(v.y) : "r"(a) : "memory"); return v; }
__device__ __forceinline__ uint4 lds128(uint32_t a) { uint4 v; asm volatile("ld.shared.v4.b32 {%0,%1,%2,%3}, [%4];" : "=r"(v.x), "=r"(v.y), "=r"(v.z), "=r"(v.w) : "r"(a) : "memory"); return v; }
__device__ __forceinline__ uint4 ldcg128(const void* p) { uint4 v; asm volatile("ld.global.cg.v4.b32 {%0,%1,%2,%3}, [%4];" : "=r"(v.x), "=r"(v.y), "=r"(v.z), "=r"(v.w) : "l"(p) : "memory"); return v; }
__device__ __forceinline__ void st_async4(uint32_t a, float x, float y, float z, float w, uint32_t bar) {
  asm volatile("st.async.weak.shared::cluster.mbarrier::complete_tx::bytes.v4.f32 [%0], {%1,%2,%3,%4}, [%5];" :: "r"(a), "f"(x), "f"(y), "f"(z), "f"(w), "r"(bar) : "memory");
}
__device__ __forceinline__ void st_async2(uint32_t a, float x, float y, uint32_t bar) {
  asm volatile("st.async.weak.shared::cluster.mbarrier::complete_tx::bytes.v2.f32 [%0], {%1,%2}, [%3];" :: "r"(a), "f"(x), "f"(y), "r"(bar) : "memory");
}
__device__ __forceinline__ void cnt_arrive(int i) { asm volatile("red.release.gpu.global.add.u32 [%0], 1;" :: "l"(&g_cnt[i * 64]) : "memory"); }
__device__ __forceinline__ void cnt_wait(int i, unsigned target) {
  unsigned v; int n = 0;
  do { asm volatile("ld.acquire.gpu.global.u32 %0, [%1];" : "=r"(v) : "l"(&g_cnt[i * 64]) : "memory"); if (++n > 2000000) __trap(); } while ((int)(v - target) < 0);
}
template <int N> __device__ __forceinline__ void cs(int n, float& c, float& s) {
  n = ((n + N / 2) & (N - 1)) - N / 2;
  float a = (float)n * (6.283185307179586f / N);
  c = __cosf(a); s = __sinf(a);
}
constexpr float ALPHA = 1.13288f;
struct FftC { uint32_t ar[2][2], ai[2][2], p[4], q1, q3; float tc[2][4], ts[2][4]; };
constexpr uint32_t NEG = 0x80008000u;

__device__ __forceinline__ void fft_s1(const FftC& K, const uint32_t (&in)[4][2], float (&cr)[2][4], float (&ci)[2][4]) {
#pragma unroll
  for (int h = 0; h < 2; h++) {
    mma0(cr[h], K.ar[0][0], K.ar[1][0], K.ar[0][1], K.ar[1][1], in[0][h], in[1][h]);
    mma0(ci[h], K.ai[0][0], K.ai[1][0], K.ai[0][1], K.ai[1][1], in[0][h], in[1][h]);
  }
#pragma unroll
  for (int h = 0; h < 2; h++) {
    mma(cr[h], K.ar[0][0], K.ar[1][0] ^ NEG, K.ar[0][1], K.ar[1][1] ^ NEG, in[2][h], in[3][h]);
    mma(ci[h], K.ai[0][0], K.ai[1][0] ^ NEG, K.ai[0][1], K.ai[1][1] ^ NEG, in[2][h], in[3][h]);
  }
}
__device__ __forceinline__ void fft_s2(const FftC& K, const float (&cr)[2][4], const float (&ci)[2][4], float (&o)[4][4]) {
  uint32_t a[2][4];
#pragma unroll
  for (int h = 0; h < 2; h++)
#pragma unroll
    for (int i = 0; i < 4; i++) {
      float xr = cr[i & 1][2 * h + (i >> 1)], xi = ci[i & 1][2 * h + (i >> 1)];
      a[h][i] = pk(xr * K.tc[h][i] + xi * K.ts[h][i], xi * K.tc[h][i] - xr * K.ts[h][i]);
    }
  mma0(o[0], a[0][0], a[1][0], a[0][1], a[1][1], K.p[0], K.p[1]);
  mma0(o[1], a[0][0], a[1][0], a[0][1], a[1][1], K.p[0], K.q1);
  mma0(o[2], a[0][0], a[1][0], a[0][1], a[1][1], K.p[0], K.p[1] ^ NEG);
  mma0(o[3], a[0][0], a[1][0], a[0][1], a[1][1], K.p[0], K.q1 ^ NEG);
  mma(o[0], a[0][2], a[1][2], a[0][3], a[1][3], K.p[2], K.p[3]);
  mma(o[1], a[0][2], a[1][2], a[0][3], a[1][3], K.p[2] ^ NEG, K.q3 ^ NEG);
  mma(o[2], a[0][2], a[1][2], a[0][3], a[1][3], K.p[2], K.p[3] ^ NEG);
  mma(o[3], a[0][2], a[1][2], a[0][3], a[1][3], K.p[2] ^ NEG, K.q3);
}
__device__ __forceinline__ int zphys(int k) { return k + 8 * (k >> 5); }
__device__ __forceinline__ float gelu(float u) {
  float z = u * (0.7978845608028654f + 0.035677408136300125f * u * u), th;
  asm("tanh.approx.f32 %0, %1;" : "=f"(th) : "f"(z));
  float hu = 0.5f * u;
  return fmaf(hu, th, hu);
}

extern "C" __global__ void __cluster_dims__(2, 1, 1) __launch_bounds__(384, 1)
fused_kernel(const __grid_constant__ CUtensorMap tmW1, const __grid_constant__ CUtensorMap tmW2, const uint2* __restrict__ x, const unsigned short* __restrict__ wr,
             const unsigned short* __restrict__ wi, const char* __restrict__ w1, const uint32_t* __restrict__ b1,
             const char* __restrict__ w2, const unsigned short* __restrict__ b2, uint4* __restrict__ out) {
  extern __shared__ __align__(1024) char smem[];
  const uint32_t sb = (uint32_t)__cvta_generic_to_shared(smem);
  const uint32_t mb = sb + BAR_OFF;
  const int b = blockIdx.x, rank = b & 1, pr = b >> 1, dt = pr & 3, ot = pr >> 2;
  const int warp = __shfl_sync(0xffffffffu, threadIdx.x >> 5, 0), lane = threadIdx.x & 31;
  const int g = lane >> 2, t = lane & 3;

  if (warp < 8) {
    const int tid = threadIdx.x;
    uint32_t xw[2][4][2];
    {
      const uint2* xp = x + (size_t)(256 * warp + 2 * b) * 128 + 8 * t + g;
#pragma unroll
      for (int a = 0; a < 2; a++)
#pragma unroll
        for (int j = 0; j < 4; j++) { uint2 v = __ldg(xp + a * 128 + 32 * j); xw[a][j][0] = v.x; xw[a][j][1] = v.y; }
    }
    STAMP(0);
    asm volatile("barrier.cluster.arrive.relaxed.aligned;" ::: "memory");
    unsigned base = 0;
    if (tid == 0) base = __ldcg(&g_cnt[1 * 64]);
    FftC K;
    {
      float c, s;
#pragma unroll
      for (int h = 0; h < 2; h++)
#pragma unroll
        for (int j = 0; j < 2; j++) {
          cs<16>((2 * g + h) * (t + 4 * j), c, s);
          K.ar[h][j] = pk(ALPHA * c, ALPHA * s); K.ai[h][j] = pk(-ALPHA * s, ALPHA * c);
        }
#pragma unroll
      for (int i = 0; i < 4; i++) {
        cs<16>((4 * t + i) * (g >> 1) + 4 * (g & 1), c, s);
        K.p[i] = pk(ALPHA * c, ALPHA * s);
        if (i == 1) K.q1 = pk(-ALPHA * s, ALPHA * c);
        if (i == 3) K.q3 = pk(-ALPHA * s, ALPHA * c);
      }
#pragma unroll
      for (int h = 0; h < 2; h++)
#pragma unroll
        for (int i = 0; i < 4; i++) {
          cs<256>((2 * g + h) * (4 * t + i), c, s);
          K.tc[h][i] = c * (1.f / (ALPHA * ALPHA)); K.ts[h][i] = s * (1.f / (ALPHA * ALPHA));
        }
    }
    const int key = ((b >> 3) & 3) * 2 + (b & 1);
    const uint32_t zb = sb + XCH_OFF;
    float mean[2];
    {
      uint32_t a8[2][4]; float vc[4], vs[4];
#pragma unroll
      for (int a = 0; a < 2; a++)
#pragma unroll
        for (int u = 0; u < 2; u++) {
          float c, s; cs<2048>(g * (256 * (t + 4 * u) + 2 * b + a), c, s);
          a8[a][2 * u] = pk(c, s); a8[a][2 * u + 1] = pk(-s, c);
        }
#pragma unroll
      for (int i = 0; i < 4; i++) cs<512>(16 * warp + 8 * (i >> 1) + 2 * t + (i & 1) + 128, vc[i], vs[i]);
      asm volatile("barrier.cluster.wait.aligned;" ::: "memory");
#pragma unroll
      for (int a = 0; a < 2; a++) {
        float cr[2][4], ci[2][4], o[4][4];
        fft_s1(K, xw[a], cr, ci);
        float sm = ((cr[0][0] + cr[0][1]) + (cr[1][0] + cr[1][1])) + ((ci[0][0] + ci[0][1]) + (ci[1][0] + ci[1][1]));
        sm += __shfl_xor_sync(0xffffffffu, sm, 1); sm += __shfl_xor_sync(0xffffffffu, sm, 2);
        sm = g == 0 ? sm * (1.f / 32.f) : 0.f;
#pragma unroll
        for (int h = 0; h < 2; h++) { cr[h][0] -= sm; cr[h][1] -= sm; ci[h][0] -= sm; ci[h][1] -= sm; }
        mean[a] = __shfl_sync(0xffffffffu, sm, 0) * (1.f / (16.f * 1.1328125f));
        float q = 0.f, q2 = 0.f;
#pragma unroll
        for (int i = 0; i < 4; i++) { q = fmaf(cr[0][i], cr[0][i], q); q2 = fmaf(cr[1][i], cr[1][i], q2); q = fmaf(ci[0][i], ci[0][i], q); q2 = fmaf(ci[1][i], ci[1][i], q2); }
        q += q2;
#pragma unroll
        for (int m = 1; m < 32; m <<= 1) q += __shfl_xor_sync(0xffffffffu, q, m);
        float r = rsqrtf(q * (1.f / (512.f * 16.f * ALPHA * ALPHA)) + 1e-5f) * 4.76837158203125e-7f;
        fft_s2(K, cr, ci, o);
#pragma unroll
        for (int j = 0; j < 4; j++)
          sts64(zb + ((a * 8 + warp) * ZROW + zphys(16 * t + 64 * j) + 2 * g) * 4, pk(o[j][0] * r, o[j][1] * r), pk(o[j][2] * r, o[j][3] * r));
      }
      wbar();
      uint4* tp = g_T1 + (size_t)(g * 16 + warp) * 1024 + b * 8;
#pragma unroll
      for (int nt = 0; nt < 2; nt++) {
        const int k = 16 * warp + 8 * nt + g, km = k == 0 ? 128 : 256 - k;
        uint32_t lo[4], hi[4];
#pragma unroll
        for (int a = 0; a < 2; a++) {
          const uint32_t rb = zb + (a * 8 + t) * ZROW * 4;
          float A[4], B[4];
          mma0(A, a8[a][0], a8[a][1], a8[a][2], a8[a][3], lds32(rb + zphys(k) * 4), lds32(rb + (4 * ZROW + zphys(k)) * 4));
          mma0(B, a8[a][0] ^ 0x80000000u, a8[a][1] ^ 0x80000000u, a8[a][2] ^ 0x80000000u, a8[a][3] ^ 0x80000000u,
               lds32(rb + zphys(km) * 4), lds32(rb + (4 * ZROW + zphys(km)) * 4));
#pragma unroll
          for (int e = 0; e < 2; e++) {
            float sr = A[e] + B[e], si = A[2 + e] + B[2 + e], dr = A[e] - B[e], di = A[2 + e] - B[2 + e];
            float c = vc[2 * nt + e], s = vs[2 * nt + e];
            float gr = dr * c + di * s, gi = di * c - dr * s;
            float lr = sr + gr, li = si + gi, hr = sr - gr, hii = si - gi;
            if (nt == 0 && e == 0) {
              const bool sp = warp == 0 && t == 0;
              lr = sp ? 2.f * B[0] : lr; li = sp ? 2.f * B[2] : li;
              hr = sp ? 2.f * (A[0] - A[2]) : hr; hii = sp ? 2.f * (A[0] + A[2]) : hii;
            }
            lo[2 * a + e] = pk(lr, li); hi[2 * a + e] = pk(hr, hii);
          }
        }
        const int w = (t + 4 * nt) ^ key;
        tp[w] = make_uint4(lo[0], lo[1], lo[2], lo[3]);
        tp[8 * 1024 + w] = make_uint4(hi[0], hi[1], hi[2], hi[3]);
      }
      asm volatile("fence.proxy.async.shared::cta;" ::: "memory");
      wbar();
      STAMP(1);
      if (tid == 0) {
        cnt_arrive(0);
        cnt_wait(0, base + NCTA);
        asm volatile("fence.proxy.async.global;" ::: "memory");
        mbar_expect(mb + MB_P2IN * 8, 16384);
#pragma unroll
        for (int j = 0; j < 4; j++) bulk_ld(zb + j * 4096, g_T1 + (size_t)b * 1024 + j * 256, 4096, mb + MB_P2IN * 8);
      }
      __syncwarp();
      STAMP(2);
    }
    {
      const uint32_t off = (8 * t + g) * 128 + ((warp ^ (2 * t + (g & 1))) << 4);
      mbar_wait(mb + MB_FILT * 8, 0);
      mbar_wait(mb + MB_P2IN * 8, 0);
      STAMP(3);
      uint32_t in[2][4][2], fw[2][4][2];
#pragma unroll
      for (int j = 0; j < 4; j++) {
        uint4 v = lds128(zb + off + j * 4096);
        in[0][j][0] = v.x; in[1][j][0] = v.y; in[0][j][1] = v.z; in[1][j][1] = v.w;
      }
#pragma unroll
      for (int j = 0; j < 4; j++) {
        uint4 v = lds128(sb + FILT_OFF + off + j * 4096);
        fw[0][j][0] = v.x; fw[1][j][0] = v.y; fw[0][j][1] = v.z; fw[1][j][1] = v.w;
      }
#pragma unroll
      for (int sg = 0; sg < 2; sg++) {
        float cr[2][4], ci[2][4], o[4][4];
        fft_s1(K, in[sg], cr, ci);
        fft_s2(K, cr, ci, o);
#pragma unroll
        for (int j = 0; j < 4; j++)
#pragma unroll
          for (int h = 0; h < 2; h++) {
            float fr = blo(fw[sg][j][h]), fi = bhi(fw[sg][j][h]), xr = o[j][2 * h], xi = o[j][2 * h + 1];
            in[sg][j][h] = pk(xr * fi + xi * fr, xr * fr - xi * fi);
          }
        fft_s1(K, in[sg], cr, ci);
        fft_s2(K, cr, ci, o);
#pragma unroll
        for (int j = 0; j < 4; j++) { in[sg][j][0] = pk(o[j][0], o[j][1]); in[sg][j][1] = pk(o[j][2], o[j][3]); }
      }
#pragma unroll
      for (int j = 0; j < 4; j++) sts128(zb + off + j * 4096, make_uint4(in[0][j][0], in[1][j][0], in[0][j][1], in[1][j][1]));
      wbar();
#pragma unroll
      for (int j = 0; j < 4; j++) g_T2[(size_t)b * 1024 + j * 256 + tid] = lds128(zb + j * 4096 + tid * 16);
      wbar();
      STAMP(4);
      if (tid == 0) cnt_arrive(1);
    }
    {
      uint32_t a8[2][4]; float vc[4], vs[4];
#pragma unroll
      for (int a = 0; a < 2; a++)
#pragma unroll
        for (int u = 0; u < 2; u++) {
          float c, s; cs<2048>((t + 4 * u) * (256 * g + 2 * b + a), c, s);
          a8[a][2 * u] = pk(c, s); a8[a][2 * u + 1] = pk(-s, c);
        }
#pragma unroll
      for (int i = 0; i < 4; i++) cs<512>(16 * warp + 4 * t + i + 128, vc[i], vs[i]);
      if (tid == 0) cnt_wait(1, base + NCTA);
      wbar();
      STAMP(5);
      const uint4* tp = g_T2 + (size_t)(t * 16 + warp) * 1024 + b * 8 + (g ^ key);
      uint4 L0 = ldcg128(tp), L1 = ldcg128(tp + 64 * 1024), H0 = ldcg128(tp + 8 * 1024), H1 = ldcg128(tp + 72 * 1024);
      const uint32_t l0[4] = {L0.x, L0.y, L0.z, L0.w}, l1[4] = {L1.x, L1.y, L1.z, L1.w}, h0[4] = {H0.x, H0.y, H0.z, H0.w}, h1[4] = {H1.x, H1.y, H1.z, H1.w};
#pragma unroll
      for (int a = 0; a < 2; a++) {
        uint32_t zf[4], zm[4];
#pragma unroll
        for (int sg = 0; sg < 2; sg++) {
          float A[4], B[4];
          mma0(A, a8[a][0], a8[a][1], a8[a][2], a8[a][3], l0[2 * a + sg], l1[2 * a + sg]);
          mma0(B, a8[a][0], a8[a][1], a8[a][2], a8[a][3], h0[2 * a + sg], h1[2 * a + sg]);
#pragma unroll
          for (int e = 0; e < 2; e++) {
            const int i = 2 * e + sg;
            float sr = A[2 + e] + B[2 + e], si = A[e] + B[e], dr = A[2 + e] - B[2 + e], di = A[e] - B[e];
            float gr = dr * vc[i] - di * vs[i], gi = di * vc[i] + dr * vs[i];
            float fr = sr + gr, fi = si + gi, mr = sr - gr, mi = gi - si;
            if (i == 0) {
              const bool sp = warp == 0 && t == 0;
              fr = sp ? B[2] : fr; fi = sp ? -B[2] : fi;
              mr = sp ? 2.f * A[2] : mr; mi = sp ? -2.f * A[0] : mi;
            }
            zf[i] = pk(fi, fr); zm[i] = pk(mi, mr);
          }
        }
        const uint32_t rb = zb + (a * 8 + g) * ZROW * 4;
        const int k0 = 16 * warp + 4 * t;
        sts128(rb + zphys(k0) * 4, make_uint4(zf[0], zf[1], zf[2], zf[3]));
        sts32(rb + zphys(k0 == 0 ? 128 : 256 - k0) * 4, zm[0]);
        sts32(rb + zphys(255 - k0) * 4, zm[1]);
        sts32(rb + zphys(254 - k0) * 4, zm[2]);
        sts32(rb + zphys(253 - k0) * 4, zm[3]);
      }
      wbar();
#pragma unroll
      for (int a = 0; a < 2; a++) {
        uint32_t in[4][2];
#pragma unroll
        for (int j = 0; j < 4; j++) { uint2 v = lds64(zb + ((a * 8 + warp) * ZROW + zphys(16 * t + 64 * j) + 2 * g) * 4); in[j][0] = v.x; in[j][1] = v.y; }
        float cr[2][4], ci[2][4], o[4][4];
        fft_s1(K, in, cr, ci);
        fft_s2(K, cr, ci, o);
        float s1 = 0.f, s2 = 0.f;
        uint2* hp = (uint2*)g_h + (size_t)(256 * warp + 2 * b + a) * 128 + 8 * t + g;
#pragma unroll
        for (int j = 0; j < 4; j++) {
          uint32_t hw[2];
#pragma unroll
          for (int h = 0; h < 2; h++) {
            uint32_t y = pk(o[j][2 * h + 1], o[j][2 * h]);
            hw[h] = pk(blo(xw[a][j][h]) + blo(y), bhi(xw[a][j][h]) + bhi(y));
            float u0 = blo(hw[h]) - mean[a], u1 = bhi(hw[h]) - mean[a];
            o[j][2 * h] = u0; o[j][2 * h + 1] = u1;
            s1 += u0 + u1; s2 = fmaf(u0, u0, fmaf(u1, u1, s2));
          }
          hp[32 * j] = make_uint2(hw[0], hw[1]);
        }
#pragma unroll
        for (int m = 1; m < 32; m <<= 1) { s1 += __shfl_xor_sync(0xffffffffu, s1, m); s2 += __shfl_xor_sync(0xffffffffu, s2, m); }
        const float mu = s1 * (1.f / 512.f), var = fmaxf(s2 * (1.f / 512.f) - mu * mu, 0.f);
        const float r1 = rsqrtf(var + 1e-5f);
        const float r = r1 * rsqrtf(var * r1 * r1 + 1e-5f);
        char* np = (char*)g_Hn + (size_t)b * 4096 + (t >> 1) * 2048 + a * 1024 + warp * 128 + ((((t & 1) * 4 + (g >> 1)) ^ warp) << 4) + (g & 1) * 8;
#pragma unroll
        for (int j = 0; j < 4; j++)
          *(uint2*)(np + (size_t)j * 128 * 4096) = make_uint2(pk((o[j][0] - mu) * r, (o[j][1] - mu) * r), pk((o[j][2] - mu) * r, (o[j][3] - mu) * r));
      }
      asm volatile("fence.proxy.async.shared::cta;" ::: "memory");
      wbar();
      STAMP(6);
      if (tid == 0) { cnt_arrive(2 + (b >> 6)); sts32(sb + BASE_OFF, base); mbar_arrive(mb + MB_P3DONE * 8); }
    }
    const int wg = warp >> 2;
    const uint32_t peer_sb = mapa(sb, rank ^ 1);
    {
      uint32_t bias[11];
#pragma unroll
      for (int j = 0; j < 11; j++) bias[j] = (11 * ot + j < 172) ? __ldg(b1 + (11 * ot + j) * 4 + t) : 0u;
      float acc[44];
      const uint64_t da0 = mkdesc(sb + RING_OFF + wg * 2048, 0, 1024, 1), db0 = mkdesc(sb, 1408, 128, 0);
      mbar_wait(mb + MB_W1 * 8, 0);
#pragma unroll
      for (int i = 0; i < 32; i++) {
        mbar_wait(mb + (MB_FULL + i % NST) * 8, (i / NST) & 1);
        if (i == 0) STAMP(7);
        asm volatile("wgmma.fence.sync.aligned;" ::: "memory");
        wgmma_n88_ss<1, 1>(acc, da0 + (((i % NST) * 8192) >> 4), db0 + ((2 * i * 2816) >> 4), i > 0);
        wgmma_n88_ss<1, 1>(acc, da0 + (((i % NST) * 8192 + 4096) >> 4), db0 + (((2 * i + 1) * 2816) >> 4), 1);
        asm volatile("wgmma.commit_group.sync.aligned;" ::: "memory");
        if (i > 0) {
          asm volatile("wgmma.wait_group.sync.aligned 1;" ::: "memory");
          if ((tid & 127) == 0) { mbar_arrive(mb + (MB_EMPTY + (i - 1) % NST) * 8); if (i == 4) mbar_arrive_cluster(peer_sb + BAR_OFF + MB_PEER1 * 8); }
        }
      }
      asm volatile("wgmma.wait_group.sync.aligned 0;" ::: "memory");
#pragma unroll
      for (int i = 0; i < 44; i++) asm volatile("" : "+f"(acc[i]) :: "memory");
      if ((tid & 127) == 0) mbar_arrive(mb + (MB_EMPTY + 31 % NST) * 8);
      STAMP(8);
      float keep[22], send[22];
#pragma unroll
      for (int j = 0; j < 11; j++) {
        keep[2 * j] = rank ? acc[4 * j + 2] : acc[4 * j]; keep[2 * j + 1] = rank ? acc[4 * j + 3] : acc[4 * j + 1];
        send[2 * j] = rank ? acc[4 * j] : acc[4 * j + 2]; send[2 * j + 1] = rank ? acc[4 * j + 1] : acc[4 * j + 3];
      }
      mbar_wait_cluster(mb + MB_PEER1 * 8, 0);
#pragma unroll
      for (int j = 0; j < 5; j++) st_async4(peer_sb + j * 4096 + tid * 16, send[4 * j], send[4 * j + 1], send[4 * j + 2], send[4 * j + 3], peer_sb + BAR_OFF + MB_X1 * 8);
      st_async2(peer_sb + 5 * 4096 + tid * 8, send[20], send[21], peer_sb + BAR_OFF + MB_X1 * 8);
      mbar_wait_cluster(mb + MB_X1 * 8, 0);
#pragma unroll
      for (int j = 0; j < 5; j++) {
        uint4 v = lds128(sb + j * 4096 + tid * 16);
        keep[4 * j] += __uint_as_float(v.x); keep[4 * j + 1] += __uint_as_float(v.y); keep[4 * j + 2] += __uint_as_float(v.z); keep[4 * j + 3] += __uint_as_float(v.w);
      }
      { uint2 v = lds64(sb + 5 * 4096 + tid * 8); keep[20] += __uint_as_float(v.x); keep[21] += __uint_as_float(v.y); }
      uint32_t* up = (uint32_t*)g_U + ((size_t)dt * 172 + 11 * ot) * 512 + (4 * (warp >> 1) + (g >> 1)) * 32 + (2 * (2 * (warp & 1) + rank) + (g & 1)) * 4 + t;
#pragma unroll
      for (int j = 0; j < 11; j++) {
        uint32_t v = pk(gelu(keep[2 * j] + blo(bias[j])), gelu(keep[2 * j + 1] + bhi(bias[j])));
        if (11 * ot + j < 172) up[j * 512] = v;
      }
      asm volatile("fence.proxy.async.shared::cta;" ::: "memory");
      wbar();
      STAMP(9);
      if (tid == 0) { cnt_arrive(4 + dt); mbar_arrive(mb + MB_X1DONE * 8); }
    }
    {
      const int srow = 128 * ot + 16 * warp + 8 * rank + g;
      float acc[64];
      const uint64_t da0 = mkdesc(sb + wg * 4096, 0, 1024, 1), db0 = mkdesc(sb + RING_OFF, 2048, 128, 0);
      uint4 hv[4]; float bias2 = 0.f;
#pragma unroll
      for (int i = 0; i < 22; i++) {
        mbar_wait(mb + (MB_W2 + i) * 8, 0);
        mbar_wait(mb + (MB_FULL + (32 + i) % NST) * 8, ((32 + i) / NST) & 1);
        if (i == 0) STAMP(10);
        asm volatile("wgmma.fence.sync.aligned;" ::: "memory");
        wgmma_n128_ss<1, 0>(acc, da0 + ((((i + 3) % 22) * 8192) >> 4), db0 + ((((32 + i) % NST) * 8192) >> 4), i > 0);
        if (i < 21) wgmma_n128_ss<1, 0>(acc, da0 + ((((i + 3) % 22) * 8192 + 2048) >> 4), db0 + ((((32 + i) % NST) * 8192 + 4096) >> 4), 1);
        asm volatile("wgmma.commit_group.sync.aligned;" ::: "memory");
        if (i == 8) {
#pragma unroll
          for (int j = 0; j < 4; j++) hv[j] = ldcg128(g_h + (size_t)srow * 64 + dt * 16 + 4 * j + t);
          bias2 = __uint_as_float((uint32_t)__ldg(b2 + srow) << 16);
        }
        if (i > 0) {
          asm volatile("wgmma.wait_group.sync.aligned 1;" ::: "memory");
          if ((tid & 127) == 0) { if (i < 22 - NST + 1) mbar_arrive(mb + (MB_EMPTY + (32 + i - 1) % NST) * 8); if (i == 4) mbar_arrive_cluster(peer_sb + BAR_OFF + MB_PEER2 * 8); }
        }
      }
      asm volatile("wgmma.wait_group.sync.aligned 0;" ::: "memory");
#pragma unroll
      for (int i = 0; i < 64; i++) asm volatile("" : "+f"(acc[i]) :: "memory");
      STAMP(11);
      mbar_wait_cluster(mb + MB_PEER2 * 8, 0);
#pragma unroll
      for (int j = 0; j < 8; j++)
        st_async4(peer_sb + 3 * 8192 + j * 4096 + tid * 16, rank ? acc[8 * j] : acc[8 * j + 2], rank ? acc[8 * j + 1] : acc[8 * j + 3],
                  rank ? acc[8 * j + 4] : acc[8 * j + 6], rank ? acc[8 * j + 5] : acc[8 * j + 7], peer_sb + BAR_OFF + MB_X2 * 8);
      float keep[32];
#pragma unroll
      for (int j = 0; j < 16; j++) {
        const uint32_t hw = j % 4 == 0 ? hv[j / 4].x : j % 4 == 1 ? hv[j / 4].y : j % 4 == 2 ? hv[j / 4].z : hv[j / 4].w;
        keep[2 * j] = (rank ? acc[4 * j + 2] : acc[4 * j]) + (bias2 + blo(hw));
        keep[2 * j + 1] = (rank ? acc[4 * j + 3] : acc[4 * j + 1]) + (bias2 + bhi(hw));
      }
      mbar_wait_cluster(mb + MB_X2 * 8, 0);
#pragma unroll
      for (int j = 0; j < 4; j++) {
        uint4 v = lds128(sb + 3 * 8192 + (2 * j) * 4096 + tid * 16), w = lds128(sb + 3 * 8192 + (2 * j + 1) * 4096 + tid * 16);
        out[(size_t)srow * 64 + dt * 16 + 4 * j + t] =
            make_uint4(pk(keep[8 * j] + __uint_as_float(v.x), keep[8 * j + 1] + __uint_as_float(v.y)), pk(keep[8 * j + 2] + __uint_as_float(v.z), keep[8 * j + 3] + __uint_as_float(v.w)),
                       pk(keep[8 * j + 4] + __uint_as_float(w.x), keep[8 * j + 5] + __uint_as_float(w.y)), pk(keep[8 * j + 6] + __uint_as_float(w.z), keep[8 * j + 7] + __uint_as_float(w.w)));
      }
      STAMP(12);
    }
  } else {
    const int pw = warp - 8;
    if (pw == 0) {
      if (lane == 0) {
        for (int i = 0; i < NST; i++) { mbar_init(mb + (MB_FULL + i) * 8, 1); mbar_init(mb + (MB_EMPTY + i) * 8, 2); }
        for (int i = 0; i < 22; i++) mbar_init(mb + (MB_W2 + i) * 8, 1);
        for (int i = 0; i < 16; i++) mbar_init(mb + (MB_W1T + i) * 8, 1);
        mbar_init(mb + MB_P2IN * 8, 1); mbar_init(mb + MB_FILT * 8, 128); mbar_init(mb + MB_W1 * 8, 128);
        mbar_init(mb + MB_PEER1 * 8, 2); mbar_init(mb + MB_X1 * 8, 1); mbar_init(mb + MB_X1DONE * 8, 1);
        mbar_init(mb + MB_PEER2 * 8, 2); mbar_init(mb + MB_X2 * 8, 1); mbar_init(mb + MB_P3DONE * 8, 1);
        mbar_expect(mb + MB_X1 * 8, 22528); mbar_expect(mb + MB_X2 * 8, 32768);
        asm volatile("fence.mbarrier_init.release.cluster;" ::: "memory");
      }
      __syncwarp();
    }
    STAMP(0);
    asm volatile("bar.sync 2, 128;" ::: "memory");
    asm volatile("barrier.cluster.arrive.relaxed.aligned;" ::: "memory");
    auto w1_issue = [&]() {
      if (elect()) {
#pragma unroll 1
        for (int i = pw; i < 16; i += 4) { mbar_expect(mb + (MB_W1T + i) * 8, 11264); tma3d(sb + i * 11264, &tmW1, 88 * ot, 0, 128 * rank + 8 * i, mb + (MB_W1T + i) * 8); }
      }
      __syncwarp();
    };
    if (!W1_LATE) w1_issue();
    {
      const int j1 = b >> 4, q = b & 15, slot = lane & 15, h = lane >> 4;
      const bool hi = q >= 8;
      const int k = 16 * (q & 7) + slot, col = hi ? 256 - k : (k == 0 ? 128 : k);
#pragma unroll 1
      for (int it = 0; it < 2; it++) {
        uint32_t vr[16], vi[16];
#pragma unroll
        for (int n = 0; n < 16; n++) {
          const int c = pw * 32 + it * 16 + n;
          int j = j1 + 8 * (2 * c + h);
          if (hi) j = (2048 - j) & 2047;
          vr[n] = __ldg(wr + j * DF + col); vi[n] = __ldg(wi + j * DF + col);
        }
#pragma unroll
        for (int n = 0; n < 16; n++) {
          const int c = pw * 32 + it * 16 + n;
          sts32(sb + FILT_OFF + c * 128 + (((slot >> 1) ^ (((c >> 3) & 3) * 2 + (c & 1))) << 4) + h * 8 + (slot & 1) * 4,
                (vr[n] | (vi[n] << 16)) ^ (hi ? 0x80000000u : 0u));
        }
      }
      mbar_arrive(mb + MB_FILT * 8);
    }
    STAMP(1);
    {
      if (W1_LATE) w1_issue();
      const uint32_t rd = ((lane & 7) * 11 + (lane >> 3)) * 16, wr = lane * 16;
#pragma unroll 1
      for (int it = 0; it < 8; it++) {
        const int box = pw + 4 * (it >> 1);
        if (!(it & 1)) mbar_wait(mb + (MB_W1T + box) * 8, 0);
        const uint32_t p = sb + box * 11264 + (it & 1) * 5632;
        uint4 v[4][3];
#pragma unroll
        for (int n = 0; n < 4; n++) { v[n][0] = lds128(p + n * 1408 + rd); v[n][1] = lds128(p + n * 1408 + rd + 64); if (lane < 24) v[n][2] = lds128(p + n * 1408 + rd + 128); }
        __syncwarp();
#pragma unroll
        for (int n = 0; n < 4; n++) { sts128(p + n * 1408 + wr, v[n][0]); sts128(p + n * 1408 + wr + 512, v[n][1]); if (lane < 24) sts128(p + n * 1408 + wr + 1024, v[n][2]); }
      }
      if (lane == 0) asm volatile("cp.async.bulk.prefetch.L2.global [%0], %1;" :: "l"(w2 + (size_t)(b * 4 + pw) * 11008), "r"(11008) : "memory");
      asm volatile("fence.proxy.async.shared::cta;" ::: "memory");
      mbar_arrive(mb + MB_W1 * 8);
    }
    STAMP(2);
    asm volatile("barrier.cluster.wait.aligned;" ::: "memory");
    if (pw == 0) {
      mbar_wait(mb + MB_P3DONE * 8, 0);
      const unsigned base = lds32(sb + BASE_OFF);
      if (lane == 0) cnt_wait(2 + rank, (base >> 1) + 64);
      __syncwarp();
      STAMP(3);
      asm volatile("fence.proxy.async.global;" ::: "memory");
      const char* hsrc = (const char*)g_Hn + ((size_t)dt * 128 + 64 * rank) * 4096;
      int nw2 = 0;
#pragma unroll
      for (int i = 0; i < 32 + NST; i++) {
        if (i >= NST) mbar_wait(mb + (MB_EMPTY + i % NST) * 8, ((i / NST) & 1) ^ 1);
        if (elect()) {
          if (i < 32) { mbar_expect(mb + (MB_FULL + i % NST) * 8, 8192); bulk_ld(sb + RING_OFF + (i % NST) * 8192, hsrc + i * 8192, 8192, mb + (MB_FULL + i % NST) * 8); }
        }
        if (i >= W2_START) {
#pragma unroll
          for (int rep = 0; rep < 19; rep++) {
            if (nw2 < 19 && (nw2 + 4) * 8192 <= (i - NST + 1) * 5632 && (rep < W2_RATE || i == 31 + NST)) {
              if (elect()) { mbar_expect(mb + (MB_W2 + nw2) * 8, 8192); tma3d(sb + (nw2 + 3) * 8192, &tmW2, 0, 688 * rank + 32 * nw2, 2 * ot, mb + (MB_W2 + nw2) * 8); }
              nw2++;
            }
          }
        }
      }
      mbar_wait(mb + MB_X1DONE * 8, 0);
      if (elect()) {
#pragma unroll
        for (int n = 19; n < 22; n++) { mbar_expect(mb + (MB_W2 + n) * 8, 8192); tma3d(sb + (n - 19) * 8192, &tmW2, 0, 688 * rank + 32 * n, 2 * ot, mb + (MB_W2 + n) * 8); }
      }
      STAMP(4);
      if (lane == 0) cnt_wait(4 + dt, (base >> 2) + 32);
      __syncwarp();
      STAMP(5);
      asm volatile("fence.proxy.async.global;" ::: "memory");
      const char* usrc = (const char*)g_U + ((size_t)dt * 172 + 86 * rank) * 2048;
#pragma unroll
      for (int i = 0; i < 22; i++) {
        if (i >= NST) mbar_wait(mb + (MB_EMPTY + (32 + i) % NST) * 8, (((32 + i) / NST) & 1) ^ 1);
        if (elect()) {
          const int bytes = i < 21 ? 8192 : 4096;
          mbar_expect(mb + (MB_FULL + (32 + i) % NST) * 8, bytes);
          bulk_ld(sb + RING_OFF + ((32 + i) % NST) * 8192, usrc + i * 8192, bytes, mb + (MB_FULL + (32 + i) % NST) * 8);
        }
      }
      STAMP(6);
    }
  }
}

typedef CUresult (*EncodeFn)(CUtensorMap*, CUtensorMapDataType, cuuint32_t, void*, const cuuint64_t*, const cuuint64_t*, const cuuint32_t*,
                             const cuuint32_t*, CUtensorMapInterleave, CUtensorMapSwizzle, CUtensorMapL2promotion, CUtensorMapFloatOOBfill);

extern "C" void kernel_launch(void* const* d_in, const int* in_sizes, int n_in, void* d_out, int out_size) {
  static EncodeFn enc = nullptr;
  if (!enc) {
    void* fn = nullptr; cudaDriverEntryPointQueryResult st;
    cudaGetDriverEntryPoint("cuTensorMapEncodeTiled", &fn, cudaEnableDefault, &st);
    enc = (EncodeFn)fn;
    cudaFuncSetAttribute(fused_kernel, cudaFuncAttributeMaxDynamicSharedMemorySize, SMEM_BYTES);
  }
  CUtensorMap tm, tm1;
  {
    cuuint64_t dims[3] = {(cuuint64_t)F_, 8, 256}, strides[2] = {(cuuint64_t)256 * F_ * 2, F_ * 2};
    cuuint32_t box[3] = {88, 8, 8}, es[3] = {1, 1, 1};
    enc(&tm1, CU_TENSOR_MAP_DATA_TYPE_BFLOAT16, 3, d_in[4], dims, strides, box, es, CU_TENSOR_MAP_INTERLEAVE_NONE, CU_TENSOR_MAP_SWIZZLE_NONE,
        W1_PROMO, CU_TENSOR_MAP_FLOAT_OOB_FILL_NONE);
  }
  {
    cuuint64_t dims[3] = {64, (cuuint64_t)F_, S_ / 64}, strides[2] = {S_ * 2, 128};
    cuuint32_t box[3] = {64, 32, 2}, es[3] = {1, 1, 1};
    enc(&tm, CU_TENSOR_MAP_DATA_TYPE_BFLOAT16, 3, d_in[6], dims, strides, box, es, CU_TENSOR_MAP_INTERLEAVE_NONE, CU_TENSOR_MAP_SWIZZLE_128B,
        CU_TENSOR_MAP_L2_PROMOTION_L2_256B, CU_TENSOR_MAP_FLOAT_OOB_FILL_NONE);
  }
  fused_kernel<<<NCTA, 384, SMEM_BYTES, cudaStreamPerThread>>>(tm1, tm, (const uint2*)d_in[0], (const unsigned short*)d_in[1], (const unsigned short*)d_in[2],
                                          (const char*)d_in[4], (const uint32_t*)d_in[5], (const char*)d_in[6], (const unsigned short*)d_in[7], (uint4*)d_out);
}
```

```cpp
#include <cuda_runtime.h>
#include <cuda.h>
#include <cuda_bf16.h>
#include <stdint.h>
#define W1_LATE 1
#define W1_PROMO CU_TENSOR_MAP_L2_PROMOTION_NONE
#define W2_RATE 1
#define PF_MODE 0
#define W1_DEPTH 1
#define W1_WARPS 3
#define DRY 1
template<int TA, int TB> __device__ __forceinline__ void wgmma_n88_ss(float (&d)[44], uint64_t da, uint64_t db, int sd) {
  asm volatile("{\n.reg .pred p;\nsetp.ne.b32 p, %46, 0;\n"
    "wgmma.mma_async.sync.aligned.m64n88k16.f32.bf16.bf16 {%0, %1, %2, %3, %4, %5, %6, %7, %8, %9, %10, %11, %12, %13, %14, %15, %16, %17, %18, %19, %20, %21, %22, %23, %24, %25, %26, %27, %28, %29, %30, %31, %32, %33, %34, %35, %36, %37, %38, %39, %40, %41, %42, %43}, %44, %45, p, 1, 1, %47, %48;\n}\n"
    : "+f"(d[0]), "+f"(d[1]), "+f"(d[2]), "+f"(d[3]), "+f"(d[4]), "+f"(d[5]), "+f"(d[6]), "+f"(d[7]), "+f"(d[8]), "+f"(d[9]), "+f"(d[10]), "+f"(d[11]), "+f"(d[12]), "+f"(d[13]), "+f"(d[14]), "+f"(d[15]), "+f"(d[16]), "+f"(d[17]), "+f"(d[18]), "+f"(d[19]), "+f"(d[20]), "+f"(d[21]), "+f"(d[22]), "+f"(d[23]), "+f"(d[24]), "+f"(d[25]), "+f"(d[26]), "+f"(d[27]), "+f"(d[28]), "+f"(d[29]), "+f"(d[30]), "+f"(d[31]), "+f"(d[32]), "+f"(d[33]), "+f"(d[34]), "+f"(d[35]), "+f"(d[36]), "+f"(d[37]), "+f"(d[38]), "+f"(d[39]), "+f"(d[40]), "+f"(d[41]), "+f"(d[42]), "+f"(d[43]) : "l"(da), "l"(db), "r"(sd), "n"(TA), "n"(TB));
}
template<int TA, int TB> __device__ __forceinline__ void wgmma_n128_ss(float (&d)[64], uint64_t da, uint64_t db, int sd) {
  asm volatile("{\n.reg .pred p;\nsetp.ne.b32 p, %66, 0;\n"
    "wgmma.mma_async.sync.aligned.m64n128k16.f32.bf16.bf16 {%0, %1, %2, %3, %4, %5, %6, %7, %8, %9, %10, %11, %12, %13, %14, %15, %16, %17, %18, %19, %20, %21, %22, %23, %24, %25, %26, %27, %28, %29, %30, %31, %32, %33, %34, %35, %36, %37, %38, %39, %40, %41, %42, %43, %44, %45, %46, %47, %48, %49, %50, %51, %52, %53, %54, %55, %56, %57, %58, %59, %60, %61, %62, %63}, %64, %65, p, 1, 1, %67, %68;\n}\n"
    : "+f"(d[0]), "+f"(d[1]), "+f"(d[2]), "+f"(d[3]), "+f"(d[4]), "+f"(d[5]), "+f"(d[6]), "+f"(d[7]), "+f"(d[8]), "+f"(d[9]), "+f"(d[10]), "+f"(d[11]), "+f"(d[12]), "+f"(d[13]), "+f"(d[14]), "+f"(d[15]), "+f"(d[16]), "+f"(d[17]), "+f"(d[18]), "+f"(d[19]), "+f"(d[20]), "+f"(d[21]), "+f"(d[22]), "+f"(d[23]), "+f"(d[24]), "+f"(d[25]), "+f"(d[26]), "+f"(d[27]), "+f"(d[28]), "+f"(d[29]), "+f"(d[30]), "+f"(d[31]), "+f"(d[32]), "+f"(d[33]), "+f"(d[34]), "+f"(d[35]), "+f"(d[36]), "+f"(d[37]), "+f"(d[38]), "+f"(d[39]), "+f"(d[40]), "+f"(d[41]), "+f"(d[42]), "+f"(d[43]), "+f"(d[44]), "+f"(d[45]), "+f"(d[46]), "+f"(d[47]), "+f"(d[48]), "+f"(d[49]), "+f"(d[50]), "+f"(d[51]), "+f"(d[52]), "+f"(d[53]), "+f"(d[54]), "+f"(d[55]), "+f"(d[56]), "+f"(d[57]), "+f"(d[58]), "+f"(d[59]), "+f"(d[60]), "+f"(d[61]), "+f"(d[62]), "+f"(d[63]) : "l"(da), "l"(db), "r"(sd), "n"(TA), "n"(TB));
}

constexpr int S_ = 2048, D_ = 512, F_ = 1376, DF = 257;
constexpr int NCTA = 128;
constexpr int W_BYTES = 180224;
constexpr int RING_OFF = W_BYTES;
constexpr int NST = 6;
constexpr int BAR_OFF = RING_OFF + NST * 8192;
constexpr int SMEM_BYTES = BAR_OFF + 1024;
constexpr int FILT_OFF = RING_OFF;
constexpr int XCH_OFF = RING_OFF + 16384;
constexpr int ZROW = 328;
constexpr int MB_FULL = 0, MB_EMPTY = 6, MB_W2 = 12, MB_P2IN = 34, MB_FILT = 35, MB_W1 = 36, MB_PEER1 = 37, MB_X1 = 38,
              MB_X1DONE = 39, MB_PEER2 = 40, MB_X2 = 41, MB_P3DONE = 42, MB_W1T = 43;
constexpr int BASE_OFF = BAR_OFF + 960;
#define W2_START 18

__device__ uint4 g_T1[NCTA * 1024];
__device__ uint4 g_T2[NCTA * 1024];
__device__ uint4 g_h[S_ * D_ / 8];
__device__ uint4 g_Hn[4 * 128 * 256];
__device__ uint4 g_U[4 * 172 * 128];
__device__ unsigned g_cnt[8 * 64];
#define STAMP(i)

__device__ __forceinline__ void mbar_init(uint32_t b, int c) { asm volatile("mbarrier.init.shared::cta.b64 [%0], %1;" :: "r"(b), "r"(c) : "memory"); }
__device__ __forceinline__ void mbar_expect(uint32_t b, int bytes) { asm volatile("mbarrier.arrive.expect_tx.shared::cta.b64 _, [%0], %1;" :: "r"(b), "r"(bytes) : "memory"); }
__device__ __forceinline__ void mbar_arrive(uint32_t b) { asm volatile("mbarrier.arrive.shared::cta.b64 _, [%0];" :: "r"(b) : "memory"); }
__device__ __forceinline__ void mbar_arrive_cluster(uint32_t remote) { asm volatile("mbarrier.arrive.release.cluster.shared::cluster.b64 _, [%0];" :: "r"(remote) : "memory"); }
__device__ __forceinline__ uint32_t mapa(uint32_t a, uint32_t cta) { uint32_t r; asm("mapa.shared::cluster.u32 %0, %1, %2;" : "=r"(r) : "r"(a), "r"(cta)); return r; }
__device__ __forceinline__ void mbar_wait(uint32_t b, int ph) {
  asm volatile("{\n.reg .pred p;\n.reg .u32 n;\nmov.u32 n, 0;\nL_W:\n"
               "mbarrier.try_wait.parity.shared::cta.b64 p, [%0], %1;\n@p bra L_D;\n"
               "add.u32 n, n, 1;\nsetp.lt.u32 p, n, 4000000;\n@p bra L_W;\ntrap;\nL_D:\n}" :: "r"(b), "r"(ph) : "memory");
}
__device__ __forceinline__ void mbar_wait_cluster(uint32_t b, int ph) {
  asm volatile("{\n.reg .pred p;\n.reg .u32 n;\nmov.u32 n, 0;\nL_W:\n"
               "mbarrier.try_wait.parity.acquire.cluster.shared::cta.b64 p, [%0], %1;\n@p bra L_D;\n"
               "add.u32 n, n, 1;\nsetp.lt.u32 p, n, 4000000;\n@p bra L_W;\ntrap;\nL_D:\n}" :: "r"(b), "r"(ph) : "memory");
}
__device__ __forceinline__ void bulk_ld(uint32_t dst, const void* src, int bytes, uint32_t bar) {
  asm volatile("cp.async.bulk.shared::cluster.global.mbarrier::complete_tx::bytes [%0], [%1], %2, [%3];" :: "r"(dst), "l"(src), "r"(bytes), "r"(bar) : "memory");
}
__device__ __forceinline__ void tma3d(uint32_t dst, const CUtensorMap* tm, int c0, int c1, int c2, uint32_t bar) {
  asm volatile("cp.async.bulk.tensor.3d.shared::cluster.global.mbarrier::complete_tx::bytes [%0], [%1, {%3, %4, %5}], [%2];"
               :: "r"(dst), "l"(tm), "r"(bar), "r"(c0), "r"(c1), "r"(c2) : "memory");
}
__device__ __forceinline__ bool elect() { uint32_t p; asm volatile("{.reg .pred p; elect.sync _|p, 0xffffffff; selp.b32 %0, 1, 0, p;}" : "=r"(p)); return p; }
__device__ __forceinline__ uint64_t mkdesc(uint32_t addr, uint32_t lbo, uint32_t sbo, uint32_t sw) {
  return (uint64_t)((addr & 0x3FFFF) >> 4) | ((uint64_t)(lbo >> 4) << 16) | ((uint64_t)(sbo >> 4) << 32) | ((uint64_t)sw << 62);
}
__device__ __forceinline__ uint32_t pk(float lo, float hi) { uint32_t r; asm("cvt.rn.bf16x2.f32 %0, %1, %2;" : "=r"(r) : "f"(hi), "f"(lo)); return r; }
__device__ __forceinline__ float blo(uint32_t w) { return __uint_as_float(w << 16); }
__device__ __forceinline__ float bhi(uint32_t w) { return __uint_as_float(w & 0xffff0000u); }
__device__ __forceinline__ void mma(float (&c)[4], uint32_t a0, uint32_t a1, uint32_t a2, uint32_t a3, uint32_t b0, uint32_t b1) {
  asm("mma.sync.aligned.m16n8k16.row.col.f32.bf16.bf16.f32 {%0,%1,%2,%3}, {%4,%5,%6,%7}, {%8,%9}, {%0,%1,%2,%3};"
      : "+f"(c[0]), "+f"(c[1]), "+f"(c[2]), "+f"(c[3]) : "r"(a0), "r"(a1), "r"(a2), "r"(a3), "r"(b0), "r"(b1));
}
__device__ __forceinline__ void mma0(float (&c)[4], uint32_t a0, uint32_t a1, uint32_t a2, uint32_t a3, uint32_t b0, uint32_t b1) {
  asm("mma.sync.aligned.m16n8k16.row.col.f32.bf16.bf16.f32 {%0,%1,%2,%3}, {%4,%5,%6,%7}, {%8,%9}, {%10,%10,%10,%10};"
      : "=f"(c[0]), "=f"(c[1]), "=f"(c[2]), "=f"(c[3]) : "r"(a0), "r"(a1), "r"(a2), "r"(a3), "r"(b0), "r"(b1), "f"(0.f));
}
__device__ __forceinline__ void wbar() { asm volatile("bar.sync 1, 256;" ::: "memory"); }
__device__ __forceinline__ void sts32(uint32_t a, uint32_t v) { asm volatile("st.shared.b32 [%0], %1;" :: "r"(a), "r"(v) : "memory"); }
__device__ __forceinline__ void sts64(uint32_t a, uint32_t x, uint32_t y) { asm volatile("st.shared.v2.b32 [%0], {%1,%2};" :: "r"(a), "r"(x), "r"(y) : "memory"); }
__device__ __forceinline__ void sts128(uint32_t a, uint4 v) { asm volatile("st.shared.v4.b32 [%0], {%1,%2,%3,%4};" :: "r"(a), "r"(v.x), "r"(v.y), "r"(v.z), "r"(v.w) : "memory"); }
__device__ __forceinline__ uint32_t lds32(uint32_t a) { uint32_t v; asm volatile("ld.shared.b32 %0, [%1];" : "=r"(v) : "r"(a) : "memory"); return v; }
__device__ __forceinline__ uint2 lds64(uint32_t a) { uint2 v; asm volatile("ld.shared.v2.b32 {%0,%1}, [%2];" : "=r"(v.x), "=r"(v.y) : "r"(a) : "memory"); return v; }
__device__ __forceinline__ uint4 lds128(uint32_t a) { uint4 v; asm volatile("ld.shared.v4.b32 {%0,%1,%2,%3}, [%4];" : "=r"(v.x), "=r"(v.y), "=r"(v.z), "=r"(v.w) : "r"(a) : "memory"); return v; }
__device__ __forceinline__ uint4 ldcg128(const void* p) { uint4 v; asm volatile("ld.global.cg.v4.b32 {%0,%1,%2,%3}, [%4];" : "=r"(v.x), "=r"(v.y), "=r"(v.z), "=r"(v.w) : "l"(p) : "memory"); return v; }
__device__ __forceinline__ void st_async4(uint32_t a, float x, float y, float z, float w, uint32_t bar) {
  asm volatile("st.async.weak.shared::cluster.mbarrier::complete_tx::bytes.v4.f32 [%0], {%1,%2,%3,%4}, [%5];" :: "r"(a), "f"(x), "f"(y), "f"(z), "f"(w), "r"(bar) : "memory");
}
__device__ __forceinline__ void st_async2(uint32_t a, float x, float y, uint32_t bar) {
  asm volatile("st.async.weak.shared::cluster.mbarrier::complete_tx::bytes.v2.f32 [%0], {%1,%2}, [%3];" :: "r"(a), "f"(x), "f"(y), "r"(bar) : "memory");
}
__device__ __forceinline__ void cnt_arrive(int i) { asm volatile("red.release.gpu.global.add.u32 [%0], 1;" :: "l"(&g_cnt[i * 64]) : "memory"); }
__device__ __forceinline__ void cnt_wait(int i, unsigned target) {
  unsigned v; int n = 0;
  do { asm volatile("ld.acquire.gpu.global.u32 %0, [%1];" : "=r"(v) : "l"(&g_cnt[i * 64]) : "memory"); if (++n > 2000000) __trap(); } while ((int)(v - target) < 0);
}
template <int N> __device__ __forceinline__ void cs(int n, float& c, float& s) {
  n = ((n + N / 2) & (N - 1)) - N / 2;
  float a = (float)n * (6.283185307179586f / N);
  c = __cosf(a); s = __sinf(a);
}
constexpr float ALPHA = 1.13288f;
struct FftC { uint32_t ar[2][2], ai[2][2], p[4], q1, q3; float tc[2][4], ts[2][4]; };
constexpr uint32_t NEG = 0x80008000u;

__device__ __forceinline__ void fft_s1(const FftC& K, const uint32_t (&in)[4][2], float (&cr)[2][4], float (&ci)[2][4]) {
#pragma unroll
  for (int h = 0; h < 2; h++) {
    mma0(cr[h], K.ar[0][0], K.ar[1][0], K.ar[0][1], K.ar[1][1], in[0][h], in[1][h]);
    mma0(ci[h], K.ai[0][0], K.ai[1][0], K.ai[0][1], K.ai[1][1], in[0][h], in[1][h]);
  }
#pragma unroll
  for (int h = 0; h < 2; h++) {
    mma(cr[h], K.ar[0][0], K.ar[1][0] ^ NEG, K.ar[0][1], K.ar[1][1] ^ NEG, in[2][h], in[3][h]);
    mma(ci[h], K.ai[0][0], K.ai[1][0] ^ NEG, K.ai[0][1], K.ai[1][1] ^ NEG, in[2][h], in[3][h]);
  }
}
__device__ __forceinline__ void fft_s2(const FftC& K, const float (&cr)[2][4], const float (&ci)[2][4], float (&o)[4][4]) {
  uint32_t a[2][4];
#pragma unroll
  for (int h = 0; h < 2; h++)
#pragma unroll
    for (int i = 0; i < 4; i++) {
      float xr = cr[i & 1][2 * h + (i >> 1)], xi = ci[i & 1][2 * h + (i >> 1)];
      a[h][i] = pk(xr * K.tc[h][i] + xi * K.ts[h][i], xi * K.tc[h][i] - xr * K.ts[h][i]);
    }
  mma0(o[0], a[0][0], a[1][0], a[0][1], a[1][1], K.p[0], K.p[1]);
  mma0(o[1], a[0][0], a[1][0], a[0][1], a[1][1], K.p[0], K.q1);
  mma0(o[2], a[0][0], a[1][0], a[0][1], a[1][1], K.p[0], K.p[1] ^ NEG);
  mma0(o[3], a[0][0], a[1][0], a[0][1], a[1][1], K.p[0], K.q1 ^ NEG);
  mma(o[0], a[0][2], a[1][2], a[0][3], a[1][3], K.p[2], K.p[3]);
  mma(o[1], a[0][2], a[1][2], a[0][3], a[1][3], K.p[2] ^ NEG, K.q3 ^ NEG);
  mma(o[2], a[0][2], a[1][2], a[0][3], a[1][3], K.p[2], K.p[3] ^ NEG);
  mma(o[3], a[0][2], a[1][2], a[0][3], a[1][3], K.p[2] ^ NEG, K.q3);
}
__device__ __forceinline__ int zphys(int k) { return k + 8 * (k >> 5); }
__device__ __forceinline__ float gelu(float u) {
  float z = u * (0.7978845608028654f + 0.035677408136300125f * u * u), th;
  asm("tanh.approx.f32 %0, %1;" : "=f"(th) : "f"(z));
  float hu = 0.5f * u;
  return fmaf(hu, th, hu);
}

extern "C" __global__ void __cluster_dims__(2, 1, 1) __launch_bounds__(384, 1)
fused_kernel(const __grid_constant__ CUtensorMap tmW1, const __grid_constant__ CUtensorMap tmW2, const uint2* __restrict__ x, const unsigned short* __restrict__ wr,
             const unsigned short* __restrict__ wi, const char* __restrict__ w1, const uint32_t* __restrict__ b1,
             const char* __restrict__ w2, const unsigned short* __restrict__ b2, uint4* __restrict__ out) {
  extern __shared__ __align__(1024) char smem[];
  const uint32_t sb = (uint32_t)__cvta_generic_to_shared(smem);
  const uint32_t mb = sb + BAR_OFF;
  const int b = blockIdx.x, rank = b & 1, pr = b >> 1, dt = pr & 3, ot = pr >> 2;
  const int warp = __shfl_sync(0xffffffffu, threadIdx.x >> 5, 0), lane = threadIdx.x & 31;
  const int g = lane >> 2, t = lane & 3;

  if (warp < 8) {
    const int tid = threadIdx.x;
    uint32_t xw[2][4][2];
    {
      const uint2* xp = x + (size_t)(256 * warp + 2 * b) * 128 + 8 * t + g;
#pragma unroll
      for (int a = 0; a < 2; a++)
#pragma unroll
        for (int j = 0; j < 4; j++) { uint2 v = __ldg(xp + a * 128 + 32 * j); xw[a][j][0] = v.x; xw[a][j][1] = v.y; }
    }
    STAMP(0);
    asm volatile("barrier.cluster.arrive.relaxed.aligned;" ::: "memory");
    unsigned base = 0;
    if (tid == 0) base = __ldcg(&g_cnt[1 * 64]);
    FftC K;
    {
      float c, s;
#pragma unroll
      for (int h = 0; h < 2; h++)
#pragma unroll
        for (int j = 0; j < 2; j++) {
          cs<16>((2 * g + h) * (t + 4 * j), c, s);
          K.ar[h][j] = pk(ALPHA * c, ALPHA * s); K.ai[h][j] = pk(-ALPHA * s, ALPHA * c);
        }
#pragma unroll
      for (int i = 0; i < 4; i++) {
        cs<16>((4 * t + i) * (g >> 1) + 4 * (g & 1), c, s);
        K.p[i] = pk(ALPHA * c, ALPHA * s);
        if (i == 1) K.q1 = pk(-ALPHA * s, ALPHA * c);
        if (i == 3) K.q3 = pk(-ALPHA * s, ALPHA * c);
      }
#pragma unroll
      for (int h = 0; h < 2; h++)
#pragma unroll
        for (int i = 0; i < 4; i++) {
          cs<256>((2 * g + h) * (4 * t + i), c, s);
          K.tc[h][i] = c * (1.f / (ALPHA * ALPHA)); K.ts[h][i] = s * (1.f / (ALPHA * ALPHA));
        }
    }
    const int key = ((b >> 3) & 3) * 2 + (b & 1);
    const uint32_t zb = sb + XCH_OFF;
    float mean[2];
    {
      uint32_t a8[2][4]; float vc[4], vs[4];
#pragma unroll
      for (int a = 0; a < 2; a++)
#pragma unroll
        for (int u = 0; u < 2; u++) {
          float c, s; cs<2048>(g * (256 * (t + 4 * u) + 2 * b + a), c, s);
          a8[a][2 * u] = pk(c, s); a8[a][2 * u + 1] = pk(-s, c);
        }
#pragma unroll
      for (int i = 0; i < 4; i++) cs<512>(16 * warp + 8 * (i >> 1) + 2 * t + (i & 1) + 128, vc[i], vs[i]);
      asm volatile("barrier.cluster.wait.aligned;" ::: "memory");
#pragma unroll
      for (int a = 0; a < 2; a++) {
        float cr[2][4], ci[2][4], o[4][4];
        fft_s1(K, xw[a], cr, ci);
        float sm = ((cr[0][0] + cr[0][1]) + (cr[1][0] + cr[1][1])) + ((ci[0][0] + ci[0][1]) + (ci[1][0] + ci[1][1]));
        sm += __shfl_xor_sync(0xffffffffu, sm, 1); sm += __shfl_xor_sync(0xffffffffu, sm, 2);
        sm = g == 0 ? sm * (1.f / 32.f) : 0.f;
#pragma unroll
        for (int h = 0; h < 2; h++) { cr[h][0] -= sm; cr[h][1] -= sm; ci[h][0] -= sm; ci[h][1] -= sm; }
        mean[a] = __shfl_sync(0xffffffffu, sm, 0) * (1.f / (16.f * 1.1328125f));
        float q = 0.f, q2 = 0.f;
#pragma unroll
        for (int i = 0; i < 4; i++) { q = fmaf(cr[0][i], cr[0][i], q); q2 = fmaf(cr[1][i], cr[1][i], q2); q = fmaf(ci[0][i], ci[0][i], q); q2 = fmaf(ci[1][i], ci[1][i], q2); }
        q += q2;
#pragma unroll
        for (int m = 1; m < 32; m <<= 1) q += __shfl_xor_sync(0xffffffffu, q, m);
        float r = rsqrtf(q * (1.f / (512.f * 16.f * ALPHA * ALPHA)) + 1e-5f) * 4.76837158203125e-7f;
        fft_s2(K, cr, ci, o);
#pragma unroll
        for (int j = 0; j < 4; j++)
          sts64(zb + ((a * 8 + warp) * ZROW + zphys(16 * t + 64 * j) + 2 * g) * 4, pk(o[j][0] * r, o[j][1] * r), pk(o[j][2] * r, o[j][3] * r));
      }
      wbar();
      uint4* tp = g_T1 + (size_t)(g * 16 + warp) * 1024 + b * 8;
#pragma unroll
      for (int nt = 0; nt < 2; nt++) {
        const int k = 16 * warp + 8 * nt + g, km = k == 0 ? 128 : 256 - k;
        uint32_t lo[4], hi[4];
#pragma unroll
        for (int a = 0; a < 2; a++) {
          const uint32_t rb = zb + (a * 8 + t) * ZROW * 4;
          float A[4], B[4];
          mma0(A, a8[a][0], a8[a][1], a8[a][2], a8[a][3], lds32(rb + zphys(k) * 4), lds32(rb + (4 * ZROW + zphys(k)) * 4));
          mma0(B, a8[a][0] ^ 0x80000000u, a8[a][1] ^ 0x80000000u, a8[a][2] ^ 0x80000000u, a8[a][3] ^ 0x80000000u,
               lds32(rb + zphys(km) * 4), lds32(rb + (4 * ZROW + zphys(km)) * 4));
#pragma unroll
          for (int e = 0; e < 2; e++) {
            float sr = A[e] + B[e], si = A[2 + e] + B[2 + e], dr = A[e] - B[e], di = A[2 + e] - B[2 + e];
            float c = vc[2 * nt + e], s = vs[2 * nt + e];
            float gr = dr * c + di * s, gi = di * c - dr * s;
            float lr = sr + gr, li = si + gi, hr = sr - gr, hii = si - gi;
            if (nt == 0 && e == 0) {
              const bool sp = warp == 0 && t == 0;
              lr = sp ? 2.f * B[0] : lr; li = sp ? 2.f * B[2] : li;
              hr = sp ? 2.f * (A[0] - A[2]) : hr; hii = sp ? 2.f * (A[0] + A[2]) : hii;
            }
            lo[2 * a + e] = pk(lr, li); hi[2 * a + e] = pk(hr, hii);
          }
        }
        const int w = (t + 4 * nt) ^ key;
        tp[w] = make_uint4(lo[0], lo[1], lo[2], lo[3]);
        tp[8 * 1024 + w] = make_uint4(hi[0], hi[1], hi[2], hi[3]);
      }
      wbar();
      STAMP(1);
      if (tid == 0) cnt_arrive(0);
    }
#pragma unroll 1
    for (int pass = DRY ? 0 : 1; pass < 2; pass++) {
      const uint32_t off = (8 * t + g) * 128 + ((warp ^ (2 * t + (g & 1))) << 4);
      asm volatile("" : "+r"(pass));
      if (pass) {
        if (tid == 0) cnt_wait(0, base + NCTA);
        wbar();
#pragma unroll
        for (int j = 0; j < 4; j++)
          asm volatile("cp.async.cg.shared.global [%0], [%1], 16;" :: "r"(zb + j * 4096 + tid * 16), "l"(g_T1 + (size_t)b * 1024 + j * 256 + tid) : "memory");
        STAMP(2);
        mbar_wait(mb + MB_FILT * 8, 0);
        asm volatile("cp.async.wait_all;" ::: "memory");
        wbar();
        STAMP(3);
      }
      uint32_t in[2][4][2], fw[2][4][2];
#pragma unroll
      for (int j = 0; j < 4; j++) {
        uint4 v = lds128(zb + off + j * 4096);
        in[0][j][0] = v.x; in[1][j][0] = v.y; in[0][j][1] = v.z; in[1][j][1] = v.w;
      }
#pragma unroll
      for (int j = 0; j < 4; j++) {
        uint4 v = lds128(sb + FILT_OFF + off + j * 4096);
        fw[0][j][0] = v.x; fw[1][j][0] = v.y; fw[0][j][1] = v.z; fw[1][j][1] = v.w;
      }
#pragma unroll
      for (int sg = 0; sg < 2; sg++) {
        float cr[2][4], ci[2][4], o[4][4];
        fft_s1(K, in[sg], cr, ci);
        fft_s2(K, cr, ci, o);
#pragma unroll
        for (int j = 0; j < 4; j++)
#pragma unroll
          for (int h = 0; h < 2; h++) {
            float fr = blo(fw[sg][j][h]), fi = bhi(fw[sg][j][h]), xr = o[j][2 * h], xi = o[j][2 * h + 1];
            in[sg][j][h] = pk(xr * fi + xi * fr, xr * fr - xi * fi);
          }
        fft_s1(K, in[sg], cr, ci);
        fft_s2(K, cr, ci, o);
#pragma unroll
        for (int j = 0; j < 4; j++) { in[sg][j][0] = pk(o[j][0], o[j][1]); in[sg][j][1] = pk(o[j][2], o[j][3]); }
      }
#pragma unroll
      for (int j = 0; j < 4; j++) sts128(zb + off + j * 4096, make_uint4(in[0][j][0], in[1][j][0], in[0][j][1], in[1][j][1]));
      wbar();
#pragma unroll
      for (int j = 0; j < 4; j++) { uint4 v = lds128(zb + j * 4096 + tid * 16); if (pass) g_T2[(size_t)b * 1024 + j * 256 + tid] = v; }
      wbar();
      if (pass) STAMP(4); else STAMP(13);
    }
    if (tid == 0) cnt_arrive(1);
    {
      uint32_t a8[2][4]; float vc[4], vs[4];
#pragma unroll
      for (int a = 0; a < 2; a++)
#pragma unroll
        for (int u = 0; u < 2; u++) {
          float c, s; cs<2048>((t + 4 * u) * (256 * g + 2 * b + a), c, s);
          a8[a][2 * u] = pk(c, s); a8[a][2 * u + 1] = pk(-s, c);
        }
#pragma unroll
      for (int i = 0; i < 4; i++) cs<512>(16 * warp + 4 * t + i + 128, vc[i], vs[i]);
      if (tid == 0) cnt_wait(1, base + NCTA);
      wbar();
      STAMP(5);
      const uint4* tp = g_T2 + (size_t)(t * 16 + warp) * 1024 + b * 8 + (g ^ key);
      uint4 L0 = ldcg128(tp), L1 = ldcg128(tp + 64 * 1024), H0 = ldcg128(tp + 8 * 1024), H1 = ldcg128(tp + 72 * 1024);
      const uint32_t l0[4] = {L0.x, L0.y, L0.z, L0.w}, l1[4] = {L1.x, L1.y, L1.z, L1.w}, h0[4] = {H0.x, H0.y, H0.z, H0.w}, h1[4] = {H1.x, H1.y, H1.z, H1.w};
#pragma unroll
      for (int a = 0; a < 2; a++) {
        uint32_t zf[4], zm[4];
#pragma unroll
        for (int sg = 0; sg < 2; sg++) {
          float A[4], B[4];
          mma0(A, a8[a][0], a8[a][1], a8[a][2], a8[a][3], l0[2 * a + sg], l1[2 * a + sg]);
          mma0(B, a8[a][0], a8[a][1], a8[a][2], a8[a][3], h0[2 * a + sg], h1[2 * a + sg]);
#pragma unroll
          for (int e = 0; e < 2; e++) {
            const int i = 2 * e + sg;
            float sr = A[2 + e] + B[2 + e], si = A[e] + B[e], dr = A[2 + e] - B[2 + e], di = A[e] - B[e];
            float gr = dr * vc[i] - di * vs[i], gi = di * vc[i] + dr * vs[i];
            float fr = sr + gr, fi = si + gi, mr = sr - gr, mi = gi - si;
            if (i == 0) {
              const bool sp = warp == 0 && t == 0;
              fr = sp ? B[2] : fr; fi = sp ? -B[2] : fi;
              mr = sp ? 2.f * A[2] : mr; mi = sp ? -2.f * A[0] : mi;
            }
            zf[i] = pk(fi, fr); zm[i] = pk(mi, mr);
          }
        }
        const uint32_t rb = zb + (a * 8 + g) * ZROW * 4;
        const int k0 = 16 * warp + 4 * t;
        sts128(rb + zphys(k0) * 4, make_uint4(zf[0], zf[1], zf[2], zf[3]));
        sts32(rb + zphys(k0 == 0 ? 128 : 256 - k0) * 4, zm[0]);
        sts32(rb + zphys(255 - k0) * 4, zm[1]);
        sts32(rb + zphys(254 - k0) * 4, zm[2]);
        sts32(rb + zphys(253 - k0) * 4, zm[3]);
      }
      wbar();
#pragma unroll
      for (int a = 0; a < 2; a++) {
        uint32_t in[4][2];
#pragma unroll
        for (int j = 0; j < 4; j++) { uint2 v = lds64(zb + ((a * 8 + warp) * ZROW + zphys(16 * t + 64 * j) + 2 * g) * 4); in[j][0] = v.x; in[j][1] = v.y; }
        float cr[2][4], ci[2][4], o[4][4];
        fft_s1(K, in, cr, ci);
        fft_s2(K, cr, ci, o);
        float s1 = 0.f, s2 = 0.f;
        uint2* hp = (uint2*)g_h + (size_t)(256 * warp + 2 * b + a) * 128 + 8 * t + g;
#pragma unroll
        for (int j = 0; j < 4; j++) {
          uint32_t hw[2];
#pragma unroll
          for (int h = 0; h < 2; h++) {
            uint32_t y = pk(o[j][2 * h + 1], o[j][2 * h]);
            hw[h] = pk(blo(xw[a][j][h]) + blo(y), bhi(xw[a][j][h]) + bhi(y));
            float u0 = blo(hw[h]) - mean[a], u1 = bhi(hw[h]) - mean[a];
            o[j][2 * h] = u0; o[j][2 * h + 1] = u1;
            s1 += u0 + u1; s2 = fmaf(u0, u0, fmaf(u1, u1, s2));
          }
          hp[32 * j] = make_uint2(hw[0], hw[1]);
        }
#pragma unroll
        for (int m = 1; m < 32; m <<= 1) { s1 += __shfl_xor_sync(0xffffffffu, s1, m); s2 += __shfl_xor_sync(0xffffffffu, s2, m); }
        const float mu = s1 * (1.f / 512.f), var = fmaxf(s2 * (1.f / 512.f) - mu * mu, 0.f);
        const float r1 = rsqrtf(var + 1e-5f);
        const float r = r1 * rsqrtf(var * r1 * r1 + 1e-5f);
        char* np = (char*)g_Hn + (size_t)b * 4096 + (t >> 1) * 2048 + a * 1024 + warp * 128 + ((((t & 1) * 4 + (g >> 1)) ^ warp) << 4) + (g & 1) * 8;
#pragma unroll
        for (int j = 0; j < 4; j++)
          *(uint2*)(np + (size_t)j * 128 * 4096) = make_uint2(pk((o[j][0] - mu) * r, (o[j][1] - mu) * r), pk((o[j][2] - mu) * r, (o[j][3] - mu) * r));
      }
      asm volatile("fence.proxy.async.shared::cta;" ::: "memory");
      wbar();
      STAMP(6);
      if (tid == 0) { cnt_arrive(2 + (b >> 6)); sts32(sb + BASE_OFF, base); mbar_arrive(mb + MB_P3DONE * 8); }
    }
    const int wg = warp >> 2;
    const uint32_t peer_sb = mapa(sb, rank ^ 1);
    {
      uint32_t bias[11];
#pragma unroll
      for (int j = 0; j < 11; j++) bias[j] = (11 * ot + j < 172) ? __ldg(b1 + (11 * ot + j) * 4 + t) : 0u;
      float acc[44];
      const uint64_t da0 = mkdesc(sb + RING_OFF + wg * 2048, 0, 1024, 1), db0 = mkdesc(sb, 1408, 128, 0);
      mbar_wait(mb + MB_W1 * 8, 0);
#pragma unroll
      for (int i = 0; i < 32; i++) {
        mbar_wait(mb + (MB_FULL + i % NST) * 8, (i / NST) & 1);
        if (i == 0) STAMP(7);
        asm volatile("wgmma.fence.sync.aligned;" ::: "memory");
        wgmma_n88_ss<1, 1>(acc, da0 + (((i % NST) * 8192) >> 4), db0 + ((2 * i * 2816) >> 4), i > 0);
        wgmma_n88_ss<1, 1>(acc, da0 + (((i % NST) * 8192 + 4096) >> 4), db0 + (((2 * i + 1) * 2816) >> 4), 1);
        asm volatile("wgmma.commit_group.sync.aligned;" ::: "memory");
        if (i > 0) {
          asm volatile("wgmma.wait_group.sync.aligned 1;" ::: "memory");
          if ((tid & 127) == 0) { mbar_arrive(mb + (MB_EMPTY + (i - 1) % NST) * 8); if (i == 4) mbar_arrive_cluster(peer_sb + BAR_OFF + MB_PEER1 * 8); }
        }
      }
      asm volatile("wgmma.wait_group.sync.aligned 0;" ::: "memory");
#pragma unroll
      for (int i = 0; i < 44; i++) asm volatile("" : "+f"(acc[i]) :: "memory");
      if ((tid & 127) == 0) mbar_arrive(mb + (MB_EMPTY + 31 % NST) * 8);
      STAMP(8);
      float keep[22], send[22];
#pragma unroll
      for (int j = 0; j < 11; j++) {
        keep[2 * j] = rank ? acc[4 * j + 2] : acc[4 * j]; keep[2 * j + 1] = rank ? acc[4 * j + 3] : acc[4 * j + 1];
        send[2 * j] = rank ? acc[4 * j] : acc[4 * j + 2]; send[2 * j + 1] = rank ? acc[4 * j + 1] : acc[4 * j + 3];
      }
      mbar_wait_cluster(mb + MB_PEER1 * 8, 0);
#pragma unroll
      for (int j = 0; j < 5; j++) st_async4(peer_sb + j * 4096 + tid * 16, send[4 * j], send[4 * j + 1], send[4 * j + 2], send[4 * j + 3], peer_sb + BAR_OFF + MB_X1 * 8);
      st_async2(peer_sb + 5 * 4096 + tid * 8, send[20], send[21], peer_sb + BAR_OFF + MB_X1 * 8);
      mbar_wait_cluster(mb + MB_X1 * 8, 0);
#pragma unroll
      for (int j = 0; j < 5; j++) {
        uint4 v = lds128(sb + j * 4096 + tid * 16);
        keep[4 * j] += __uint_as_float(v.x); keep[4 * j + 1] += __uint_as_float(v.y); keep[4 * j + 2] += __uint_as_float(v.z); keep[4 * j + 3] += __uint_as_float(v.w);
      }
      { uint2 v = lds64(sb + 5 * 4096 + tid * 8); keep[20] += __uint_as_float(v.x); keep[21] += __uint_as_float(v.y); }
      uint32_t* up = (uint32_t*)g_U + ((size_t)dt * 172 + 11 * ot) * 512 + (4 * (warp >> 1) + (g >> 1)) * 32 + (2 * (2 * (warp & 1) + rank) + (g & 1)) * 4 + t;
#pragma unroll
      for (int j = 0; j < 11; j++) {
        uint32_t v = pk(gelu(keep[2 * j] + blo(bias[j])), gelu(keep[2 * j + 1] + bhi(bias[j])));
        if (11 * ot + j < 172) up[j * 512] = v;
      }
      asm volatile("fence.proxy.async.shared::cta;" ::: "memory");
      wbar();
      STAMP(9);
      if (tid == 0) { cnt_arrive(4 + dt); mbar_arrive(mb + MB_X1DONE * 8); }
    }
    {
      const int srow = 128 * ot + 16 * warp + 8 * rank + g;
      float acc[64];
      const uint64_t da0 = mkdesc(sb + wg * 4096, 0, 1024, 1), db0 = mkdesc(sb + RING_OFF, 2048, 128, 0);
      uint4 hv[4]; float bias2 = 0.f;
#pragma unroll
      for (int i = 0; i < 22; i++) {
        mbar_wait(mb + (MB_W2 + i) * 8, 0);
        mbar_wait(mb + (MB_FULL + (32 + i) % NST) * 8, ((32 + i) / NST) & 1);
        if (i == 0) STAMP(10);
        asm volatile("wgmma.fence.sync.aligned;" ::: "memory");
        wgmma_n128_ss<1, 0>(acc, da0 + ((((i + 3) % 22) * 8192) >> 4), db0 + ((((32 + i) % NST) * 8192) >> 4), i > 0);
        if (i < 21) wgmma_n128_ss<1, 0>(acc, da0 + ((((i + 3) % 22) * 8192 + 2048) >> 4), db0 + ((((32 + i) % NST) * 8192 + 4096) >> 4), 1);
        asm volatile("wgmma.commit_group.sync.aligned;" ::: "memory");
        if (i == 8) {
#pragma unroll
          for (int j = 0; j < 4; j++) hv[j] = ldcg128(g_h + (size_t)srow * 64 + dt * 16 + 4 * j + t);
          bias2 = __uint_as_float((uint32_t)__ldg(b2 + srow) << 16);
        }
        if (i > 0) {
          asm volatile("wgmma.wait_group.sync.aligned 1;" ::: "memory");
          if ((tid & 127) == 0) { if (i < 22 - NST + 1) mbar_arrive(mb + (MB_EMPTY + (32 + i - 1) % NST) * 8); if (i == 4) mbar_arrive_cluster(peer_sb + BAR_OFF + MB_PEER2 * 8); }
        }
      }
      asm volatile("wgmma.wait_group.sync.aligned 0;" ::: "memory");
#pragma unroll
      for (int i = 0; i < 64; i++) asm volatile("" : "+f"(acc[i]) :: "memory");
      STAMP(11);
      mbar_wait_cluster(mb + MB_PEER2 * 8, 0);
#pragma unroll
      for (int j = 0; j < 8; j++)
        st_async4(peer_sb + 3 * 8192 + j * 4096 + tid * 16, rank ? acc[8 * j] : acc[8 * j + 2], rank ? acc[8 * j + 1] : acc[8 * j + 3],
                  rank ? acc[8 * j + 4] : acc[8 * j + 6], rank ? acc[8 * j + 5] : acc[8 * j + 7], peer_sb + BAR_OFF + MB_X2 * 8);
      float keep[32];
#pragma unroll
      for (int j = 0; j < 16; j++) {
        const uint32_t hw = j % 4 == 0 ? hv[j / 4].x : j % 4 == 1 ? hv[j / 4].y : j % 4 == 2 ? hv[j / 4].z : hv[j / 4].w;
        keep[2 * j] = (rank ? acc[4 * j + 2] : acc[4 * j]) + (bias2 + blo(hw));
        keep[2 * j + 1] = (rank ? acc[4 * j + 3] : acc[4 * j + 1]) + (bias2 + bhi(hw));
      }
      mbar_wait_cluster(mb + MB_X2 * 8, 0);
#pragma unroll
      for (int j = 0; j < 4; j++) {
        uint4 v = lds128(sb + 3 * 8192 + (2 * j) * 4096 + tid * 16), w = lds128(sb + 3 * 8192 + (2 * j + 1) * 4096 + tid * 16);
        out[(size_t)srow * 64 + dt * 16 + 4 * j + t] =
            make_uint4(pk(keep[8 * j] + __uint_as_float(v.x), keep[8 * j + 1] + __uint_as_float(v.y)), pk(keep[8 * j + 2] + __uint_as_float(v.z), keep[8 * j + 3] + __uint_as_float(v.w)),
                       pk(keep[8 * j + 4] + __uint_as_float(w.x), keep[8 * j + 5] + __uint_as_float(w.y)), pk(keep[8 * j + 6] + __uint_as_float(w.z), keep[8 * j + 7] + __uint_as_float(w.w)));
      }
      STAMP(12);
    }
  } else {
    const int pw = warp - 8;
    if (pw == 0) {
      if (lane == 0) {
        for (int i = 0; i < NST; i++) { mbar_init(mb + (MB_FULL + i) * 8, 1); mbar_init(mb + (MB_EMPTY + i) * 8, 2); }
        for (int i = 0; i < 22; i++) mbar_init(mb + (MB_W2 + i) * 8, 1);
        for (int i = 0; i < 32; i++) mbar_init(mb + (MB_W1T + i) * 8, 1);
        mbar_init(mb + MB_P2IN * 8, 1); mbar_init(mb + MB_FILT * 8, 128); mbar_init(mb + MB_W1 * 8, 128);
        mbar_init(mb + MB_PEER1 * 8, 2); mbar_init(mb + MB_X1 * 8, 1); mbar_init(mb + MB_X1DONE * 8, 1);
        mbar_init(mb + MB_PEER2 * 8, 2); mbar_init(mb + MB_X2 * 8, 1); mbar_init(mb + MB_P3DONE * 8, 1);
        mbar_expect(mb + MB_X1 * 8, 22528); mbar_expect(mb + MB_X2 * 8, 32768);
        asm volatile("fence.mbarrier_init.release.cluster;" ::: "memory");
      }
      __syncwarp();
    }
    STAMP(0);
    asm volatile("bar.sync 2, 128;" ::: "memory");
    asm volatile("barrier.cluster.arrive.relaxed.aligned;" ::: "memory");
    auto w1_issue = [&](int i) {
      if (elect()) { mbar_expect(mb + (MB_W1T + i) * 8, 5632); tma3d(sb + i * 5632, &tmW1, 88 * ot, 0, 128 * rank + 4 * i, mb + (MB_W1T + i) * 8); }
      __syncwarp();
    };
    if (!W1_LATE && pw < W1_WARPS) for (int i = 0; i < W1_DEPTH; i++) w1_issue(pw + W1_WARPS * i);
    {
      const int j1 = b >> 4, q = b & 15, slot = lane & 15, h = lane >> 4;
      const bool hi = q >= 8;
      const int k = 16 * (q & 7) + slot, col = hi ? 256 - k : (k == 0 ? 128 : k);
#pragma unroll 1
      for (int it = 0; it < 2; it++) {
        uint32_t vr[16], vi[16];
#pragma unroll
        for (int n = 0; n < 16; n++) {
          const int c = pw * 32 + it * 16 + n;
          int j = j1 + 8 * (2 * c + h);
          if (hi) j = (2048 - j) & 2047;
          vr[n] = __ldg(wr + j * DF + col); vi[n] = __ldg(wi + j * DF + col);
        }
#pragma unroll
        for (int n = 0; n < 16; n++) {
          const int c = pw * 32 + it * 16 + n;
          sts32(sb + FILT_OFF + c * 128 + (((slot >> 1) ^ (((c >> 3) & 3) * 2 + (c & 1))) << 4) + h * 8 + (slot & 1) * 4,
                (vr[n] | (vi[n] << 16)) ^ (hi ? 0x80000000u : 0u));
        }
      }
      mbar_arrive(mb + MB_FILT * 8);
    }
    STAMP(1);
    {
      if (W1_LATE && pw < W1_WARPS) for (int i = 0; i < W1_DEPTH; i++) w1_issue(pw + W1_WARPS * i);
      const uint32_t rd = ((lane & 7) * 11 + (lane >> 3)) * 16, wr = lane * 16;
#pragma unroll 1
      for (int box = pw < W1_WARPS ? pw : 32; box < 32; box += W1_WARPS) {
        mbar_wait(mb + (MB_W1T + box) * 8, 0);
        if (box + W1_WARPS * W1_DEPTH < 32) w1_issue(box + W1_WARPS * W1_DEPTH);
        const uint32_t p = sb + box * 5632;
        uint4 v[4][3];
#pragma unroll
        for (int n = 0; n < 4; n++) { v[n][0] = lds128(p + n * 1408 + rd); v[n][1] = lds128(p + n * 1408 + rd + 64); if (lane < 24) v[n][2] = lds128(p + n * 1408 + rd + 128); }
        __syncwarp();
#pragma unroll
        for (int n = 0; n < 4; n++) { sts128(p + n * 1408 + wr, v[n][0]); sts128(p + n * 1408 + wr + 512, v[n][1]); if (lane < 24) sts128(p + n * 1408 + wr + 1024, v[n][2]); }
      }
      if (lane == 0) asm volatile("cp.async.bulk.prefetch.L2.global [%0], %1;" :: "l"(w2 + (size_t)(b * 4 + pw) * 11008), "r"(11008) : "memory");
      asm volatile("fence.proxy.async.shared::cta;" ::: "memory");
      mbar_arrive(mb + MB_W1 * 8);
    }
    STAMP(2);
    asm volatile("barrier.cluster.wait.aligned;" ::: "memory");
    if (pw == 0) {
      mbar_wait(mb + MB_P3DONE * 8, 0);
      const unsigned base = lds32(sb + BASE_OFF);
      if (lane == 0) cnt_wait(2 + rank, (base >> 1) + 64);
      __syncwarp();
      STAMP(3);
      asm volatile("fence.proxy.async.global;" ::: "memory");
      const char* hsrc = (const char*)g_Hn + ((size_t)dt * 128 + 64 * rank) * 4096;
      int nw2 = 0;
#pragma unroll
      for (int i = 0; i < 32 + NST; i++) {
        if (i >= NST) mbar_wait(mb + (MB_EMPTY + i % NST) * 8, ((i / NST) & 1) ^ 1);
        if (elect()) {
          if (i < 32) { mbar_expect(mb + (MB_FULL + i % NST) * 8, 8192); bulk_ld(sb + RING_OFF + (i % NST) * 8192, hsrc + i * 8192, 8192, mb + (MB_FULL + i % NST) * 8); }
        }
        if (i >= W2_START) {
#pragma unroll
          for (int rep = 0; rep < 19; rep++) {
            if (nw2 < 19 && (nw2 + 4) * 8192 <= (i - NST + 1) * 5632 && (rep < W2_RATE || i == 31 + NST)) {
              if (elect()) { mbar_expect(mb + (MB_W2 + nw2) * 8, 8192); tma3d(sb + (nw2 + 3) * 8192, &tmW2, 0, 688 * rank + 32 * nw2, 2 * ot, mb + (MB_W2 + nw2) * 8); }
              nw2++;
            }
          }
        }
      }
      mbar_wait(mb + MB_X1DONE * 8, 0);
      if (elect()) {
#pragma unroll
        for (int n = 19; n < 22; n++) { mbar_expect(mb + (MB_W2 + n) * 8, 8192); tma3d(sb + (n - 19) * 8192, &tmW2, 0, 688 * rank + 32 * n, 2 * ot, mb + (MB_W2 + n) * 8); }
      }
      STAMP(4);
      if (lane == 0) cnt_wait(4 + dt, (base >> 2) + 32);
      __syncwarp();
      STAMP(5);
      asm volatile("fence.proxy.async.global;" ::: "memory");
      const char* usrc = (const char*)g_U + ((size_t)dt * 172 + 86 * rank) * 2048;
#pragma unroll
      for (int i = 0; i < 22; i++) {
        if (i >= NST) mbar_wait(mb + (MB_EMPTY + (32 + i) % NST) * 8, (((32 + i) / NST) & 1) ^ 1);
        if (elect()) {
          const int bytes = i < 21 ? 8192 : 4096;
          mbar_expect(mb + (MB_FULL + (32 + i) % NST) * 8, bytes);
          bulk_ld(sb + RING_OFF + ((32 + i) % NST) * 8192, usrc + i * 8192, bytes, mb + (MB_FULL + (32 + i) % NST) * 8);
        }
      }
      STAMP(6);
    }
  }
}

typedef CUresult (*EncodeFn)(CUtensorMap*, CUtensorMapDataType, cuuint32_t, void*, const cuuint64_t*, const cuuint64_t*, const cuuint32_t*,
                             const cuuint32_t*, CUtensorMapInterleave, CUtensorMapSwizzle, CUtensorMapL2promotion, CUtensorMapFloatOOBfill);

extern "C" void kernel_launch(void* const* d_in, const int* in_sizes, int n_in, void* d_out, int out_size) {
  static EncodeFn enc = nullptr;
  if (!enc) {
    void* fn = nullptr; cudaDriverEntryPointQueryResult st;
    cudaGetDriverEntryPoint("cuTensorMapEncodeTiled", &fn, cudaEnableDefault, &st);
    enc = (EncodeFn)fn;
    cudaFuncSetAttribute(fused_kernel, cudaFuncAttributeMaxDynamicSharedMemorySize, SMEM_BYTES);
  }
  CUtensorMap tm, tm1;
  {
    cuuint64_t dims[3] = {(cuuint64_t)F_, 8, 256}, strides[2] = {(cuuint64_t)256 * F_ * 2, F_ * 2};
    cuuint32_t box[3] = {88, 8, 4}, es[3] = {1, 1, 1};
    enc(&tm1, CU_TENSOR_MAP_DATA_TYPE_BFLOAT16, 3, d_in[4], dims, strides, box, es, CU_TENSOR_MAP_INTERLEAVE_NONE, CU_TENSOR_MAP_SWIZZLE_NONE,
        W1_PROMO, CU_TENSOR_MAP_FLOAT_OOB_FILL_NONE);
  }
  {
    cuuint64_t dims[3] = {64, (cuuint64_t)F_, S_ / 64}, strides[2] = {S_ * 2, 128};
    cuuint32_t box[3] = {64, 32, 2}, es[3] = {1, 1, 1};
    enc(&tm, CU_TENSOR_MAP_DATA_TYPE_BFLOAT16, 3, d_in[6], dims, strides, box, es, CU_TENSOR_MAP_INTERLEAVE_NONE, CU_TENSOR_MAP_SWIZZLE_128B,
        CU_TENSOR_MAP_L2_PROMOTION_L2_256B, CU_TENSOR_MAP_FLOAT_OOB_FILL_NONE);
  }
  fused_kernel<<<NCTA, 384, SMEM_BYTES, cudaStreamPerThread>>>(tm1, tm, (const uint2*)d_in[0], (const unsigned short*)d_in[1], (const unsigned short*)d_in[2],
                                          (const char*)d_in[4], (const uint32_t*)d_in[5], (const char*)d_in[6], (const unsigned short*)d_in[7], (uint4*)d_out);
}
```

```cpp
#include <cuda_runtime.h>
#include <cuda.h>
#include <cuda_bf16.h>
#include <stdint.h>
#define W1_LATE 1
#define W1_PROMO CU_TENSOR_MAP_L2_PROMOTION_NONE
#define W2_RATE 1
#define PF_MODE 0
#define W1_DEPTH 1
#define W1_WARPS 3
#define W2_PRE 19
#define W2_RATE2 1
template<int TA, int TB> __device__ __forceinline__ void wgmma_n88_ss(float (&d)[44], uint64_t da, uint64_t db, int sd) {
  asm volatile("{\n.reg .pred p;\nsetp.ne.b32 p, %46, 0;\n"
    "wgmma.mma_async.sync.aligned.m64n88k16.f32.bf16.bf16 {%0, %1, %2, %3, %4, %5, %6, %7, %8, %9, %10, %11, %12, %13, %14, %15, %16, %17, %18, %19, %20, %21, %22, %23, %24, %25, %26, %27, %28, %29, %30, %31, %32, %33, %34, %35, %36, %37, %38, %39, %40, %41, %42, %43}, %44, %45, p, 1, 1, %47, %48;\n}\n"
    : "+f"(d[0]), "+f"(d[1]), "+f"(d[2]), "+f"(d[3]), "+f"(d[4]), "+f"(d[5]), "+f"(d[6]), "+f"(d[7]), "+f"(d[8]), "+f"(d[9]), "+f"(d[10]), "+f"(d[11]), "+f"(d[12]), "+f"(d[13]), "+f"(d[14]), "+f"(d[15]), "+f"(d[16]), "+f"(d[17]), "+f"(d[18]), "+f"(d[19]), "+f"(d[20]), "+f"(d[21]), "+f"(d[22]), "+f"(d[23]), "+f"(d[24]), "+f"(d[25]), "+f"(d[26]), "+f"(d[27]), "+f"(d[28]), "+f"(d[29]), "+f"(d[30]), "+f"(d[31]), "+f"(d[32]), "+f"(d[33]), "+f"(d[34]), "+f"(d[35]), "+f"(d[36]), "+f"(d[37]), "+f"(d[38]), "+f"(d[39]), "+f"(d[40]), "+f"(d[41]), "+f"(d[42]), "+f"(d[43]) : "l"(da), "l"(db), "r"(sd), "n"(TA), "n"(TB));
}
template<int TA, int TB> __device__ __forceinline__ void wgmma_n128_ss(float (&d)[64], uint64_t da, uint64_t db, int sd) {
  asm volatile("{\n.reg .pred p;\nsetp.ne.b32 p, %66, 0;\n"
    "wgmma.mma_async.sync.aligned.m64n128k16.f32.bf16.bf16 {%0, %1, %2, %3, %4, %5, %6, %7, %8, %9, %10, %11, %12, %13, %14, %15, %16, %17, %18, %19, %20, %21, %22, %23, %24, %25, %26, %27, %28, %29, %30, %31, %32, %33, %34, %35, %36, %37, %38, %39, %40, %41, %42, %43, %44, %45, %46, %47, %48, %49, %50, %51, %52, %53, %54, %55, %56, %57, %58, %59, %60, %61, %62, %63}, %64, %65, p, 1, 1, %67, %68;\n}\n"
    : "+f"(d[0]), "+f"(d[1]), "+f"(d[2]), "+f"(d[3]), "+f"(d[4]), "+f"(d[5]), "+f"(d[6]), "+f"(d[7]), "+f"(d[8]), "+f"(d[9]), "+f"(d[10]), "+f"(d[11]), "+f"(d[12]), "+f"(d[13]), "+f"(d[14]), "+f"(d[15]), "+f"(d[16]), "+f"(d[17]), "+f"(d[18]), "+f"(d[19]), "+f"(d[20]), "+f"(d[21]), "+f"(d[22]), "+f"(d[23]), "+f"(d[24]), "+f"(d[25]), "+f"(d[26]), "+f"(d[27]), "+f"(d[28]), "+f"(d[29]), "+f"(d[30]), "+f"(d[31]), "+f"(d[32]), "+f"(d[33]), "+f"(d[34]), "+f"(d[35]), "+f"(d[36]), "+f"(d[37]), "+f"(d[38]), "+f"(d[39]), "+f"(d[40]), "+f"(d[41]), "+f"(d[42]), "+f"(d[43]), "+f"(d[44]), "+f"(d[45]), "+f"(d[46]), "+f"(d[47]), "+f"(d[48]), "+f"(d[49]), "+f"(d[50]), "+f"(d[51]), "+f"(d[52]), "+f"(d[53]), "+f"(d[54]), "+f"(d[55]), "+f"(d[56]), "+f"(d[57]), "+f"(d[58]), "+f"(d[59]), "+f"(d[60]), "+f"(d[61]), "+f"(d[62]), "+f"(d[63]) : "l"(da), "l"(db), "r"(sd), "n"(TA), "n"(TB));
}

constexpr int S_ = 2048, D_ = 512, F_ = 1376, DF = 257;
constexpr int NCTA = 128;
constexpr int W_BYTES = 180224;
constexpr int RING_OFF = W_BYTES;
constexpr int NST = 6;
constexpr int BAR_OFF = RING_OFF + NST * 8192;
constexpr int SMEM_BYTES = BAR_OFF + 1024;
constexpr int FILT_OFF = RING_OFF;
constexpr int XCH_OFF = RING_OFF + 16384;
constexpr int ZROW = 328;
constexpr int MB_FULL = 0, MB_EMPTY = 6, MB_W2 = 12, MB_P2IN = 34, MB_FILT = 35, MB_W1 = 36, MB_PEER1 = 37, MB_X1 = 38,
              MB_X1DONE = 39, MB_PEER2 = 40, MB_X2 = 41, MB_P3DONE = 42, MB_W1T = 43;
constexpr int BASE_OFF = BAR_OFF + 960;
#define W2_START 18

__device__ uint4 g_T1[NCTA * 1024];
__device__ uint4 g_T2[NCTA * 1024];
__device__ uint4 g_h[S_ * D_ / 8];
__device__ uint4 g_Hn[4 * 128 * 256];
__device__ uint4 g_U[4 * 172 * 128];
__device__ unsigned g_cnt[8 * 4 * 64];
#define STAMP(i)

__device__ __forceinline__ void mbar_init(uint32_t b, int c) { asm volatile("mbarrier.init.shared::cta.b64 [%0], %1;" :: "r"(b), "r"(c) : "memory"); }
__device__ __forceinline__ void mbar_expect(uint32_t b, int bytes) { asm volatile("mbarrier.arrive.expect_tx.shared::cta.b64 _, [%0], %1;" :: "r"(b), "r"(bytes) : "memory"); }
__device__ __forceinline__ void mbar_arrive(uint32_t b) { asm volatile("mbarrier.arrive.shared::cta.b64 _, [%0];" :: "r"(b) : "memory"); }
__device__ __forceinline__ void mbar_arrive_cluster(uint32_t remote) { asm volatile("mbarrier.arrive.relaxed.cluster.shared::cluster.b64 _, [%0];" :: "r"(remote) : "memory"); }
__device__ __forceinline__ uint32_t mapa(uint32_t a, uint32_t cta) { uint32_t r; asm("mapa.shared::cluster.u32 %0, %1, %2;" : "=r"(r) : "r"(a), "r"(cta)); return r; }
__device__ __forceinline__ void mbar_wait(uint32_t b, int ph) {
  asm volatile("{\n.reg .pred p;\n.reg .u32 n;\nmov.u32 n, 0;\nL_W:\n"
               "mbarrier.try_wait.parity.shared::cta.b64 p, [%0], %1;\n@p bra L_D;\n"
               "add.u32 n, n, 1;\nsetp.lt.u32 p, n, 4000000;\n@p bra L_W;\ntrap;\nL_D:\n}" :: "r"(b), "r"(ph) : "memory");
}
__device__ __forceinline__ void mbar_wait_cluster(uint32_t b, int ph) {
  asm volatile("{\n.reg .pred p;\n.reg .u32 n;\nmov.u32 n, 0;\nL_W:\n"
               "mbarrier.try_wait.parity.acquire.cluster.shared::cta.b64 p, [%0], %1;\n@p bra L_D;\n"
               "add.u32 n, n, 1;\nsetp.lt.u32 p, n, 4000000;\n@p bra L_W;\ntrap;\nL_D:\n}" :: "r"(b), "r"(ph) : "memory");
}
__device__ __forceinline__ void bulk_ld(uint32_t dst, const void* src, int bytes, uint32_t bar) {
  asm volatile("cp.async.bulk.shared::cluster.global.mbarrier::complete_tx::bytes [%0], [%1], %2, [%3];" :: "r"(dst), "l"(src), "r"(bytes), "r"(bar) : "memory");
}
__device__ __forceinline__ void tma3d(uint32_t dst, const CUtensorMap* tm, int c0, int c1, int c2, uint32_t bar) {
  asm volatile("cp.async.bulk.tensor.3d.shared::cluster.global.mbarrier::complete_tx::bytes [%0], [%1, {%3, %4, %5}], [%2];"
               :: "r"(dst), "l"(tm), "r"(bar), "r"(c0), "r"(c1), "r"(c2) : "memory");
}
__device__ __forceinline__ bool elect() { uint32_t p; asm volatile("{.reg .pred p; elect.sync _|p, 0xffffffff; selp.b32 %0, 1, 0, p;}" : "=r"(p)); return p; }
__device__ __forceinline__ uint64_t mkdesc(uint32_t addr, uint32_t lbo, uint32_t sbo, uint32_t sw) {
  return (uint64_t)((addr & 0x3FFFF) >> 4) | ((uint64_t)(lbo >> 4) << 16) | ((uint64_t)(sbo >> 4) << 32) | ((uint64_t)sw << 62);
}
__device__ __forceinline__ uint32_t pk(float lo, float hi) { uint32_t r; asm("cvt.rn.bf16x2.f32 %0, %1, %2;" : "=r"(r) : "f"(hi), "f"(lo)); return r; }
__device__ __forceinline__ float blo(uint32_t w) { return __uint_as_float(w << 16); }
__device__ __forceinline__ float bhi(uint32_t w) { return __uint_as_float(w & 0xffff0000u); }
__device__ __forceinline__ void mma(float (&c)[4], uint32_t a0, uint32_t a1, uint32_t a2, uint32_t a3, uint32_t b0, uint32_t b1) {
  asm("mma.sync.aligned.m16n8k16.row.col.f32.bf16.bf16.f32 {%0,%1,%2,%3}, {%4,%5,%6,%7}, {%8,%9}, {%0,%1,%2,%3};"
      : "+f"(c[0]), "+f"(c[1]), "+f"(c[2]), "+f"(c[3]) : "r"(a0), "r"(a1), "r"(a2), "r"(a3), "r"(b0), "r"(b1));
}
__device__ __forceinline__ void mma0(float (&c)[4], uint32_t a0, uint32_t a1, uint32_t a2, uint32_t a3, uint32_t b0, uint32_t b1) {
  asm("mma.sync.aligned.m16n8k16.row.col.f32.bf16.bf16.f32 {%0,%1,%2,%3}, {%4,%5,%6,%7}, {%8,%9}, {%10,%10,%10,%10};"
      : "=f"(c[0]), "=f"(c[1]), "=f"(c[2]), "=f"(c[3]) : "r"(a0), "r"(a1), "r"(a2), "r"(a3), "r"(b0), "r"(b1), "f"(0.f));
}
__device__ __forceinline__ void wbar() { asm volatile("bar.sync 1, 256;" ::: "memory"); }
__device__ __forceinline__ void sts32(uint32_t a, uint32_t v) { asm volatile("st.shared.b32 [%0], %1;" :: "r"(a), "r"(v) : "memory"); }
__device__ __forceinline__ void sts64(uint32_t a, uint32_t x, uint32_t y) { asm volatile("st.shared.v2.b32 [%0], {%1,%2};" :: "r"(a), "r"(x), "r"(y) : "memory"); }
__device__ __forceinline__ void sts128(uint32_t a, uint4 v) { asm volatile("st.shared.v4.b32 [%0], {%1,%2,%3,%4};" :: "r"(a), "r"(v.x), "r"(v.y), "r"(v.z), "r"(v.w) : "memory"); }
__device__ __forceinline__ uint32_t lds32(uint32_t a) { uint32_t v; asm volatile("ld.shared.b32 %0, [%1];" : "=r"(v) : "r"(a) : "memory"); return v; }
__device__ __forceinline__ uint2 lds64(uint32_t a) { uint2 v; asm volatile("ld.shared.v2.b32 {%0,%1}, [%2];" : "=r"(v.x), "=r"(v.y) : "r"(a) : "memory"); return v; }
__device__ __forceinline__ uint4 lds128(uint32_t a) { uint4 v; asm volatile("ld.shared.v4.b32 {%0,%1,%2,%3}, [%4];" : "=r"(v.x), "=r"(v.y), "=r"(v.z), "=r"(v.w) : "r"(a) : "memory"); return v; }
__device__ __forceinline__ uint4 ldcg128(const void* p) { uint4 v; asm volatile("ld.global.cg.v4.b32 {%0,%1,%2,%3}, [%4];" : "=r"(v.x), "=r"(v.y), "=r"(v.z), "=r"(v.w) : "l"(p) : "memory"); return v; }
__device__ __forceinline__ void st_async4(uint32_t a, float x, float y, float z, float w, uint32_t bar) {
  asm volatile("st.async.weak.shared::cluster.mbarrier::complete_tx::bytes.v4.f32 [%0], {%1,%2,%3,%4}, [%5];" :: "r"(a), "f"(x), "f"(y), "f"(z), "f"(w), "r"(bar) : "memory");
}
__device__ __forceinline__ void st_async2(uint32_t a, float x, float y, uint32_t bar) {
  asm volatile("st.async.weak.shared::cluster.mbarrier::complete_tx::bytes.v2.f32 [%0], {%1,%2}, [%3];" :: "r"(a), "f"(x), "f"(y), "r"(bar) : "memory");
}
constexpr int NREP = 4;
__device__ __forceinline__ void cnt_arrive(int i, int lane) {
  if (lane < NREP) asm volatile("red.relaxed.gpu.global.add.u32 [%0], 1;" :: "l"(&g_cnt[(i * NREP + lane) * 64]) : "memory");
}
__device__ __forceinline__ void cnt_wait(int i, int rep, unsigned target) {
  unsigned v; int n = 0;
  do { asm volatile("ld.relaxed.gpu.global.u32 %0, [%1];" : "=r"(v) : "l"(&g_cnt[(i * NREP + rep) * 64]) : "memory"); if (++n > 2000000) __trap(); } while ((int)(v - target) < 0);
}
__device__ __forceinline__ void fence_gpu() { asm volatile("fence.acq_rel.gpu;" ::: "memory"); }
__device__ __forceinline__ void tag_check(uint4& v, const uint4* p, uint32_t tag) {
  int n = 0;
  while ((v.x ^ tag) & 1) {
    asm volatile("ld.relaxed.gpu.global.v4.b32 {%0,%1,%2,%3}, [%4];" : "=r"(v.x), "=r"(v.y), "=r"(v.z), "=r"(v.w) : "l"(p) : "memory");
    if (++n > 2000000) __trap();
  }
}
template <int N> __device__ __forceinline__ void cs(int n, float& c, float& s) {
  n = ((n + N / 2) & (N - 1)) - N / 2;
  float a = (float)n * (6.283185307179586f / N);
  c = __cosf(a); s = __sinf(a);
}
constexpr float ALPHA = 1.13288f;
struct FftC { uint32_t ar[2][2], ai[2][2], p[4], q1, q3; float tc[2][4], ts[2][4]; };
constexpr uint32_t NEG = 0x80008000u;

__device__ __forceinline__ void fft_s1(const FftC& K, const uint32_t (&in)[4][2], float (&cr)[2][4], float (&ci)[2][4]) {
#pragma unroll
  for (int h = 0; h < 2; h++) {
    mma0(cr[h], K.ar[0][0], K.ar[1][0], K.ar[0][1], K.ar[1][1], in[0][h], in[1][h]);
    mma0(ci[h], K.ai[0][0], K.ai[1][0], K.ai[0][1], K.ai[1][1], in[0][h], in[1][h]);
  }
#pragma unroll
  for (int h = 0; h < 2; h++) {
    mma(cr[h], K.ar[0][0], K.ar[1][0] ^ NEG, K.ar[0][1], K.ar[1][1] ^ NEG, in[2][h], in[3][h]);
    mma(ci[h], K.ai[0][0], K.ai[1][0] ^ NEG, K.ai[0][1], K.ai[1][1] ^ NEG, in[2][h], in[3][h]);
  }
}
__device__ __forceinline__ void fft_s2(const FftC& K, const float (&cr)[2][4], const float (&ci)[2][4], float (&o)[4][4]) {
  uint32_t a[2][4];
#pragma unroll
  for (int h = 0; h < 2; h++)
#pragma unroll
    for (int i = 0; i < 4; i++) {
      float xr = cr[i & 1][2 * h + (i >> 1)], xi = ci[i & 1][2 * h + (i >> 1)];
      a[h][i] = pk(xr * K.tc[h][i] + xi * K.ts[h][i], xi * K.tc[h][i] - xr * K.ts[h][i]);
    }
  mma0(o[0], a[0][0], a[1][0], a[0][1], a[1][1], K.p[0], K.p[1]);
  mma0(o[1], a[0][0], a[1][0], a[0][1], a[1][1], K.p[0], K.q1);
  mma0(o[2], a[0][0], a[1][0], a[0][1], a[1][1], K.p[0], K.p[1] ^ NEG);
  mma0(o[3], a[0][0], a[1][0], a[0][1], a[1][1], K.p[0], K.q1 ^ NEG);
  mma(o[0], a[0][2], a[1][2], a[0][3], a[1][3], K.p[2], K.p[3]);
  mma(o[1], a[0][2], a[1][2], a[0][3], a[1][3], K.p[2] ^ NEG, K.q3 ^ NEG);
  mma(o[2], a[0][2], a[1][2], a[0][3], a[1][3], K.p[2], K.p[3] ^ NEG);
  mma(o[3], a[0][2], a[1][2], a[0][3], a[1][3], K.p[2] ^ NEG, K.q3);
}
__device__ __forceinline__ int zphys(int k) { return k + 8 * (k >> 5); }
__device__ __forceinline__ float gelu(float u) {
  float z = u * (0.7978845608028654f + 0.035677408136300125f * u * u), th;
  asm("tanh.approx.f32 %0, %1;" : "=f"(th) : "f"(z));
  float hu = 0.5f * u;
  return fmaf(hu, th, hu);
}

extern "C" __global__ void __cluster_dims__(2, 1, 1) __launch_bounds__(384, 1)
fused_kernel(const __grid_constant__ CUtensorMap tmW1, const __grid_constant__ CUtensorMap tmW2, const uint2* __restrict__ x, const unsigned short* __restrict__ wr,
             const unsigned short* __restrict__ wi, const char* __restrict__ w1, const uint32_t* __restrict__ b1,
             const char* __restrict__ w2, const unsigned short* __restrict__ b2, uint4* __restrict__ out) {
  extern __shared__ __align__(1024) char smem[];
  const uint32_t sb = (uint32_t)__cvta_generic_to_shared(smem);
  const uint32_t mb = sb + BAR_OFF;
  const int b = blockIdx.x, rank = b & 1, pr = b >> 1, dt = pr & 3, ot = pr >> 2;
  const int warp = __shfl_sync(0xffffffffu, threadIdx.x >> 5, 0), lane = threadIdx.x & 31;
  const int g = lane >> 2, t = lane & 3;

  if (warp < 8) {
    const int tid = threadIdx.x;
    uint32_t xw[2][4][2];
    {
      const uint2* xp = x + (size_t)(256 * warp + 2 * b) * 128 + 8 * t + g;
#pragma unroll
      for (int a = 0; a < 2; a++)
#pragma unroll
        for (int j = 0; j < 4; j++) { uint2 v = __ldg(xp + a * 128 + 32 * j); xw[a][j][0] = v.x; xw[a][j][1] = v.y; }
    }
    STAMP(0);
    asm volatile("barrier.cluster.arrive.relaxed.aligned;" ::: "memory");
    const int rep = ot & (NREP - 1);
    const unsigned base = __ldcg(&g_cnt[(1 * NREP + rep) * 64]);
    const uint32_t tag = (~base >> 7) & 1;
    FftC K;
    {
      float c, s;
#pragma unroll
      for (int h = 0; h < 2; h++)
#pragma unroll
        for (int j = 0; j < 2; j++) {
          cs<16>((2 * g + h) * (t + 4 * j), c, s);
          K.ar[h][j] = pk(ALPHA * c, ALPHA * s); K.ai[h][j] = pk(-ALPHA * s, ALPHA * c);
        }
#pragma unroll
      for (int i = 0; i < 4; i++) {
        cs<16>((4 * t + i) * (g >> 1) + 4 * (g & 1), c, s);
        K.p[i] = pk(ALPHA * c, ALPHA * s);
        if (i == 1) K.q1 = pk(-ALPHA * s, ALPHA * c);
        if (i == 3) K.q3 = pk(-ALPHA * s, ALPHA * c);
      }
#pragma unroll
      for (int h = 0; h < 2; h++)
#pragma unroll
        for (int i = 0; i < 4; i++) {
          cs<256>((2 * g + h) * (4 * t + i), c, s);
          K.tc[h][i] = c * (1.f / (ALPHA * ALPHA)); K.ts[h][i] = s * (1.f / (ALPHA * ALPHA));
        }
    }
    const int key = ((b >> 3) & 3) * 2 + (b & 1);
    const uint32_t zb = sb + XCH_OFF;
    float mean[2];
    {
      uint32_t a8[2][4]; float vc[4], vs[4];
#pragma unroll
      for (int a = 0; a < 2; a++)
#pragma unroll
        for (int u = 0; u < 2; u++) {
          float c, s; cs<2048>(g * (256 * (t + 4 * u) + 2 * b + a), c, s);
          a8[a][2 * u] = pk(c, s); a8[a][2 * u + 1] = pk(-s, c);
        }
#pragma unroll
      for (int i = 0; i < 4; i++) cs<512>(16 * warp + 8 * (i >> 1) + 2 * t + (i & 1) + 128, vc[i], vs[i]);
#pragma unroll
      for (int a = 0; a < 2; a++) {
        float cr[2][4], ci[2][4], o[4][4];
        fft_s1(K, xw[a], cr, ci);
        float sm = ((cr[0][0] + cr[0][1]) + (cr[1][0] + cr[1][1])) + ((ci[0][0] + ci[0][1]) + (ci[1][0] + ci[1][1]));
        sm += __shfl_xor_sync(0xffffffffu, sm, 1); sm += __shfl_xor_sync(0xffffffffu, sm, 2);
        sm = g == 0 ? sm * (1.f / 32.f) : 0.f;
#pragma unroll
        for (int h = 0; h < 2; h++) { cr[h][0] -= sm; cr[h][1] -= sm; ci[h][0] -= sm; ci[h][1] -= sm; }
        mean[a] = __shfl_sync(0xffffffffu, sm, 0) * (1.f / (16.f * 1.1328125f));
        float q = 0.f, q2 = 0.f;
#pragma unroll
        for (int i = 0; i < 4; i++) { q = fmaf(cr[0][i], cr[0][i], q); q2 = fmaf(cr[1][i], cr[1][i], q2); q = fmaf(ci[0][i], ci[0][i], q); q2 = fmaf(ci[1][i], ci[1][i], q2); }
        q += q2;
#pragma unroll
        for (int m = 1; m < 32; m <<= 1) q += __shfl_xor_sync(0xffffffffu, q, m);
        float r = rsqrtf(q * (1.f / (512.f * 16.f * ALPHA * ALPHA)) + 1e-5f) * 4.76837158203125e-7f;
        fft_s2(K, cr, ci, o);
#pragma unroll
        for (int j = 0; j < 4; j++)
          sts64(zb + ((a * 8 + warp) * ZROW + zphys(16 * t + 64 * j) + 2 * g) * 4, pk(o[j][0] * r, o[j][1] * r), pk(o[j][2] * r, o[j][3] * r));
      }
      wbar();
      uint4* tp = g_T1 + (size_t)(g * 16 + warp) * 1024 + b * 8;
#pragma unroll
      for (int nt = 0; nt < 2; nt++) {
        const int k = 16 * warp + 8 * nt + g, km = k == 0 ? 128 : 256 - k;
        uint32_t lo[4], hi[4];
#pragma unroll
        for (int a = 0; a < 2; a++) {
          const uint32_t rb = zb + (a * 8 + t) * ZROW * 4;
          float A[4], B[4];
          mma0(A, a8[a][0], a8[a][1], a8[a][2], a8[a][3], lds32(rb + zphys(k) * 4), lds32(rb + (4 * ZROW + zphys(k)) * 4));
          mma0(B, a8[a][0] ^ 0x80000000u, a8[a][1] ^ 0x80000000u, a8[a][2] ^ 0x80000000u, a8[a][3] ^ 0x80000000u,
               lds32(rb + zphys(km) * 4), lds32(rb + (4 * ZROW + zphys(km)) * 4));
#pragma unroll
          for (int e = 0; e < 2; e++) {
            float sr = A[e] + B[e], si = A[2 + e] + B[2 + e], dr = A[e] - B[e], di = A[2 + e] - B[2 + e];
            float c = vc[2 * nt + e], s = vs[2 * nt + e];
            float gr = dr * c + di * s, gi = di * c - dr * s;
            float lr = sr + gr, li = si + gi, hr = sr - gr, hii = si - gi;
            if (nt == 0 && e == 0) {
              const bool sp = warp == 0 && t == 0;
              lr = sp ? 2.f * B[0] : lr; li = sp ? 2.f * B[2] : li;
              hr = sp ? 2.f * (A[0] - A[2]) : hr; hii = sp ? 2.f * (A[0] + A[2]) : hii;
            }
            lo[2 * a + e] = pk(lr, li); hi[2 * a + e] = pk(hr, hii);
          }
        }
        const int w = (t + 4 * nt) ^ key;
        tp[w] = make_uint4((lo[0] & ~1u) | tag, lo[1], lo[2], lo[3]);
        tp[8 * 1024 + w] = make_uint4((hi[0] & ~1u) | tag, hi[1], hi[2], hi[3]);
      }
      wbar();
      STAMP(1);
      if (warp == 0) cnt_arrive(0, lane);
    }
    {
      const uint32_t off = (8 * t + g) * 128 + ((warp ^ (2 * t + (g & 1))) << 4);
      asm volatile("barrier.cluster.wait.aligned;" ::: "memory");
      mbar_wait(mb + MB_FILT * 8, 0);
      if (tid == 0) cnt_wait(0, rep, base + NCTA);
      wbar();
#pragma unroll
      for (int j = 0; j < 4; j++)
        asm volatile("cp.async.cg.shared.global [%0], [%1], 16;" :: "r"(zb + j * 4096 + tid * 16), "l"(g_T1 + (size_t)b * 1024 + j * 256 + tid) : "memory");
      STAMP(2);
      uint32_t in[2][4][2], fw[2][4][2];
#pragma unroll
      for (int j = 0; j < 4; j++) {
        uint4 v = lds128(sb + FILT_OFF + off + j * 4096);
        fw[0][j][0] = v.x; fw[1][j][0] = v.y; fw[0][j][1] = v.z; fw[1][j][1] = v.w;
      }
      asm volatile("cp.async.wait_all;" ::: "memory");
      wbar();
      STAMP(3);
      uint4 iv[4];
#pragma unroll
      for (int j = 0; j < 4; j++) iv[j] = lds128(zb + off + j * 4096);
      if (((iv[0].x ^ tag) | (iv[1].x ^ tag) | (iv[2].x ^ tag) | (iv[3].x ^ tag)) & 1) {
#pragma unroll
        for (int j = 0; j < 4; j++) tag_check(iv[j], g_T1 + (size_t)b * 1024 + j * 256 + (off >> 4), tag);
      }
      __syncwarp();
#pragma unroll
      for (int j = 0; j < 4; j++) { in[0][j][0] = iv[j].x; in[1][j][0] = iv[j].y; in[0][j][1] = iv[j].z; in[1][j][1] = iv[j].w; }
#pragma unroll
      for (int sg = 0; sg < 2; sg++) {
        float cr[2][4], ci[2][4], o[4][4];
        fft_s1(K, in[sg], cr, ci);
        fft_s2(K, cr, ci, o);
#pragma unroll
        for (int j = 0; j < 4; j++)
#pragma unroll
          for (int h = 0; h < 2; h++) {
            float fr = blo(fw[sg][j][h]), fi = bhi(fw[sg][j][h]), xr = o[j][2 * h], xi = o[j][2 * h + 1];
            in[sg][j][h] = pk(xr * fi + xi * fr, xr * fr - xi * fi);
          }
        fft_s1(K, in[sg], cr, ci);
        fft_s2(K, cr, ci, o);
#pragma unroll
        for (int j = 0; j < 4; j++) { in[sg][j][0] = pk(o[j][0], o[j][1]); in[sg][j][1] = pk(o[j][2], o[j][3]); }
      }
#pragma unroll
      for (int j = 0; j < 4; j++) sts128(zb + off + j * 4096, make_uint4((in[0][j][0] & ~1u) | tag, in[1][j][0], in[0][j][1], in[1][j][1]));
      wbar();
#pragma unroll
      for (int j = 0; j < 4; j++) g_T2[(size_t)b * 1024 + j * 256 + tid] = lds128(zb + j * 4096 + tid * 16);
      wbar();
      STAMP(4);
      if (warp == 0) cnt_arrive(1, lane);
    }
    {
      uint32_t a8[2][4]; float vc[4], vs[4];
#pragma unroll
      for (int a = 0; a < 2; a++)
#pragma unroll
        for (int u = 0; u < 2; u++) {
          float c, s; cs<2048>((t + 4 * u) * (256 * g + 2 * b + a), c, s);
          a8[a][2 * u] = pk(c, s); a8[a][2 * u + 1] = pk(-s, c);
        }
#pragma unroll
      for (int i = 0; i < 4; i++) cs<512>(16 * warp + 4 * t + i + 128, vc[i], vs[i]);
      if (tid == 0) cnt_wait(1, rep, base + NCTA);
      wbar();
      STAMP(5);
      const uint4* tp = g_T2 + (size_t)(t * 16 + warp) * 1024 + b * 8 + (g ^ key);
      uint4 L0 = ldcg128(tp), L1 = ldcg128(tp + 64 * 1024), H0 = ldcg128(tp + 8 * 1024), H1 = ldcg128(tp + 72 * 1024);
      if (((L0.x ^ tag) | (L1.x ^ tag) | (H0.x ^ tag) | (H1.x ^ tag)) & 1) {
        tag_check(L0, tp, tag); tag_check(L1, tp + 64 * 1024, tag); tag_check(H0, tp + 8 * 1024, tag); tag_check(H1, tp + 72 * 1024, tag);
      }
      __syncwarp();
      const uint32_t l0[4] = {L0.x, L0.y, L0.z, L0.w}, l1[4] = {L1.x, L1.y, L1.z, L1.w}, h0[4] = {H0.x, H0.y, H0.z, H0.w}, h1[4] = {H1.x, H1.y, H1.z, H1.w};
#pragma unroll
      for (int a = 0; a < 2; a++) {
        uint32_t zf[4], zm[4];
#pragma unroll
        for (int sg = 0; sg < 2; sg++) {
          float A[4], B[4];
          mma0(A, a8[a][0], a8[a][1], a8[a][2], a8[a][3], l0[2 * a + sg], l1[2 * a + sg]);
          mma0(B, a8[a][0], a8[a][1], a8[a][2], a8[a][3], h0[2 * a + sg], h1[2 * a + sg]);
#pragma unroll
          for (int e = 0; e < 2; e++) {
            const int i = 2 * e + sg;
            float sr = A[2 + e] + B[2 + e], si = A[e] + B[e], dr = A[2 + e] - B[2 + e], di = A[e] - B[e];
            float gr = dr * vc[i] - di * vs[i], gi = di * vc[i] + dr * vs[i];
            float fr = sr + gr, fi = si + gi, mr = sr - gr, mi = gi - si;
            if (i == 0) {
              const bool sp = warp == 0 && t == 0;
              fr = sp ? B[2] : fr; fi = sp ? -B[2] : fi;
              mr = sp ? 2.f * A[2] : mr; mi = sp ? -2.f * A[0] : mi;
            }
            zf[i] = pk(fi, fr); zm[i] = pk(mi, mr);
          }
        }
        const uint32_t rb = zb + (a * 8 + g) * ZROW * 4;
        const int k0 = 16 * warp + 4 * t;
        sts128(rb + zphys(k0) * 4, make_uint4(zf[0], zf[1], zf[2], zf[3]));
        sts32(rb + zphys(k0 == 0 ? 128 : 256 - k0) * 4, zm[0]);
        sts32(rb + zphys(255 - k0) * 4, zm[1]);
        sts32(rb + zphys(254 - k0) * 4, zm[2]);
        sts32(rb + zphys(253 - k0) * 4, zm[3]);
      }
      wbar();
#pragma unroll
      for (int a = 0; a < 2; a++) {
        uint32_t in[4][2];
#pragma unroll
        for (int j = 0; j < 4; j++) { uint2 v = lds64(zb + ((a * 8 + warp) * ZROW + zphys(16 * t + 64 * j) + 2 * g) * 4); in[j][0] = v.x; in[j][1] = v.y; }
        float cr[2][4], ci[2][4], o[4][4];
        fft_s1(K, in, cr, ci);
        fft_s2(K, cr, ci, o);
        float s1 = 0.f, s2 = 0.f;
        uint2* hp = (uint2*)g_h + (size_t)(256 * warp + 2 * b + a) * 128 + 8 * t + g;
#pragma unroll
        for (int j = 0; j < 4; j++) {
          uint32_t hw[2];
#pragma unroll
          for (int h = 0; h < 2; h++) {
            uint32_t y = pk(o[j][2 * h + 1], o[j][2 * h]);
            hw[h] = pk(blo(xw[a][j][h]) + blo(y), bhi(xw[a][j][h]) + bhi(y));
            float u0 = blo(hw[h]) - mean[a], u1 = bhi(hw[h]) - mean[a];
            o[j][2 * h] = u0; o[j][2 * h + 1] = u1;
            s1 += u0 + u1; s2 = fmaf(u0, u0, fmaf(u1, u1, s2));
          }
          hp[32 * j] = make_uint2(hw[0], hw[1]);
        }
#pragma unroll
        for (int m = 1; m < 32; m <<= 1) { s1 += __shfl_xor_sync(0xffffffffu, s1, m); s2 += __shfl_xor_sync(0xffffffffu, s2, m); }
        const float mu = s1 * (1.f / 512.f), var = fmaxf(s2 * (1.f / 512.f) - mu * mu, 0.f);
        const float r1 = rsqrtf(var + 1e-5f);
        const float r = r1 * rsqrtf(var * r1 * r1 + 1e-5f);
        char* np = (char*)g_Hn + (size_t)b * 4096 + (t >> 1) * 2048 + a * 1024 + warp * 128 + ((((t & 1) * 4 + (g >> 1)) ^ warp) << 4) + (g & 1) * 8;
#pragma unroll
        for (int j = 0; j < 4; j++)
          *(uint2*)(np + (size_t)j * 128 * 4096) = make_uint2(pk((o[j][0] - mu) * r, (o[j][1] - mu) * r), pk((o[j][2] - mu) * r, (o[j][3] - mu) * r));
      }
      asm volatile("fence.proxy.async.shared::cta;" ::: "memory");
      wbar();
      STAMP(6);
      if (warp == 0) { fence_gpu(); cnt_arrive(2 + (b >> 6), lane); }
      if (tid == 32) { sts32(sb + BASE_OFF, base); mbar_arrive(mb + MB_P3DONE * 8); }
    }
    const int wg = warp >> 2;
    int slot = 0, ph = 0, prev = 0;
    const uint32_t peer_sb = mapa(sb, rank ^ 1);
    {
      uint32_t bias[11];
#pragma unroll
      for (int j = 0; j < 11; j++) bias[j] = (11 * ot + j < 172) ? __ldg(b1 + (11 * ot + j) * 4 + t) : 0u;
      float acc[44];
      const uint64_t da0 = mkdesc(sb + RING_OFF + wg * 2048, 0, 1024, 1), db0 = mkdesc(sb, 1408, 128, 0);
      mbar_wait(mb + MB_W1 * 8, 0);
#pragma unroll 1
      for (int i = 0; i < 32; i++) {
        mbar_wait(mb + (MB_FULL + slot) * 8, ph);
        if (i == 0) STAMP(7);
        asm volatile("wgmma.fence.sync.aligned;" ::: "memory");
        wgmma_n88_ss<1, 1>(acc, da0 + slot * 512, db0 + i * 352, i > 0);
        wgmma_n88_ss<1, 1>(acc, da0 + slot * 512 + 256, db0 + i * 352 + 176, 1);
        asm volatile("wgmma.commit_group.sync.aligned;" ::: "memory");
        asm volatile("wgmma.wait_group.sync.aligned 1;" ::: "memory");
        if ((tid & 127) == 0) { if (i > 0) mbar_arrive(mb + (MB_EMPTY + prev) * 8); if (i == 4) mbar_arrive_cluster(peer_sb + BAR_OFF + MB_PEER1 * 8); }
        prev = slot;
        if (++slot == NST) { slot = 0; ph ^= 1; }
      }
      asm volatile("wgmma.wait_group.sync.aligned 0;" ::: "memory");
#pragma unroll
      for (int i = 0; i < 44; i++) asm volatile("" : "+f"(acc[i]) :: "memory");
      if ((tid & 127) == 0) mbar_arrive(mb + (MB_EMPTY + prev) * 8);
      STAMP(8);
      float keep[22], send[22];
#pragma unroll
      for (int j = 0; j < 11; j++) {
        keep[2 * j] = rank ? acc[4 * j + 2] : acc[4 * j]; keep[2 * j + 1] = rank ? acc[4 * j + 3] : acc[4 * j + 1];
        send[2 * j] = rank ? acc[4 * j] : acc[4 * j + 2]; send[2 * j + 1] = rank ? acc[4 * j + 1] : acc[4 * j + 3];
      }
      mbar_wait_cluster(mb + MB_PEER1 * 8, 0);
#pragma unroll
      for (int j = 0; j < 5; j++) st_async4(peer_sb + j * 4096 + tid * 16, send[4 * j], send[4 * j + 1], send[4 * j + 2], send[4 * j + 3], peer_sb + BAR_OFF + MB_X1 * 8);
      st_async2(peer_sb + 5 * 4096 + tid * 8, send[20], send[21], peer_sb + BAR_OFF + MB_X1 * 8);
      mbar_wait_cluster(mb + MB_X1 * 8, 0);
#pragma unroll
      for (int j = 0; j < 5; j++) {
        uint4 v = lds128(sb + j * 4096 + tid * 16);
        keep[4 * j] += __uint_as_float(v.x); keep[4 * j + 1] += __uint_as_float(v.y); keep[4 * j + 2] += __uint_as_float(v.z); keep[4 * j + 3] += __uint_as_float(v.w);
      }
      { uint2 v = lds64(sb + 5 * 4096 + tid * 8); keep[20] += __uint_as_float(v.x); keep[21] += __uint_as_float(v.y); }
      uint32_t* up = (uint32_t*)g_U + ((size_t)dt * 172 + 11 * ot) * 512 + (4 * (warp >> 1) + (g >> 1)) * 32 + (2 * (2 * (warp & 1) + rank) + (g & 1)) * 4 + t;
#pragma unroll
      for (int j = 0; j < 11; j++) {
        uint32_t v = pk(gelu(keep[2 * j] + blo(bias[j])), gelu(keep[2 * j + 1] + bhi(bias[j])));
        if (11 * ot + j < 172) up[j * 512] = v;
      }
      asm volatile("fence.proxy.async.shared::cta;" ::: "memory");
      wbar();
      STAMP(9);
      if (warp == 0) { fence_gpu(); cnt_arrive(4 + dt, lane); }
      if (tid == 32) mbar_arrive(mb + MB_X1DONE * 8);
    }
    {
      const int srow = 128 * ot + 16 * warp + 8 * rank + g;
      float acc[64];
      const uint64_t da0 = mkdesc(sb + wg * 4096, 0, 1024, 1), db0 = mkdesc(sb + RING_OFF, 2048, 128, 0);
      uint4 hv[4];
#pragma unroll
      for (int j = 0; j < 4; j++) hv[j] = ldcg128(g_h + (size_t)srow * 64 + dt * 16 + 4 * j + t);
      const float bias2 = __uint_as_float((uint32_t)__ldg(b2 + srow) << 16);
#pragma unroll 1
      for (int i = 0; i < 21; i++) {
        const int ws = i < 19 ? i + 3 : i - 19;
        mbar_wait(mb + (MB_W2 + i) * 8, 0);
        mbar_wait(mb + (MB_FULL + slot) * 8, ph);
        if (i == 0) STAMP(10);
        asm volatile("wgmma.fence.sync.aligned;" ::: "memory");
        wgmma_n128_ss<1, 0>(acc, da0 + ws * 512, db0 + slot * 512, i > 0);
        wgmma_n128_ss<1, 0>(acc, da0 + ws * 512 + 128, db0 + slot * 512 + 256, 1);
        asm volatile("wgmma.commit_group.sync.aligned;" ::: "memory");
        asm volatile("wgmma.wait_group.sync.aligned 1;" ::: "memory");
        if ((tid & 127) == 0) { if (i > 0) mbar_arrive(mb + (MB_EMPTY + prev) * 8); if (i == 4) mbar_arrive_cluster(peer_sb + BAR_OFF + MB_PEER2 * 8); }
        prev = slot;
        if (++slot == NST) { slot = 0; ph ^= 1; }
      }
      mbar_wait(mb + (MB_W2 + 21) * 8, 0);
      mbar_wait(mb + (MB_FULL + 53 % NST) * 8, (53 / NST) & 1);
      asm volatile("wgmma.fence.sync.aligned;" ::: "memory");
      wgmma_n128_ss<1, 0>(acc, da0 + 2 * 512, db0 + (53 % NST) * 512, 1);
      asm volatile("wgmma.commit_group.sync.aligned;" ::: "memory");
      asm volatile("wgmma.wait_group.sync.aligned 0;" ::: "memory");
#pragma unroll
      for (int i = 0; i < 64; i++) asm volatile("" : "+f"(acc[i]) :: "memory");
      STAMP(11);
      mbar_wait_cluster(mb + MB_PEER2 * 8, 0);
#pragma unroll
      for (int j = 0; j < 8; j++)
        st_async4(peer_sb + 3 * 8192 + j * 4096 + tid * 16, rank ? acc[8 * j] : acc[8 * j + 2], rank ? acc[8 * j + 1] : acc[8 * j + 3],
                  rank ? acc[8 * j + 4] : acc[8 * j + 6], rank ? acc[8 * j + 5] : acc[8 * j + 7], peer_sb + BAR_OFF + MB_X2 * 8);
      float keep[32];
#pragma unroll
      for (int j = 0; j < 16; j++) {
        const uint32_t hw = j % 4 == 0 ? hv[j / 4].x : j % 4 == 1 ? hv[j / 4].y : j % 4 == 2 ? hv[j / 4].z : hv[j / 4].w;
        keep[2 * j] = (rank ? acc[4 * j + 2] : acc[4 * j]) + (bias2 + blo(hw));
        keep[2 * j + 1] = (rank ? acc[4 * j + 3] : acc[4 * j + 1]) + (bias2 + bhi(hw));
      }
      mbar_wait_cluster(mb + MB_X2 * 8, 0);
#pragma unroll
      for (int j = 0; j < 4; j++) {
        uint4 v = lds128(sb + 3 * 8192 + (2 * j) * 4096 + tid * 16), w = lds128(sb + 3 * 8192 + (2 * j + 1) * 4096 + tid * 16);
        out[(size_t)srow * 64 + dt * 16 + 4 * j + t] =
            make_uint4(pk(keep[8 * j] + __uint_as_float(v.x), keep[8 * j + 1] + __uint_as_float(v.y)), pk(keep[8 * j + 2] + __uint_as_float(v.z), keep[8 * j + 3] + __uint_as_float(v.w)),
                       pk(keep[8 * j + 4] + __uint_as_float(w.x), keep[8 * j + 5] + __uint_as_float(w.y)), pk(keep[8 * j + 6] + __uint_as_float(w.z), keep[8 * j + 7] + __uint_as_float(w.w)));
      }
      STAMP(12);
    }
  } else {
    const int pw = warp - 8;
    if (pw == 0) {
      if (lane == 0) {
        _Pragma("unroll 1") for (int i = 0; i < NST; i++) { mbar_init(mb + (MB_FULL + i) * 8, 1); mbar_init(mb + (MB_EMPTY + i) * 8, 2); }
        _Pragma("unroll 1") for (int i = 0; i < 22; i++) mbar_init(mb + (MB_W2 + i) * 8, 1);
        _Pragma("unroll 1") for (int i = 0; i < 32; i++) mbar_init(mb + (MB_W1T + i) * 8, 1);
        mbar_init(mb + MB_P2IN * 8, 1); mbar_init(mb + MB_FILT * 8, 128); mbar_init(mb + MB_W1 * 8, 128);
        mbar_init(mb + MB_PEER1 * 8, 2); mbar_init(mb + MB_X1 * 8, 1); mbar_init(mb + MB_X1DONE * 8, 1);
        mbar_init(mb + MB_PEER2 * 8, 2); mbar_init(mb + MB_X2 * 8, 1); mbar_init(mb + MB_P3DONE * 8, 1);
        mbar_expect(mb + MB_X1 * 8, 22528); mbar_expect(mb + MB_X2 * 8, 32768);
        asm volatile("fence.mbarrier_init.release.cluster;" ::: "memory");
      }
      __syncwarp();
    }
    STAMP(0);
    asm volatile("bar.sync 2, 128;" ::: "memory");
    asm volatile("barrier.cluster.arrive.relaxed.aligned;" ::: "memory");
    auto w1_issue = [&](int i) {
      if (elect()) { mbar_expect(mb + (MB_W1T + i) * 8, 5632); tma3d(sb + i * 5632, &tmW1, 88 * ot, 0, 128 * rank + 4 * i, mb + (MB_W1T + i) * 8); }
      __syncwarp();
    };
    if (!W1_LATE && pw < W1_WARPS) for (int i = 0; i < W1_DEPTH; i++) w1_issue(pw + W1_WARPS * i);
    {
      const int j1 = b >> 4, q = b & 15, slot = lane & 15, h = lane >> 4;
      const bool hi = q >= 8;
      const int k = 16 * (q & 7) + slot, col = hi ? 256 - k : (k == 0 ? 128 : k);
#pragma unroll 1
      for (int it = 0; it < 2; it++) {
        uint32_t vr[16], vi[16];
#pragma unroll
        for (int n = 0; n < 16; n++) {
          const int c = pw * 32 + it * 16 + n;
          int j = j1 + 8 * (2 * c + h);
          if (hi) j = (2048 - j) & 2047;
          vr[n] = __ldg(wr + j * DF + col); vi[n] = __ldg(wi + j * DF + col);
        }
#pragma unroll
        for (int n = 0; n < 16; n++) {
          const int c = pw * 32 + it * 16 + n;
          sts32(sb + FILT_OFF + c * 128 + (((slot >> 1) ^ (((c >> 3) & 3) * 2 + (c & 1))) << 4) + h * 8 + (slot & 1) * 4,
                (vr[n] | (vi[n] << 16)) ^ (hi ? 0x80000000u : 0u));
        }
      }
      mbar_arrive(mb + MB_FILT * 8);
    }
    STAMP(1);
    {
      if (W1_LATE && pw < W1_WARPS) for (int i = 0; i < W1_DEPTH; i++) w1_issue(pw + W1_WARPS * i);
      const uint32_t rd = ((lane & 7) * 11 + (lane >> 3)) * 16, wr = lane * 16;
#pragma unroll 1
      for (int box = pw < W1_WARPS ? pw : 32; box < 32; box += W1_WARPS) {
        mbar_wait(mb + (MB_W1T + box) * 8, 0);
        if (box + W1_WARPS * W1_DEPTH < 32) w1_issue(box + W1_WARPS * W1_DEPTH);
        const uint32_t p = sb + box * 5632;
        uint4 v[4][3];
#pragma unroll
        for (int n = 0; n < 4; n++) { v[n][0] = lds128(p + n * 1408 + rd); v[n][1] = lds128(p + n * 1408 + rd + 64); if (lane < 24) v[n][2] = lds128(p + n * 1408 + rd + 128); }
        __syncwarp();
#pragma unroll
        for (int n = 0; n < 4; n++) { sts128(p + n * 1408 + wr, v[n][0]); sts128(p + n * 1408 + wr + 512, v[n][1]); if (lane < 24) sts128(p + n * 1408 + wr + 1024, v[n][2]); }
      }
      if (lane == 0) asm volatile("cp.async.bulk.prefetch.L2.global [%0], %1;" :: "l"(w2 + (size_t)(b * 4 + pw) * 11008), "r"(11008) : "memory");
      asm volatile("fence.proxy.async.shared::cta;" ::: "memory");
      mbar_arrive(mb + MB_W1 * 8);
    }
    STAMP(2);
    asm volatile("barrier.cluster.wait.aligned;" ::: "memory");
    if (pw == 0) {
      mbar_wait(mb + MB_P3DONE * 8, 0);
      const unsigned base = lds32(sb + BASE_OFF);
      const int rep = ot & (NREP - 1);
      if (lane == 0) { cnt_wait(2 + rank, rep, (base >> 1) + 64); fence_gpu(); }
      __syncwarp();
      STAMP(3);
      asm volatile("fence.proxy.async.global;" ::: "memory");
      const char* src = (const char*)g_Hn + ((size_t)dt * 128 + 64 * rank) * 4096;
      int nw2 = 0, slot = 0, ph = 1;
      auto w2_upto = [&](int n) {
#pragma unroll 1
        for (; nw2 < n; nw2++)
          if (elect()) { mbar_expect(mb + (MB_W2 + nw2) * 8, 8192); tma3d(sb + (nw2 < 19 ? nw2 + 3 : nw2 - 19) * 8192, &tmW2, 0, 688 * rank + 32 * nw2, 2 * ot, mb + (MB_W2 + nw2) * 8); }
      };
#pragma unroll 1
      for (int i = 0; i < 54; i++) {
        if (i == 32) {
          mbar_wait(mb + (MB_EMPTY + 31 % NST) * 8, (31 / NST) & 1);
          w2_upto(W2_PRE);
          mbar_wait(mb + MB_X1DONE * 8, 0);
          STAMP(4);
          if (lane == 0) { cnt_wait(4 + dt, rep, (base >> 2) + 32); fence_gpu(); }
          __syncwarp();
          STAMP(5);
          asm volatile("fence.proxy.async.global;" ::: "memory");
          src = (const char*)g_U + ((size_t)dt * 172 + 86 * rank) * 2048;
        }
        mbar_wait(mb + (MB_EMPTY + slot) * 8, ph);
        if (elect()) {
          const int bytes = i < 53 ? 8192 : 4096;
          mbar_expect(mb + (MB_FULL + slot) * 8, bytes); bulk_ld(sb + RING_OFF + slot * 8192, src, bytes, mb + (MB_FULL + slot) * 8);
        }
        src += 8192;
        if (++slot == NST) { slot = 0; ph ^= 1; }
        if (i >= W2_START) w2_upto(i < 32 ? min(nw2 + W2_RATE, (((i - NST + 1) * 11) >> 4) - 3) : min(22, nw2 + W2_RATE2));
      }
      STAMP(6);
    }
  }
}

typedef CUresult (*EncodeFn)(CUtensorMap*, CUtensorMapDataType, cuuint32_t, void*, const cuuint64_t*, const cuuint64_t*, const cuuint32_t*,
                             const cuuint32_t*, CUtensorMapInterleave, CUtensorMapSwizzle, CUtensorMapL2promotion, CUtensorMapFloatOOBfill);

extern "C" void kernel_launch(void* const* d_in, const int* in_sizes, int n_in, void* d_out, int out_size) {
  static EncodeFn enc = nullptr;
  if (!enc) {
    void* fn = nullptr; cudaDriverEntryPointQueryResult st;
    cudaGetDriverEntryPoint("cuTensorMapEncodeTiled", &fn, cudaEnableDefault, &st);
    enc = (EncodeFn)fn;
    cudaFuncSetAttribute(fused_kernel, cudaFuncAttributeMaxDynamicSharedMemorySize, SMEM_BYTES);
  }
  CUtensorMap tm, tm1;
  {
    cuuint64_t dims[3] = {(cuuint64_t)F_, 8, 256}, strides[2] = {(cuuint64_t)256 * F_ * 2, F_ * 2};
    cuuint32_t box[3] = {88, 8, 4}, es[3] = {1, 1, 1};
    enc(&tm1, CU_TENSOR_MAP_DATA_TYPE_BFLOAT16, 3, d_in[4], dims, strides, box, es, CU_TENSOR_MAP_INTERLEAVE_NONE, CU_TENSOR_MAP_SWIZZLE_NONE,
        W1_PROMO, CU_TENSOR_MAP_FLOAT_OOB_FILL_NONE);
  }
  {
    cuuint64_t dims[3] = {64, (cuuint64_t)F_, S_ / 64}, strides[2] = {S_ * 2, 128};
    cuuint32_t box[3] = {64, 32, 2}, es[3] = {1, 1, 1};
    enc(&tm, CU_TENSOR_MAP_DATA_TYPE_BFLOAT16, 3, d_in[6], dims, strides, box, es, CU_TENSOR_MAP_INTERLEAVE_NONE, CU_TENSOR_MAP_SWIZZLE_128B,
        CU_TENSOR_MAP_L2_PROMOTION_L2_256B, CU_TENSOR_MAP_FLOAT_OOB_FILL_NONE);
  }
  fused_kernel<<<NCTA, 384, SMEM_BYTES, cudaStreamPerThread>>>(tm1, tm, (const uint2*)d_in[0], (const unsigned short*)d_in[1], (const unsigned short*)d_in[2],
                                          (const char*)d_in[4], (const uint32_t*)d_in[5], (const char*)d_in[6], (const unsigned short*)d_in[7], (uint4*)d_out);
}
```

```cpp
#include <cuda_runtime.h>
#include <cuda.h>
#include <cuda_bf16.h>
#include <stdint.h>
#define W1_LATE 1
#define W1_PROMO CU_TENSOR_MAP_L2_PROMOTION_NONE
#define W2_NUM 1
#define W2_DEN 1
#define PF_MODE 0
#define W1_DEPTH 1
#define W1_WARPS 3
#define W2_PRE 19
#define W2_PACE 0
template<int TA, int TB, uint32_t HA, uint32_t HB> __device__ __forceinline__ void wgmma_n88_ss(float (&d)[44], uint32_t da, uint32_t db, int sd) {
  asm volatile("{\n.reg .pred p;\n.reg .b64 da, db;\nsetp.ne.b32 p, %46, 0;\nmov.b64 da, {%44, %49};\nmov.b64 db, {%45, %50};\n"
    "wgmma.mma_async.sync.aligned.m64n88k16.f32.bf16.bf16 {%0, %1, %2, %3, %4, %5, %6, %7, %8, %9, %10, %11, %12, %13, %14, %15, %16, %17, %18, %19, %20, %21, %22, %23, %24, %25, %26, %27, %28, %29, %30, %31, %32, %33, %34, %35, %36, %37, %38, %39, %40, %41, %42, %43}, da, db, p, 1, 1, %47, %48;\n}\n"
    : "+f"(d[0]), "+f"(d[1]), "+f"(d[2]), "+f"(d[3]), "+f"(d[4]), "+f"(d[5]), "+f"(d[6]), "+f"(d[7]), "+f"(d[8]), "+f"(d[9]), "+f"(d[10]), "+f"(d[11]), "+f"(d[12]), "+f"(d[13]), "+f"(d[14]), "+f"(d[15]), "+f"(d[16]), "+f"(d[17]), "+f"(d[18]), "+f"(d[19]), "+f"(d[20]), "+f"(d[21]), "+f"(d[22]), "+f"(d[23]), "+f"(d[24]), "+f"(d[25]), "+f"(d[26]), "+f"(d[27]), "+f"(d[28]), "+f"(d[29]), "+f"(d[30]), "+f"(d[31]), "+f"(d[32]), "+f"(d[33]), "+f"(d[34]), "+f"(d[35]), "+f"(d[36]), "+f"(d[37]), "+f"(d[38]), "+f"(d[39]), "+f"(d[40]), "+f"(d[41]), "+f"(d[42]), "+f"(d[43]) : "r"(da), "r"(db), "r"(sd), "n"(TA), "n"(TB), "n"(HA), "n"(HB));
}
template<int TA, int TB, uint32_t HA, uint32_t HB> __device__ __forceinline__ void wgmma_n128_ss(float (&d)[64], uint32_t da, uint32_t db, int sd) {
  asm volatile("{\n.reg .pred p;\n.reg .b64 da, db;\nsetp.ne.b32 p, %66, 0;\nmov.b64 da, {%64, %69};\nmov.b64 db, {%65, %70};\n"
    "wgmma.mma_async.sync.aligned.m64n128k16.f32.bf16.bf16 {%0, %1, %2, %3, %4, %5, %6, %7, %8, %9, %10, %11, %12, %13, %14, %15, %16, %17, %18, %19, %20, %21, %22, %23, %24, %25, %26, %27, %28, %29, %30, %31, %32, %33, %34, %35, %36, %37, %38, %39, %40, %41, %42, %43, %44, %45, %46, %47, %48, %49, %50, %51, %52, %53, %54, %55, %56, %57, %58, %59, %60, %61, %62, %63}, da, db, p, 1, 1, %67, %68;\n}\n"
    : "+f"(d[0]), "+f"(d[1]), "+f"(d[2]), "+f"(d[3]), "+f"(d[4]), "+f"(d[5]), "+f"(d[6]), "+f"(d[7]), "+f"(d[8]), "+f"(d[9]), "+f"(d[10]), "+f"(d[11]), "+f"(d[12]), "+f"(d[13]), "+f"(d[14]), "+f"(d[15]), "+f"(d[16]), "+f"(d[17]), "+f"(d[18]), "+f"(d[19]), "+f"(d[20]), "+f"(d[21]), "+f"(d[22]), "+f"(d[23]), "+f"(d[24]), "+f"(d[25]), "+f"(d[26]), "+f"(d[27]), "+f"(d[28]), "+f"(d[29]), "+f"(d[30]), "+f"(d[31]), "+f"(d[32]), "+f"(d[33]), "+f"(d[34]), "+f"(d[35]), "+f"(d[36]), "+f"(d[37]), "+f"(d[38]), "+f"(d[39]), "+f"(d[40]), "+f"(d[41]), "+f"(d[42]), "+f"(d[43]), "+f"(d[44]), "+f"(d[45]), "+f"(d[46]), "+f"(d[47]), "+f"(d[48]), "+f"(d[49]), "+f"(d[50]), "+f"(d[51]), "+f"(d[52]), "+f"(d[53]), "+f"(d[54]), "+f"(d[55]), "+f"(d[56]), "+f"(d[57]), "+f"(d[58]), "+f"(d[59]), "+f"(d[60]), "+f"(d[61]), "+f"(d[62]), "+f"(d[63]) : "r"(da), "r"(db), "r"(sd), "n"(TA), "n"(TB), "n"(HA), "n"(HB));
}

constexpr int S_ = 2048, D_ = 512, F_ = 1376, DF = 257;
constexpr int NCTA = 128;
constexpr int W_BYTES = 180224;
constexpr int RING_OFF = W_BYTES;
constexpr int NST = 6;
constexpr int BAR_OFF = RING_OFF + NST * 8192;
constexpr int SMEM_BYTES = BAR_OFF + 1536;
constexpr int FILT_OFF = RING_OFF;
constexpr int XCH_OFF = RING_OFF + 16384;
constexpr int ZROW = 328;
constexpr int MB_FULL = 0, MB_EMPTY = 54, MB_PEER1 = 108, MB_PEER2 = 109, MB_W2 = 110, MB_W1T = 132, MB_X1 = 164, MB_X2 = 165,
              MB_X1DONE = 166, MB_P3DONE = 167, MB_FILT = 168, MB_W1 = 169, MB_N = 170;
constexpr int BASE_OFF = BAR_OFF + MB_N * 8;
#define W2_START 12

__device__ uint4 g_T1[NCTA * 1024];
__device__ uint4 g_T2[NCTA * 1024];
__device__ uint4 g_h[S_ * D_ / 8];
__device__ uint4 g_Hn[4 * 128 * 256];
__device__ uint4 g_U[4 * 172 * 128];
__device__ unsigned g_cnt[8 * 4 * 64];
#define STAMP(i)

__device__ __forceinline__ void mbar_init(uint32_t b, int c) { asm volatile("mbarrier.init.shared::cta.b64 [%0], %1;" :: "r"(b), "r"(c) : "memory"); }
__device__ __forceinline__ void mbar_expect(uint32_t b, int bytes) { asm volatile("mbarrier.arrive.expect_tx.shared::cta.b64 _, [%0], %1;" :: "r"(b), "r"(bytes) : "memory"); }
__device__ __forceinline__ void mbar_arrive(uint32_t b) { asm volatile("mbarrier.arrive.shared::cta.b64 _, [%0];" :: "r"(b) : "memory"); }
__device__ __forceinline__ void mbar_arrive_cluster(uint32_t remote) { asm volatile("mbarrier.arrive.relaxed.cluster.shared::cluster.b64 _, [%0];" :: "r"(remote) : "memory"); }
__device__ __forceinline__ uint32_t mapa(uint32_t a, uint32_t cta) { uint32_t r; asm("mapa.shared::cluster.u32 %0, %1, %2;" : "=r"(r) : "r"(a), "r"(cta)); return r; }
__device__ __forceinline__ void mbar_wait(uint32_t b, int ph) {
  asm volatile("{\n.reg .pred p;\n.reg .u32 n;\nmov.u32 n, 0;\nL_W:\n"
               "mbarrier.try_wait.parity.shared::cta.b64 p, [%0], %1;\n@p bra L_D;\n"
               "add.u32 n, n, 1;\nsetp.lt.u32 p, n, 4000000;\n@p bra L_W;\ntrap;\nL_D:\n}" :: "r"(b), "r"(ph) : "memory");
}
__device__ __forceinline__ void mbar_wait_cluster(uint32_t b, int ph) {
  asm volatile("{\n.reg .pred p;\n.reg .u32 n;\nmov.u32 n, 0;\nL_W:\n"
               "mbarrier.try_wait.parity.acquire.cluster.shared::cta.b64 p, [%0], %1;\n@p bra L_D;\n"
               "add.u32 n, n, 1;\nsetp.lt.u32 p, n, 4000000;\n@p bra L_W;\ntrap;\nL_D:\n}" :: "r"(b), "r"(ph) : "memory");
}
__device__ __forceinline__ void bulk_ld(uint32_t dst, const void* src, int bytes, uint32_t bar) {
  asm volatile("cp.async.bulk.shared::cluster.global.mbarrier::complete_tx::bytes [%0], [%1], %2, [%3];" :: "r"(dst), "l"(src), "r"(bytes), "r"(bar) : "memory");
}
__device__ __forceinline__ void tma3d(uint32_t dst, const CUtensorMap* tm, int c0, int c1, int c2, uint32_t bar) {
  asm volatile("cp.async.bulk.tensor.3d.shared::cluster.global.mbarrier::complete_tx::bytes [%0], [%1, {%3, %4, %5}], [%2];"
               :: "r"(dst), "l"(tm), "r"(bar), "r"(c0), "r"(c1), "r"(c2) : "memory");
}
__device__ __forceinline__ bool elect() { uint32_t p; asm volatile("{.reg .pred p; elect.sync _|p, 0xffffffff; selp.b32 %0, 1, 0, p;}" : "=r"(p)); return p; }
__device__ __forceinline__ uint32_t desc_lo(uint32_t addr, uint32_t lbo) { return ((addr & 0x3FFFF) >> 4) | ((lbo >> 4) << 16); }
constexpr uint32_t HI_SW128 = (1024 >> 4) | (1u << 30), HI_NOSW = 128 >> 4;
__device__ __forceinline__ uint32_t pk(float lo, float hi) { uint32_t r; asm("cvt.rn.bf16x2.f32 %0, %1, %2;" : "=r"(r) : "f"(hi), "f"(lo)); return r; }
__device__ __forceinline__ float blo(uint32_t w) { return __uint_as_float(w << 16); }
__device__ __forceinline__ float bhi(uint32_t w) { return __uint_as_float(w & 0xffff0000u); }
__device__ __forceinline__ void mma(float (&c)[4], uint32_t a0, uint32_t a1, uint32_t a2, uint32_t a3, uint32_t b0, uint32_t b1) {
  asm("mma.sync.aligned.m16n8k16.row.col.f32.bf16.bf16.f32 {%0,%1,%2,%3}, {%4,%5,%6,%7}, {%8,%9}, {%0,%1,%2,%3};"
      : "+f"(c[0]), "+f"(c[1]), "+f"(c[2]), "+f"(c[3]) : "r"(a0), "r"(a1), "r"(a2), "r"(a3), "r"(b0), "r"(b1));
}
__device__ __forceinline__ void mma0(float (&c)[4], uint32_t a0, uint32_t a1, uint32_t a2, uint32_t a3, uint32_t b0, uint32_t b1) {
  asm("mma.sync.aligned.m16n8k16.row.col.f32.bf16.bf16.f32 {%0,%1,%2,%3}, {%4,%5,%6,%7}, {%8,%9}, {%10,%10,%10,%10};"
      : "=f"(c[0]), "=f"(c[1]), "=f"(c[2]), "=f"(c[3]) : "r"(a0), "r"(a1), "r"(a2), "r"(a3), "r"(b0), "r"(b1), "f"(0.f));
}
__device__ __forceinline__ void wbar() { asm volatile("bar.sync 1, 256;" ::: "memory"); }
__device__ __forceinline__ void sts32(uint32_t a, uint32_t v) { asm volatile("st.shared.b32 [%0], %1;" :: "r"(a), "r"(v) : "memory"); }
__device__ __forceinline__ void sts64(uint32_t a, uint32_t x, uint32_t y) { asm volatile("st.shared.v2.b32 [%0], {%1,%2};" :: "r"(a), "r"(x), "r"(y) : "memory"); }
__device__ __forceinline__ void sts128(uint32_t a, uint4 v) { asm volatile("st.shared.v4.b32 [%0], {%1,%2,%3,%4};" :: "r"(a), "r"(v.x), "r"(v.y), "r"(v.z), "r"(v.w) : "memory"); }
__device__ __forceinline__ uint32_t lds32(uint32_t a) { uint32_t v; asm volatile("ld.shared.b32 %0, [%1];" : "=r"(v) : "r"(a) : "memory"); return v; }
__device__ __forceinline__ uint2 lds64(uint32_t a) { uint2 v; asm volatile("ld.shared.v2.b32 {%0,%1}, [%2];" : "=r"(v.x), "=r"(v.y) : "r"(a) : "memory"); return v; }
__device__ __forceinline__ uint4 lds128(uint32_t a) { uint4 v; asm volatile("ld.shared.v4.b32 {%0,%1,%2,%3}, [%4];" : "=r"(v.x), "=r"(v.y), "=r"(v.z), "=r"(v.w) : "r"(a) : "memory"); return v; }
__device__ __forceinline__ uint4 ldcg128(const void* p) { uint4 v; asm volatile("ld.global.cg.v4.b32 {%0,%1,%2,%3}, [%4];" : "=r"(v.x), "=r"(v.y), "=r"(v.z), "=r"(v.w) : "l"(p) : "memory"); return v; }
__device__ __forceinline__ void st_async4(uint32_t a, float x, float y, float z, float w, uint32_t bar) {
  asm volatile("st.async.weak.shared::cluster.mbarrier::complete_tx::bytes.v4.f32 [%0], {%1,%2,%3,%4}, [%5];" :: "r"(a), "f"(x), "f"(y), "f"(z), "f"(w), "r"(bar) : "memory");
}
__device__ __forceinline__ void st_async2(uint32_t a, float x, float y, uint32_t bar) {
  asm volatile("st.async.weak.shared::cluster.mbarrier::complete_tx::bytes.v2.f32 [%0], {%1,%2}, [%3];" :: "r"(a), "f"(x), "f"(y), "r"(bar) : "memory");
}
constexpr int NREP = 4;
__device__ __forceinline__ void cnt_arrive(int i, int lane) {
  if (lane < NREP) asm volatile("red.relaxed.gpu.global.add.u32 [%0], 1;" :: "l"(&g_cnt[(i * NREP + lane) * 64]) : "memory");
}
template <bool ACQ> __device__ __forceinline__ void cnt_wait(int i, int rep, unsigned target) {
  unsigned v; int n = 0;
  do {
    if (ACQ) asm volatile("ld.acquire.gpu.global.u32 %0, [%1];" : "=r"(v) : "l"(&g_cnt[(i * NREP + rep) * 64]) : "memory");
    else asm volatile("ld.relaxed.gpu.global.u32 %0, [%1];" : "=r"(v) : "l"(&g_cnt[(i * NREP + rep) * 64]) : "memory");
    if (++n > 2000000) __trap(); } while ((int)(v - target) < 0);
}
__device__ __forceinline__ void fence_gpu() { asm volatile("fence.acq_rel.gpu;" ::: "memory"); }
__device__ __forceinline__ void tag_check(uint4& v, const uint4* p, uint32_t tag) {
  int n = 0;
  while ((v.x ^ tag) & 1) {
    asm volatile("ld.relaxed.gpu.global.v4.b32 {%0,%1,%2,%3}, [%4];" : "=r"(v.x), "=r"(v.y), "=r"(v.z), "=r"(v.w) : "l"(p) : "memory");
    if (++n > 2000000) __trap();
  }
}
template <int N> __device__ __forceinline__ void cs(int n, float& c, float& s) {
  n = ((n + N / 2) & (N - 1)) - N / 2;
  float a = (float)n * (6.283185307179586f / N);
  c = __cosf(a); s = __sinf(a);
}
constexpr float ALPHA = 1.13288f;
struct FftC { uint32_t ar[2][2], ai[2][2], p[4], q1, q3; float tc[2][4], ts[2][4]; };
constexpr uint32_t NEG = 0x80008000u;

__device__ __forceinline__ void fft_s1(const FftC& K, const uint32_t (&in)[4][2], float (&cr)[2][4], float (&ci)[2][4]) {
#pragma unroll
  for (int h = 0; h < 2; h++) {
    mma0(cr[h], K.ar[0][0], K.ar[1][0], K.ar[0][1], K.ar[1][1], in[0][h], in[1][h]);
    mma0(ci[h], K.ai[0][0], K.ai[1][0], K.ai[0][1], K.ai[1][1], in[0][h], in[1][h]);
  }
#pragma unroll
  for (int h = 0; h < 2; h++) {
    mma(cr[h], K.ar[0][0], K.ar[1][0] ^ NEG, K.ar[0][1], K.ar[1][1] ^ NEG, in[2][h], in[3][h]);
    mma(ci[h], K.ai[0][0], K.ai[1][0] ^ NEG, K.ai[0][1], K.ai[1][1] ^ NEG, in[2][h], in[3][h]);
  }
}
__device__ __forceinline__ void fft_s2(const FftC& K, const float (&cr)[2][4], const float (&ci)[2][4], float (&o)[4][4]) {
  uint32_t a[2][4];
#pragma unroll
  for (int h = 0; h < 2; h++)
#pragma unroll
    for (int i = 0; i < 4; i++) {
      float xr = cr[i & 1][2 * h + (i >> 1)], xi = ci[i & 1][2 * h + (i >> 1)];
      a[h][i] = pk(xr * K.tc[h][i] + xi * K.ts[h][i], xi * K.tc[h][i] - xr * K.ts[h][i]);
    }
  mma0(o[0], a[0][0], a[1][0], a[0][1], a[1][1], K.p[0], K.p[1]);
  mma0(o[1], a[0][0], a[1][0], a[0][1], a[1][1], K.p[0], K.q1);
  mma0(o[2], a[0][0], a[1][0], a[0][1], a[1][1], K.p[0], K.p[1] ^ NEG);
  mma0(o[3], a[0][0], a[1][0], a[0][1], a[1][1], K.p[0], K.q1 ^ NEG);
  mma(o[0], a[0][2], a[1][2], a[0][3], a[1][3], K.p[2], K.p[3]);
  mma(o[1], a[0][2], a[1][2], a[0][3], a[1][3], K.p[2] ^ NEG, K.q3 ^ NEG);
  mma(o[2], a[0][2], a[1][2], a[0][3], a[1][3], K.p[2], K.p[3] ^ NEG);
  mma(o[3], a[0][2], a[1][2], a[0][3], a[1][3], K.p[2] ^ NEG, K.q3);
}
__device__ __forceinline__ int zphys(int k) { return k + 8 * (k >> 5); }
__device__ __forceinline__ float gelu(float u) {
  float z = u * (0.7978845608028654f + 0.035677408136300125f * u * u), th;
  asm("tanh.approx.f32 %0, %1;" : "=f"(th) : "f"(z));
  float hu = 0.5f * u;
  return fmaf(hu, th, hu);
}

extern "C" __global__ void __cluster_dims__(2, 1, 1) __launch_bounds__(384, 1)
fused_kernel(const __grid_constant__ CUtensorMap tmW1, const __grid_constant__ CUtensorMap tmW2, const uint2* __restrict__ x, const unsigned short* __restrict__ wr,
             const unsigned short* __restrict__ wi, const char* __restrict__ w1, const uint32_t* __restrict__ b1,
             const char* __restrict__ w2, const unsigned short* __restrict__ b2, uint4* __restrict__ out) {
  extern __shared__ __align__(1024) char smem[];
  const uint32_t sb = (uint32_t)__cvta_generic_to_shared(smem);
  const uint32_t mb = sb + BAR_OFF;
  const int b = blockIdx.x, rank = b & 1, pr = b >> 1, dt = pr & 3, ot = pr >> 2;
  const int warp = __shfl_sync(0xffffffffu, threadIdx.x >> 5, 0), lane = threadIdx.x & 31;
  const int g = lane >> 2, t = lane & 3;

  if (warp < 8) {
    const int tid = threadIdx.x;
    uint32_t xw[2][4][2];
    {
      const uint2* xp = x + (size_t)(256 * warp + 2 * b) * 128 + 8 * t + g;
#pragma unroll
      for (int a = 0; a < 2; a++)
#pragma unroll
        for (int j = 0; j < 4; j++) { uint2 v = __ldg(xp + a * 128 + 32 * j); xw[a][j][0] = v.x; xw[a][j][1] = v.y; }
    }
    STAMP(0);
    asm volatile("barrier.cluster.arrive.relaxed.aligned;" ::: "memory");
    const int rep = ot & (NREP - 1);
    const unsigned base = __ldcg(&g_cnt[(1 * NREP + rep) * 64]);
    const uint32_t tag = (~base >> 7) & 1;
    FftC K;
    {
      float c, s;
#pragma unroll
      for (int h = 0; h < 2; h++)
#pragma unroll
        for (int j = 0; j < 2; j++) {
          cs<16>((2 * g + h) * (t + 4 * j), c, s);
          K.ar[h][j] = pk(ALPHA * c, ALPHA * s); K.ai[h][j] = pk(-ALPHA * s, ALPHA * c);
        }
#pragma unroll
      for (int i = 0; i < 4; i++) {
        cs<16>((4 * t + i) * (g >> 1) + 4 * (g & 1), c, s);
        K.p[i] = pk(ALPHA * c, ALPHA * s);
        if (i == 1) K.q1 = pk(-ALPHA * s, ALPHA * c);
        if (i == 3) K.q3 = pk(-ALPHA * s, ALPHA * c);
      }
#pragma unroll
      for (int h = 0; h < 2; h++)
#pragma unroll
        for (int i = 0; i < 4; i++) {
          cs<256>((2 * g + h) * (4 * t + i), c, s);
          K.tc[h][i] = c * (1.f / (ALPHA * ALPHA)); K.ts[h][i] = s * (1.f / (ALPHA * ALPHA));
        }
    }
    const int key = ((b >> 3) & 3) * 2 + (b & 1);
    const uint32_t zb = sb + XCH_OFF;
    float mean[2];
    {
      uint32_t a8[2][4]; float vc[4], vs[4];
#pragma unroll
      for (int a = 0; a < 2; a++)
#pragma unroll
        for (int u = 0; u < 2; u++) {
          float c, s; cs<2048>(g * (256 * (t + 4 * u) + 2 * b + a), c, s);
          a8[a][2 * u] = pk(c, s); a8[a][2 * u + 1] = pk(-s, c);
        }
#pragma unroll
      for (int i = 0; i < 4; i++) cs<512>(16 * warp + 8 * (i >> 1) + 2 * t + (i & 1) + 128, vc[i], vs[i]);
#pragma unroll
      for (int a = 0; a < 2; a++) {
        float cr[2][4], ci[2][4], o[4][4];
        fft_s1(K, xw[a], cr, ci);
        float sm = ((cr[0][0] + cr[0][1]) + (cr[1][0] + cr[1][1])) + ((ci[0][0] + ci[0][1]) + (ci[1][0] + ci[1][1]));
        sm += __shfl_xor_sync(0xffffffffu, sm, 1); sm += __shfl_xor_sync(0xffffffffu, sm, 2);
        sm = g == 0 ? sm * (1.f / 32.f) : 0.f;
#pragma unroll
        for (int h = 0; h < 2; h++) { cr[h][0] -= sm; cr[h][1] -= sm; ci[h][0] -= sm; ci[h][1] -= sm; }
        mean[a] = __shfl_sync(0xffffffffu, sm, 0) * (1.f / (16.f * 1.1328125f));
        float q = 0.f, q2 = 0.f;
#pragma unroll
        for (int i = 0; i < 4; i++) { q = fmaf(cr[0][i], cr[0][i], q); q2 = fmaf(cr[1][i], cr[1][i], q2); q = fmaf(ci[0][i], ci[0][i], q); q2 = fmaf(ci[1][i], ci[1][i], q2); }
        q += q2;
#pragma unroll
        for (int m = 1; m < 32; m <<= 1) q += __shfl_xor_sync(0xffffffffu, q, m);
        float r = rsqrtf(q * (1.f / (512.f * 16.f * ALPHA * ALPHA)) + 1e-5f) * 4.76837158203125e-7f;
        fft_s2(K, cr, ci, o);
#pragma unroll
        for (int j = 0; j < 4; j++)
          sts64(zb + ((a * 8 + warp) * ZROW + zphys(16 * t + 64 * j) + 2 * g) * 4, pk(o[j][0] * r, o[j][1] * r), pk(o[j][2] * r, o[j][3] * r));
      }
      wbar();
      uint4* tp = g_T1 + (size_t)(g * 16 + warp) * 1024 + b * 8;
#pragma unroll
      for (int nt = 0; nt < 2; nt++) {
        const int k = 16 * warp + 8 * nt + g, km = k == 0 ? 128 : 256 - k;
        uint32_t lo[4], hi[4];
#pragma unroll
        for (int a = 0; a < 2; a++) {
          const uint32_t rb = zb + (a * 8 + t) * ZROW * 4;
          float A[4], B[4];
          mma0(A, a8[a][0], a8[a][1], a8[a][2], a8[a][3], lds32(rb + zphys(k) * 4), lds32(rb + (4 * ZROW + zphys(k)) * 4));
          mma0(B, a8[a][0] ^ 0x80000000u, a8[a][1] ^ 0x80000000u, a8[a][2] ^ 0x80000000u, a8[a][3] ^ 0x80000000u,
               lds32(rb + zphys(km) * 4), lds32(rb + (4 * ZROW + zphys(km)) * 4));
#pragma unroll
          for (int e = 0; e < 2; e++) {
            float sr = A[e] + B[e], si = A[2 + e] + B[2 + e], dr = A[e] - B[e], di = A[2 + e] - B[2 + e];
            float c = vc[2 * nt + e], s = vs[2 * nt + e];
            float gr = dr * c + di * s, gi = di * c - dr * s;
            float lr = sr + gr, li = si + gi, hr = sr - gr, hii = si - gi;
            if (nt == 0 && e == 0) {
              const bool sp = warp == 0 && t == 0;
              lr = sp ? 2.f * B[0] : lr; li = sp ? 2.f * B[2] : li;
              hr = sp ? 2.f * (A[0] - A[2]) : hr; hii = sp ? 2.f * (A[0] + A[2]) : hii;
            }
            lo[2 * a + e] = pk(lr, li); hi[2 * a + e] = pk(hr, hii);
          }
        }
        const int w = (t + 4 * nt) ^ key;
        tp[w] = make_uint4((lo[0] & ~1u) | tag, lo[1], lo[2], lo[3]);
        tp[8 * 1024 + w] = make_uint4((hi[0] & ~1u) | tag, hi[1], hi[2], hi[3]);
      }
      wbar();
      STAMP(1);
      if (warp == 0) cnt_arrive(0, lane);
    }
    {
      const uint32_t off = (8 * t + g) * 128 + ((warp ^ (2 * t + (g & 1))) << 4);
      asm volatile("barrier.cluster.wait.aligned;" ::: "memory");
      mbar_wait(mb + MB_FILT * 8, 0);
      if (tid == 0) cnt_wait<false>(0, rep, base + NCTA);
      wbar();
#pragma unroll
      for (int j = 0; j < 4; j++)
        asm volatile("cp.async.cg.shared.global [%0], [%1], 16;" :: "r"(zb + j * 4096 + tid * 16), "l"(g_T1 + (size_t)b * 1024 + j * 256 + tid) : "memory");
      STAMP(2);
      uint32_t in[2][4][2], fw[2][4][2];
#pragma unroll
      for (int j = 0; j < 4; j++) {
        uint4 v = lds128(sb + FILT_OFF + off + j * 4096);
        fw[0][j][0] = v.x; fw[1][j][0] = v.y; fw[0][j][1] = v.z; fw[1][j][1] = v.w;
      }
      asm volatile("cp.async.wait_all;" ::: "memory");
      wbar();
      STAMP(3);
      uint4 iv[4];
#pragma unroll
      for (int j = 0; j < 4; j++) iv[j] = lds128(zb + off + j * 4096);
      if (((iv[0].x ^ tag) | (iv[1].x ^ tag) | (iv[2].x ^ tag) | (iv[3].x ^ tag)) & 1) {
#pragma unroll
        for (int j = 0; j < 4; j++) tag_check(iv[j], g_T1 + (size_t)b * 1024 + j * 256 + (off >> 4), tag);
      }
      __syncwarp();
#pragma unroll
      for (int j = 0; j < 4; j++) { in[0][j][0] = iv[j].x; in[1][j][0] = iv[j].y; in[0][j][1] = iv[j].z; in[1][j][1] = iv[j].w; }
#pragma unroll
      for (int sg = 0; sg < 2; sg++) {
        float cr[2][4], ci[2][4], o[4][4];
        fft_s1(K, in[sg], cr, ci);
        fft_s2(K, cr, ci, o);
#pragma unroll
        for (int j = 0; j < 4; j++)
#pragma unroll
          for (int h = 0; h < 2; h++) {
            float fr = blo(fw[sg][j][h]), fi = bhi(fw[sg][j][h]), xr = o[j][2 * h], xi = o[j][2 * h + 1];
            in[sg][j][h] = pk(xr * fi + xi * fr, xr * fr - xi * fi);
          }
        fft_s1(K, in[sg], cr, ci);
        fft_s2(K, cr, ci, o);
#pragma unroll
        for (int j = 0; j < 4; j++) { in[sg][j][0] = pk(o[j][0], o[j][1]); in[sg][j][1] = pk(o[j][2], o[j][3]); }
      }
#pragma unroll
      for (int j = 0; j < 4; j++) sts128(zb + off + j * 4096, make_uint4((in[0][j][0] & ~1u) | tag, in[1][j][0], in[0][j][1], in[1][j][1]));
      wbar();
#pragma unroll
      for (int j = 0; j < 4; j++) g_T2[(size_t)b * 1024 + j * 256 + tid] = lds128(zb + j * 4096 + tid * 16);
      wbar();
      STAMP(4);
      if (warp == 0) cnt_arrive(1, lane);
    }
    {
      uint32_t a8[2][4]; float vc[4], vs[4];
#pragma unroll
      for (int a = 0; a < 2; a++)
#pragma unroll
        for (int u = 0; u < 2; u++) {
          float c, s; cs<2048>((t + 4 * u) * (256 * g + 2 * b + a), c, s);
          a8[a][2 * u] = pk(c, s); a8[a][2 * u + 1] = pk(-s, c);
        }
#pragma unroll
      for (int i = 0; i < 4; i++) cs<512>(16 * warp + 4 * t + i + 128, vc[i], vs[i]);
      if (tid == 0) cnt_wait<false>(1, rep, base + NCTA);
      wbar();
      STAMP(5);
      const uint4* tp = g_T2 + (size_t)(t * 16 + warp) * 1024 + b * 8 + (g ^ key);
      uint4 L0 = ldcg128(tp), L1 = ldcg128(tp + 64 * 1024), H0 = ldcg128(tp + 8 * 1024), H1 = ldcg128(tp + 72 * 1024);
      if (((L0.x ^ tag) | (L1.x ^ tag) | (H0.x ^ tag) | (H1.x ^ tag)) & 1) {
        tag_check(L0, tp, tag); tag_check(L1, tp + 64 * 1024, tag); tag_check(H0, tp + 8 * 1024, tag); tag_check(H1, tp + 72 * 1024, tag);
      }
      __syncwarp();
      const uint32_t l0[4] = {L0.x, L0.y, L0.z, L0.w}, l1[4] = {L1.x, L1.y, L1.z, L1.w}, h0[4] = {H0.x, H0.y, H0.z, H0.w}, h1[4] = {H1.x, H1.y, H1.z, H1.w};
#pragma unroll
      for (int a = 0; a < 2; a++) {
        uint32_t zf[4], zm[4];
#pragma unroll
        for (int sg = 0; sg < 2; sg++) {
          float A[4], B[4];
          mma0(A, a8[a][0], a8[a][1], a8[a][2], a8[a][3], l0[2 * a + sg], l1[2 * a + sg]);
          mma0(B, a8[a][0], a8[a][1], a8[a][2], a8[a][3], h0[2 * a + sg], h1[2 * a + sg]);
#pragma unroll
          for (int e = 0; e < 2; e++) {
            const int i = 2 * e + sg;
            float sr = A[2 + e] + B[2 + e], si = A[e] + B[e], dr = A[2 + e] - B[2 + e], di = A[e] - B[e];
            float gr = dr * vc[i] - di * vs[i], gi = di * vc[i] + dr * vs[i];
            float fr = sr + gr, fi = si + gi, mr = sr - gr, mi = gi - si;
            if (i == 0) {
              const bool sp = warp == 0 && t == 0;
              fr = sp ? B[2] : fr; fi = sp ? -B[2] : fi;
              mr = sp ? 2.f * A[2] : mr; mi = sp ? -2.f * A[0] : mi;
            }
            zf[i] = pk(fi, fr); zm[i] = pk(mi, mr);
          }
        }
        const uint32_t rb = zb + (a * 8 + g) * ZROW * 4;
        const int k0 = 16 * warp + 4 * t;
        sts128(rb + zphys(k0) * 4, make_uint4(zf[0], zf[1], zf[2], zf[3]));
        sts32(rb + zphys(k0 == 0 ? 128 : 256 - k0) * 4, zm[0]);
        sts32(rb + zphys(255 - k0) * 4, zm[1]);
        sts32(rb + zphys(254 - k0) * 4, zm[2]);
        sts32(rb + zphys(253 - k0) * 4, zm[3]);
      }
      wbar();
#pragma unroll
      for (int a = 0; a < 2; a++) {
        uint32_t in[4][2];
#pragma unroll
        for (int j = 0; j < 4; j++) { uint2 v = lds64(zb + ((a * 8 + warp) * ZROW + zphys(16 * t + 64 * j) + 2 * g) * 4); in[j][0] = v.x; in[j][1] = v.y; }
        float cr[2][4], ci[2][4], o[4][4];
        fft_s1(K, in, cr, ci);
        fft_s2(K, cr, ci, o);
        float s1 = 0.f, s2 = 0.f;
        uint2* hp = (uint2*)g_h + (size_t)(256 * warp + 2 * b + a) * 128 + 8 * t + g;
#pragma unroll
        for (int j = 0; j < 4; j++) {
          uint32_t hw[2];
#pragma unroll
          for (int h = 0; h < 2; h++) {
            uint32_t y = pk(o[j][2 * h + 1], o[j][2 * h]);
            hw[h] = pk(blo(xw[a][j][h]) + blo(y), bhi(xw[a][j][h]) + bhi(y));
            float u0 = blo(hw[h]) - mean[a], u1 = bhi(hw[h]) - mean[a];
            o[j][2 * h] = u0; o[j][2 * h + 1] = u1;
            s1 += u0 + u1; s2 = fmaf(u0, u0, fmaf(u1, u1, s2));
          }
          hp[32 * j] = make_uint2(hw[0], hw[1]);
        }
#pragma unroll
        for (int m = 1; m < 32; m <<= 1) { s1 += __shfl_xor_sync(0xffffffffu, s1, m); s2 += __shfl_xor_sync(0xffffffffu, s2, m); }
        const float mu = s1 * (1.f / 512.f), var = fmaxf(s2 * (1.f / 512.f) - mu * mu, 0.f);
        const float r1 = rsqrtf(var + 1e-5f);
        const float r = r1 * rsqrtf(var * r1 * r1 + 1e-5f);
        char* np = (char*)g_Hn + (size_t)b * 4096 + (t >> 1) * 2048 + a * 1024 + warp * 128 + ((((t & 1) * 4 + (g >> 1)) ^ warp) << 4) + (g & 1) * 8;
#pragma unroll
        for (int j = 0; j < 4; j++)
          *(uint2*)(np + (size_t)j * 128 * 4096) = make_uint2(pk((o[j][0] - mu) * r, (o[j][1] - mu) * r), pk((o[j][2] - mu) * r, (o[j][3] - mu) * r));
      }
      asm volatile("fence.proxy.async.shared::cta;" ::: "memory");
      wbar();
      STAMP(6);
      if (warp == 0) { fence_gpu(); cnt_arrive(2 + (b >> 6), lane); }
      if (tid == 32) { sts32(sb + BASE_OFF, base); mbar_arrive(mb + MB_P3DONE * 8); }
    }
    const int wg = warp >> 2;
    const uint32_t peer_sb = mapa(sb, rank ^ 1);
    {
      uint32_t bias[11];
#pragma unroll
      for (int j = 0; j < 11; j++) bias[j] = (11 * ot + j < 172) ? __ldg(b1 + (11 * ot + j) * 4 + t) : 0u;
      float acc[44];
      const uint32_t da0 = desc_lo(sb + RING_OFF + wg * 2048, 0);
      uint32_t da = da0, db = desc_lo(sb, 1408), bar = mb;
      mbar_wait(mb + MB_W1 * 8, 0);
#pragma unroll 1
      for (int i = 0; i < 32; i++) {
        mbar_wait(bar + MB_FULL * 8, 0);
        if (i == 0) STAMP(7);
        asm volatile("wgmma.fence.sync.aligned;" ::: "memory");
        wgmma_n88_ss<1, 1, HI_SW128, HI_NOSW>(acc, da, db, i);
        wgmma_n88_ss<1, 1, HI_SW128, HI_NOSW>(acc, da + 256, db + 176, 1);
        asm volatile("wgmma.commit_group.sync.aligned;" ::: "memory");
        da = da == da0 + 5 * 512 ? da0 : da + 512; db += 352;
        asm volatile("wgmma.wait_group.sync.aligned 1;" ::: "memory");
        if ((tid & 127) == 0) { if (i > 0) mbar_arrive(bar + (MB_EMPTY - 1) * 8); if (i == 4) mbar_arrive_cluster(peer_sb + BAR_OFF + MB_PEER1 * 8); }
        bar += 8;
      }
      asm volatile("wgmma.wait_group.sync.aligned 0;" ::: "memory");
#pragma unroll
      for (int i = 0; i < 44; i++) asm volatile("" : "+f"(acc[i]) :: "memory");
      if ((tid & 127) == 0) mbar_arrive(mb + (MB_EMPTY + 31) * 8);
      STAMP(8);
      float keep[22], send[22];
#pragma unroll
      for (int j = 0; j < 11; j++) {
        keep[2 * j] = rank ? acc[4 * j + 2] : acc[4 * j]; keep[2 * j + 1] = rank ? acc[4 * j + 3] : acc[4 * j + 1];
        send[2 * j] = rank ? acc[4 * j] : acc[4 * j + 2]; send[2 * j + 1] = rank ? acc[4 * j + 1] : acc[4 * j + 3];
      }
      mbar_wait_cluster(mb + MB_PEER1 * 8, 0);
#pragma unroll
      for (int j = 0; j < 5; j++) st_async4(peer_sb + j * 4096 + tid * 16, send[4 * j], send[4 * j + 1], send[4 * j + 2], send[4 * j + 3], peer_sb + BAR_OFF + MB_X1 * 8);
      st_async2(peer_sb + 5 * 4096 + tid * 8, send[20], send[21], peer_sb + BAR_OFF + MB_X1 * 8);
      mbar_wait_cluster(mb + MB_X1 * 8, 0);
#pragma unroll
      for (int j = 0; j < 5; j++) {
        uint4 v = lds128(sb + j * 4096 + tid * 16);
        keep[4 * j] += __uint_as_float(v.x); keep[4 * j + 1] += __uint_as_float(v.y); keep[4 * j + 2] += __uint_as_float(v.z); keep[4 * j + 3] += __uint_as_float(v.w);
      }
      { uint2 v = lds64(sb + 5 * 4096 + tid * 8); keep[20] += __uint_as_float(v.x); keep[21] += __uint_as_float(v.y); }
      uint32_t* up = (uint32_t*)g_U + ((size_t)dt * 172 + 11 * ot) * 512 + (4 * (warp >> 1) + (g >> 1)) * 32 + (2 * (2 * (warp & 1) + rank) + (g & 1)) * 4 + t;
#pragma unroll
      for (int j = 0; j < 11; j++) {
        uint32_t v = pk(gelu(keep[2 * j] + blo(bias[j])), gelu(keep[2 * j + 1] + bhi(bias[j])));
        if (11 * ot + j < 172) up[j * 512] = v;
      }
      asm volatile("fence.proxy.async.shared::cta;" ::: "memory");
      wbar();
      STAMP(9);
      if (warp == 0) { fence_gpu(); cnt_arrive(4 + dt, lane); }
      if (tid == 32) mbar_arrive(mb + MB_X1DONE * 8);
    }
    {
      const int srow = 128 * ot + 16 * warp + 8 * rank + g;
      float acc[64];
      const uint32_t da0 = desc_lo(sb + wg * 4096, 0), db0 = desc_lo(sb + RING_OFF, 2048);
      uint32_t da = da0 + 3 * 512, db = db0 + (32 % NST) * 512, bar = mb;
      uint4 hv[4];
#pragma unroll
      for (int j = 0; j < 4; j++) hv[j] = ldcg128(g_h + (size_t)srow * 64 + dt * 16 + 4 * j + t);
      const float bias2 = __uint_as_float((uint32_t)__ldg(b2 + srow) << 16);
#pragma unroll 1
      for (int i = 0; i < 21; i++) {
        mbar_wait(bar + MB_W2 * 8, 0);
        mbar_wait(bar + (MB_FULL + 32) * 8, 0);
        if (i == 0) STAMP(10);
        asm volatile("wgmma.fence.sync.aligned;" ::: "memory");
        wgmma_n128_ss<1, 0, HI_SW128, HI_NOSW>(acc, da, db, i);
        wgmma_n128_ss<1, 0, HI_SW128, HI_NOSW>(acc, da + 128, db + 256, 1);
        asm volatile("wgmma.commit_group.sync.aligned;" ::: "memory");
        da = i == 18 ? da0 : da + 512; db = db == db0 + 5 * 512 ? db0 : db + 512;
        asm volatile("wgmma.wait_group.sync.aligned 1;" ::: "memory");
        if ((tid & 127) == 0) { if (i > 0) mbar_arrive(bar + (MB_EMPTY + 31) * 8); if (i == 4) mbar_arrive_cluster(peer_sb + BAR_OFF + MB_PEER2 * 8); }
        bar += 8;
      }
      mbar_wait(bar + MB_W2 * 8, 0);
      mbar_wait(bar + (MB_FULL + 32) * 8, 0);
      asm volatile("wgmma.fence.sync.aligned;" ::: "memory");
      wgmma_n128_ss<1, 0, HI_SW128, HI_NOSW>(acc, da, db, 1);
      asm volatile("wgmma.commit_group.sync.aligned;" ::: "memory");
      asm volatile("wgmma.wait_group.sync.aligned 0;" ::: "memory");
#pragma unroll
      for (int i = 0; i < 64; i++) asm volatile("" : "+f"(acc[i]) :: "memory");
      STAMP(11);
      mbar_wait_cluster(mb + MB_PEER2 * 8, 0);
#pragma unroll
      for (int j = 0; j < 8; j++)
        st_async4(peer_sb + 3 * 8192 + j * 4096 + tid * 16, rank ? acc[8 * j] : acc[8 * j + 2], rank ? acc[8 * j + 1] : acc[8 * j + 3],
                  rank ? acc[8 * j + 4] : acc[8 * j + 6], rank ? acc[8 * j + 5] : acc[8 * j + 7], peer_sb + BAR_OFF + MB_X2 * 8);
      float keep[32];
#pragma unroll
      for (int j = 0; j < 16; j++) {
        const uint32_t hw = j % 4 == 0 ? hv[j / 4].x : j % 4 == 1 ? hv[j / 4].y : j % 4 == 2 ? hv[j / 4].z : hv[j / 4].w;
        keep[2 * j] = (rank ? acc[4 * j + 2] : acc[4 * j]) + (bias2 + blo(hw));
        keep[2 * j + 1] = (rank ? acc[4 * j + 3] : acc[4 * j + 1]) + (bias2 + bhi(hw));
      }
      mbar_wait_cluster(mb + MB_X2 * 8, 0);
#pragma unroll
      for (int j = 0; j < 4; j++) {
        uint4 v = lds128(sb + 3 * 8192 + (2 * j) * 4096 + tid * 16), w = lds128(sb + 3 * 8192 + (2 * j + 1) * 4096 + tid * 16);
        out[(size_t)srow * 64 + dt * 16 + 4 * j + t] =
            make_uint4(pk(keep[8 * j] + __uint_as_float(v.x), keep[8 * j + 1] + __uint_as_float(v.y)), pk(keep[8 * j + 2] + __uint_as_float(v.z), keep[8 * j + 3] + __uint_as_float(v.w)),
                       pk(keep[8 * j + 4] + __uint_as_float(w.x), keep[8 * j + 5] + __uint_as_float(w.y)), pk(keep[8 * j + 6] + __uint_as_float(w.z), keep[8 * j + 7] + __uint_as_float(w.w)));
      }
      STAMP(12);
    }
  } else {
    const int pw = warp - 8;
    {
      const int i = threadIdx.x - 256;
      mbar_init(mb + i * 8, i >= MB_EMPTY && i < MB_W2 ? 2 : 1);
      if (i + 128 < MB_N) mbar_init(mb + (i + 128) * 8, i + 128 >= MB_FILT ? 128 : 1);
      if (i + 128 == MB_X1 || i + 128 == MB_X2) mbar_expect(mb + (i + 128) * 8, i + 128 == MB_X1 ? 22528 : 32768);
      asm volatile("fence.mbarrier_init.release.cluster;" ::: "memory");
    }
    STAMP(0);
    asm volatile("bar.sync 2, 128;" ::: "memory");
    asm volatile("barrier.cluster.arrive.relaxed.aligned;" ::: "memory");
    auto w1_issue = [&](int i) {
      if (elect()) { mbar_expect(mb + (MB_W1T + i) * 8, 5632); tma3d(sb + i * 5632, &tmW1, 88 * ot, 0, 128 * rank + 4 * i, mb + (MB_W1T + i) * 8); }
      __syncwarp();
    };
    if (!W1_LATE && pw < W1_WARPS) for (int i = 0; i < W1_DEPTH; i++) w1_issue(pw + W1_WARPS * i);
    {
      const int j1 = b >> 4, q = b & 15, slot = lane & 15, h = lane >> 4;
      const bool hi = q >= 8;
      const int k = 16 * (q & 7) + slot, col = hi ? 256 - k : (k == 0 ? 128 : k);
#pragma unroll 1
      for (int it = 0; it < 2; it++) {
        uint32_t vr[16], vi[16];
#pragma unroll
        for (int n = 0; n < 16; n++) {
          const int c = pw * 32 + it * 16 + n;
          int j = j1 + 8 * (2 * c + h);
          if (hi) j = (2048 - j) & 2047;
          vr[n] = __ldg(wr + j * DF + col); vi[n] = __ldg(wi + j * DF + col);
        }
#pragma unroll
        for (int n = 0; n < 16; n++) {
          const int c = pw * 32 + it * 16 + n;
          sts32(sb + FILT_OFF + c * 128 + (((slot >> 1) ^ (((c >> 3) & 3) * 2 + (c & 1))) << 4) + h * 8 + (slot & 1) * 4,
                (vr[n] | (vi[n] << 16)) ^ (hi ? 0x80000000u : 0u));
        }
      }
      mbar_arrive(mb + MB_FILT * 8);
    }
    STAMP(1);
    {
      if (W1_LATE && pw < W1_WARPS) for (int i = 0; i < W1_DEPTH; i++) w1_issue(pw + W1_WARPS * i);
      const uint32_t rd = ((lane & 7) * 11 + (lane >> 3)) * 16, wr = lane * 16;
#pragma unroll 1
      for (int box = pw < W1_WARPS ? pw : 32; box < 32; box += W1_WARPS) {
        mbar_wait(mb + (MB_W1T + box) * 8, 0);
        if (box + W1_WARPS * W1_DEPTH < 32) w1_issue(box + W1_WARPS * W1_DEPTH);
        const uint32_t p = sb + box * 5632;
        uint4 v[4][3];
#pragma unroll
        for (int n = 0; n < 4; n++) { v[n][0] = lds128(p + n * 1408 + rd); v[n][1] = lds128(p + n * 1408 + rd + 64); if (lane < 24) v[n][2] = lds128(p + n * 1408 + rd + 128); }
        __syncwarp();
#pragma unroll
        for (int n = 0; n < 4; n++) { sts128(p + n * 1408 + wr, v[n][0]); sts128(p + n * 1408 + wr + 512, v[n][1]); if (lane < 24) sts128(p + n * 1408 + wr + 1024, v[n][2]); }
      }
      if (lane == 0) asm volatile("cp.async.bulk.prefetch.L2.global [%0], %1;" :: "l"(w2 + (size_t)(b * 4 + pw) * 11008), "r"(11008) : "memory");
      asm volatile("fence.proxy.async.shared::cta;" ::: "memory");
      mbar_arrive(mb + MB_W1 * 8);
    }
    STAMP(2);
    asm volatile("barrier.cluster.wait.aligned;" ::: "memory");
    if (pw == 3) {
#pragma unroll 1
      for (int n = 0; n < 22; n++) {
        if (n < W2_PRE) mbar_wait(mb + (MB_EMPTY + min(31, max(((n + 4) * 16 + 10) / 11 - 1, W2_START + n * W2_NUM / W2_DEN))) * 8, 0);
        else { mbar_wait(mb + MB_X1DONE * 8, 0); if (W2_PACE) mbar_wait(mb + (MB_FULL + 32 - W2_PRE + n) * 8, 0); }
        if (elect()) { mbar_expect(mb + (MB_W2 + n) * 8, 8192); tma3d(sb + (n < 19 ? n + 3 : n - 19) * 8192, &tmW2, 0, 688 * rank + 32 * n, 2 * ot, mb + (MB_W2 + n) * 8); }
      }
    } else {
      int i = pw;
      uint32_t dst = sb + RING_OFF + pw * 8192;
      const uint32_t dsum = 2 * dst + 3 * 8192;
      const char* src = (const char*)g_Hn + ((size_t)dt * 128 + 64 * rank) * 4096;
#pragma unroll 1
      for (int gm = 0; gm < 2; gm++) {
        if (pw == 0) {
          mbar_wait(mb + (gm ? MB_X1DONE : MB_P3DONE) * 8, 0);
          STAMP(3 + 2 * gm);
          if (lane == 0) cnt_wait<true>(gm ? 4 + dt : 2 + rank, ot & (NREP - 1), ((lds32(sb + BASE_OFF) >> 1) + 64) >> gm);
        }
        asm volatile("bar.sync 2, 96;" ::: "memory");
        STAMP(4 + 2 * gm);
        asm volatile("fence.proxy.async.global;" ::: "memory");
#pragma unroll 1
        for (; i < (gm ? 54 : 32); i += 3) {
          if (i >= NST) mbar_wait(mb + (MB_EMPTY - NST + i) * 8, 0);
          if (elect()) {
            const int bytes = i < 53 ? 8192 : 4096;
            mbar_expect(mb + (MB_FULL + i) * 8, bytes); bulk_ld(dst, src + i * 8192, bytes, mb + (MB_FULL + i) * 8);
          }
          dst = dsum - dst;
        }
        src = (const char*)g_U + ((size_t)dt * 172 + 86 * rank) * 2048 - 32 * 8192;
      }
      STAMP(7);
    }
  }
}

typedef CUresult (*EncodeFn)(CUtensorMap*, CUtensorMapDataType, cuuint32_t, void*, const cuuint64_t*, const cuuint64_t*, const cuuint32_t*,
                             const cuuint32_t*, CUtensorMapInterleave, CUtensorMapSwizzle, CUtensorMapL2promotion, CUtensorMapFloatOOBfill);

extern "C" void kernel_launch(void* const* d_in, const int* in_sizes, int n_in, void* d_out, int out_size) {
  static EncodeFn enc = nullptr;
  if (!enc) {
    void* fn = nullptr; cudaDriverEntryPointQueryResult st;
    cudaGetDriverEntryPoint("cuTensorMapEncodeTiled", &fn, cudaEnableDefault, &st);
    enc = (EncodeFn)fn;
    cudaFuncSetAttribute(fused_kernel, cudaFuncAttributeMaxDynamicSharedMemorySize, SMEM_BYTES);
  }
  CUtensorMap tm, tm1;
  {
    cuuint64_t dims[3] = {(cuuint64_t)F_, 8, 256}, strides[2] = {(cuuint64_t)256 * F_ * 2, F_ * 2};
    cuuint32_t box[3] = {88, 8, 4}, es[3] = {1, 1, 1};
    enc(&tm1, CU_TENSOR_MAP_DATA_TYPE_BFLOAT16, 3, d_in[4], dims, strides, box, es, CU_TENSOR_MAP_INTERLEAVE_NONE, CU_TENSOR_MAP_SWIZZLE_NONE,
        W1_PROMO, CU_TENSOR_MAP_FLOAT_OOB_FILL_NONE);
  }
  {
    cuuint64_t dims[3] = {64, (cuuint64_t)F_, S_ / 64}, strides[2] = {S_ * 2, 128};
    cuuint32_t box[3] = {64, 32, 2}, es[3] = {1, 1, 1};
    enc(&tm, CU_TENSOR_MAP_DATA_TYPE_BFLOAT16, 3, d_in[6], dims, strides, box, es, CU_TENSOR_MAP_INTERLEAVE_NONE, CU_TENSOR_MAP_SWIZZLE_128B,
        CU_TENSOR_MAP_L2_PROMOTION_L2_256B, CU_TENSOR_MAP_FLOAT_OOB_FILL_NONE);
  }
  fused_kernel<<<NCTA, 384, SMEM_BYTES, cudaStreamPerThread>>>(tm1, tm, (const uint2*)d_in[0], (const unsigned short*)d_in[1], (const unsigned short*)d_in[2],
                                          (const char*)d_in[4], (const uint32_t*)d_in[5], (const char*)d_in[6], (const unsigned short*)d_in[7], (uint4*)d_out);
}
```

```cpp
#include <cuda_runtime.h>
#include <cuda.h>
#include <cuda_bf16.h>
#include <stdint.h>
#define W1_LATE 1
#define W1_PROMO CU_TENSOR_MAP_L2_PROMOTION_NONE
#define W2_NUM 1
#define W2_DEN 1
#define PF_MODE 0
#define W1_DEPTH 1
#define W1_WARPS 3
#define W2_PRE 12
#define W2_PACE 1
template<int TA, int TB, uint32_t HA, uint32_t HB> __device__ __forceinline__ void wgmma_n88_ss(float (&d)[44], uint32_t da, uint32_t db, int sd) {
  asm volatile("{\n.reg .pred p;\n.reg .b64 da, db;\nsetp.ne.b32 p, %46, 0;\nmov.b64 da, {%44, %49};\nmov.b64 db, {%45, %50};\n"
    "wgmma.mma_async.sync.aligned.m64n88k16.f32.bf16.bf16 {%0, %1, %2, %3, %4, %5, %6, %7, %8, %9, %10, %11, %12, %13, %14, %15, %16, %17, %18, %19, %20, %21, %22, %23, %24, %25, %26, %27, %28, %29, %30, %31, %32, %33, %34, %35, %36, %37, %38, %39, %40, %41, %42, %43}, da, db, p, 1, 1, %47, %48;\n}\n"
    : "+f"(d[0]), "+f"(d[1]), "+f"(d[2]), "+f"(d[3]), "+f"(d[4]), "+f"(d[5]), "+f"(d[6]), "+f"(d[7]), "+f"(d[8]), "+f"(d[9]), "+f"(d[10]), "+f"(d[11]), "+f"(d[12]), "+f"(d[13]), "+f"(d[14]), "+f"(d[15]), "+f"(d[16]), "+f"(d[17]), "+f"(d[18]), "+f"(d[19]), "+f"(d[20]), "+f"(d[21]), "+f"(d[22]), "+f"(d[23]), "+f"(d[24]), "+f"(d[25]), "+f"(d[26]), "+f"(d[27]), "+f"(d[28]), "+f"(d[29]), "+f"(d[30]), "+f"(d[31]), "+f"(d[32]), "+f"(d[33]), "+f"(d[34]), "+f"(d[35]), "+f"(d[36]), "+f"(d[37]), "+f"(d[38]), "+f"(d[39]), "+f"(d[40]), "+f"(d[41]), "+f"(d[42]), "+f"(d[43]) : "r"(da), "r"(db), "r"(sd), "n"(TA), "n"(TB), "n"(HA), "n"(HB));
}
template<int TA, int TB, uint32_t HA, uint32_t HB> __device__ __forceinline__ void wgmma_n128_ss(float (&d)[64], uint32_t da, uint32_t db, int sd) {
  asm volatile("{\n.reg .pred p;\n.reg .b64 da, db;\nsetp.ne.b32 p, %66, 0;\nmov.b64 da, {%64, %69};\nmov.b64 db, {%65, %70};\n"
    "wgmma.mma_async.sync.aligned.m64n128k16.f32.bf16.bf16 {%0, %1, %2, %3, %4, %5, %6, %7, %8, %9, %10, %11, %12, %13, %14, %15, %16, %17, %18, %19, %20, %21, %22, %23, %24, %25, %26, %27, %28, %29, %30, %31, %32, %33, %34, %35, %36, %37, %38, %39, %40, %41, %42, %43, %44, %45, %46, %47, %48, %49, %50, %51, %52, %53, %54, %55, %56, %57, %58, %59, %60, %61, %62, %63}, da, db, p, 1, 1, %67, %68;\n}\n"
    : "+f"(d[0]), "+f"(d[1]), "+f"(d[2]), "+f"(d[3]), "+f"(d[4]), "+f"(d[5]), "+f"(d[6]), "+f"(d[7]), "+f"(d[8]), "+f"(d[9]), "+f"(d[10]), "+f"(d[11]), "+f"(d[12]), "+f"(d[13]), "+f"(d[14]), "+f"(d[15]), "+f"(d[16]), "+f"(d[17]), "+f"(d[18]), "+f"(d[19]), "+f"(d[20]), "+f"(d[21]), "+f"(d[22]), "+f"(d[23]), "+f"(d[24]), "+f"(d[25]), "+f"(d[26]), "+f"(d[27]), "+f"(d[28]), "+f"(d[29]), "+f"(d[30]), "+f"(d[31]), "+f"(d[32]), "+f"(d[33]), "+f"(d[34]), "+f"(d[35]), "+f"(d[36]), "+f"(d[37]), "+f"(d[38]), "+f"(d[39]), "+f"(d[40]), "+f"(d[41]), "+f"(d[42]), "+f"(d[43]), "+f"(d[44]), "+f"(d[45]), "+f"(d[46]), "+f"(d[47]), "+f"(d[48]), "+f"(d[49]), "+f"(d[50]), "+f"(d[51]), "+f"(d[52]), "+f"(d[53]), "+f"(d[54]), "+f"(d[55]), "+f"(d[56]), "+f"(d[57]), "+f"(d[58]), "+f"(d[59]), "+f"(d[60]), "+f"(d[61]), "+f"(d[62]), "+f"(d[63]) : "r"(da), "r"(db), "r"(sd), "n"(TA), "n"(TB), "n"(HA), "n"(HB));
}

constexpr int S_ = 2048, D_ = 512, F_ = 1376, DF = 257;
constexpr int NCTA = 128;
constexpr int W_BYTES = 180224;
constexpr int RING_OFF = W_BYTES;
constexpr int NST = 6;
constexpr int BAR_OFF = RING_OFF + NST * 8192;
constexpr int SMEM_BYTES = BAR_OFF + 1536;
constexpr int FILT_OFF = RING_OFF;
constexpr int XCH_OFF = RING_OFF + 16384;
constexpr int ZROW = 328;
constexpr int MB_FULL = 0, MB_W2 = 54, MB_W1T = 76, MB_X1 = 108, MB_X2 = 109, MB_X1DONE = 110, MB_P3DONE = 111, MB_FILT = 112, MB_W1 = 113,
              MB_EMPTY = 114, MB_PEER1 = 168, MB_PEER2 = 169, MB_N = 171;
constexpr int BASE_OFF = BAR_OFF + MB_N * 8;
#define W2_START 24

__device__ uint4 g_T1[NCTA * 1024];
__device__ uint4 g_T2[NCTA * 1024];
__device__ uint4 g_h[S_ * D_ / 8];
__device__ uint4 g_Hn[4 * 128 * 256];
__device__ uint4 g_U[4 * 172 * 128];
__device__ unsigned g_cnt[8 * 4 * 64];
#define STAMP(i)

__device__ __forceinline__ void mbar_init(uint32_t b, int c) { asm volatile("mbarrier.init.shared::cta.b64 [%0], %1;" :: "r"(b), "r"(c) : "memory"); }
__device__ __forceinline__ void mbar_expect(uint32_t b, int bytes) { asm volatile("mbarrier.arrive.expect_tx.shared::cta.b64 _, [%0], %1;" :: "r"(b), "r"(bytes) : "memory"); }
__device__ __forceinline__ void mbar_arrive(uint32_t b) { asm volatile("mbarrier.arrive.shared::cta.b64 _, [%0];" :: "r"(b) : "memory"); }
__device__ __forceinline__ void mbar_arrive_cluster(uint32_t remote) { asm volatile("mbarrier.arrive.relaxed.cluster.shared::cluster.b64 _, [%0];" :: "r"(remote) : "memory"); }
__device__ __forceinline__ uint32_t mapa(uint32_t a, uint32_t cta) { uint32_t r; asm("mapa.shared::cluster.u32 %0, %1, %2;" : "=r"(r) : "r"(a), "r"(cta)); return r; }
__device__ __forceinline__ void mbar_wait(uint32_t b, int ph) {
  asm volatile("{\n.reg .pred p;\n.reg .u32 n;\nmov.u32 n, 0;\nL_W:\n"
               "mbarrier.try_wait.parity.shared::cta.b64 p, [%0], %1;\n@p bra L_D;\n"
               "add.u32 n, n, 1;\nsetp.lt.u32 p, n, 4000000;\n@p bra L_W;\ntrap;\nL_D:\n}" :: "r"(b), "r"(ph) : "memory");
}
__device__ __forceinline__ void mbar_wait_cluster(uint32_t b, int ph) {
  asm volatile("{\n.reg .pred p;\n.reg .u32 n;\nmov.u32 n, 0;\nL_W:\n"
               "mbarrier.try_wait.parity.acquire.cluster.shared::cta.b64 p, [%0], %1;\n@p bra L_D;\n"
               "add.u32 n, n, 1;\nsetp.lt.u32 p, n, 4000000;\n@p bra L_W;\ntrap;\nL_D:\n}" :: "r"(b), "r"(ph) : "memory");
}
__device__ __forceinline__ void bulk_ld(uint32_t dst, const void* src, int bytes, uint32_t bar) {
  asm volatile("cp.async.bulk.shared::cluster.global.mbarrier::complete_tx::bytes [%0], [%1], %2, [%3];" :: "r"(dst), "l"(src), "r"(bytes), "r"(bar) : "memory");
}
__device__ __forceinline__ void tma3d(uint32_t dst, const CUtensorMap* tm, int c0, int c1, int c2, uint32_t bar) {
  asm volatile("cp.async.bulk.tensor.3d.shared::cluster.global.mbarrier::complete_tx::bytes [%0], [%1, {%3, %4, %5}], [%2];"
               :: "r"(dst), "l"(tm), "r"(bar), "r"(c0), "r"(c1), "r"(c2) : "memory");
}
__device__ __forceinline__ bool elect() { uint32_t p; asm volatile("{.reg .pred p; elect.sync _|p, 0xffffffff; selp.b32 %0, 1, 0, p;}" : "=r"(p)); return p; }
__device__ __forceinline__ uint32_t desc_lo(uint32_t addr, uint32_t lbo) { return ((addr & 0x3FFFF) >> 4) | ((lbo >> 4) << 16); }
constexpr uint32_t HI_SW128 = (1024 >> 4) | (1u << 30), HI_NOSW = 128 >> 4;
__device__ __forceinline__ uint32_t pk(float lo, float hi) { uint32_t r; asm("cvt.rn.bf16x2.f32 %0, %1, %2;" : "=r"(r) : "f"(hi), "f"(lo)); return r; }
__device__ __forceinline__ float blo(uint32_t w) { return __uint_as_float(w << 16); }
__device__ __forceinline__ float bhi(uint32_t w) { return __uint_as_float(w & 0xffff0000u); }
__device__ __forceinline__ void mma(float (&c)[4], uint32_t a0, uint32_t a1, uint32_t a2, uint32_t a3, uint32_t b0, uint32_t b1) {
  asm("mma.sync.aligned.m16n8k16.row.col.f32.bf16.bf16.f32 {%0,%1,%2,%3}, {%4,%5,%6,%7}, {%8,%9}, {%0,%1,%2,%3};"
      : "+f"(c[0]), "+f"(c[1]), "+f"(c[2]), "+f"(c[3]) : "r"(a0), "r"(a1), "r"(a2), "r"(a3), "r"(b0), "r"(b1));
}
__device__ __forceinline__ void mma0(float (&c)[4], uint32_t a0, uint32_t a1, uint32_t a2, uint32_t a3, uint32_t b0, uint32_t b1) {
  asm("mma.sync.aligned.m16n8k16.row.col.f32.bf16.bf16.f32 {%0,%1,%2,%3}, {%4,%5,%6,%7}, {%8,%9}, {%10,%10,%10,%10};"
      : "=f"(c[0]), "=f"(c[1]), "=f"(c[2]), "=f"(c[3]) : "r"(a0), "r"(a1), "r"(a2), "r"(a3), "r"(b0), "r"(b1), "f"(0.f));
}
__device__ __forceinline__ void wbar() { asm volatile("bar.sync 1, 256;" ::: "memory"); }
__device__ __forceinline__ void sts32(uint32_t a, uint32_t v) { asm volatile("st.shared.b32 [%0], %1;" :: "r"(a), "r"(v) : "memory"); }
__device__ __forceinline__ void sts64(uint32_t a, uint32_t x, uint32_t y) { asm volatile("st.shared.v2.b32 [%0], {%1,%2};" :: "r"(a), "r"(x), "r"(y) : "memory"); }
__device__ __forceinline__ void sts128(uint32_t a, uint4 v) { asm volatile("st.shared.v4.b32 [%0], {%1,%2,%3,%4};" :: "r"(a), "r"(v.x), "r"(v.y), "r"(v.z), "r"(v.w) : "memory"); }
__device__ __forceinline__ uint32_t lds32(uint32_t a) { uint32_t v; asm volatile("ld.shared.b32 %0, [%1];" : "=r"(v) : "r"(a) : "memory"); return v; }
__device__ __forceinline__ uint2 lds64(uint32_t a) { uint2 v; asm volatile("ld.shared.v2.b32 {%0,%1}, [%2];" : "=r"(v.x), "=r"(v.y) : "r"(a) : "memory"); return v; }
__device__ __forceinline__ uint4 lds128(uint32_t a) { uint4 v; asm volatile("ld.shared.v4.b32 {%0,%1,%2,%3}, [%4];" : "=r"(v.x), "=r"(v.y), "=r"(v.z), "=r"(v.w) : "r"(a) : "memory"); return v; }
__device__ __forceinline__ uint4 ldcg128(const void* p) { uint4 v; asm volatile("ld.global.cg.v4.b32 {%0,%1,%2,%3}, [%4];" : "=r"(v.x), "=r"(v.y), "=r"(v.z), "=r"(v.w) : "l"(p) : "memory"); return v; }
__device__ __forceinline__ void st_async4(uint32_t a, float x, float y, float z, float w, uint32_t bar) {
  asm volatile("st.async.weak.shared::cluster.mbarrier::complete_tx::bytes.v4.f32 [%0], {%1,%2,%3,%4}, [%5];" :: "r"(a), "f"(x), "f"(y), "f"(z), "f"(w), "r"(bar) : "memory");
}
__device__ __forceinline__ void st_async2(uint32_t a, float x, float y, uint32_t bar) {
  asm volatile("st.async.weak.shared::cluster.mbarrier::complete_tx::bytes.v2.f32 [%0], {%1,%2}, [%3];" :: "r"(a), "f"(x), "f"(y), "r"(bar) : "memory");
}
constexpr int NREP = 4;
__device__ __forceinline__ void cnt_arrive(int i, int lane) {
  if (lane < NREP) asm volatile("red.relaxed.gpu.global.add.u32 [%0], 1;" :: "l"(&g_cnt[(i * NREP + lane) * 64]) : "memory");
}
template <bool ACQ> __device__ __forceinline__ void cnt_wait(int i, int rep, unsigned target) {
  unsigned v; int n = 0;
  do {
    if (ACQ) asm volatile("ld.acquire.gpu.global.u32 %0, [%1];" : "=r"(v) : "l"(&g_cnt[(i * NREP + rep) * 64]) : "memory");
    else asm volatile("ld.relaxed.gpu.global.u32 %0, [%1];" : "=r"(v) : "l"(&g_cnt[(i * NREP + rep) * 64]) : "memory");
    if (++n > 2000000) __trap(); } while ((int)(v - target) < 0);
}
__device__ __forceinline__ void fence_gpu() { asm volatile("fence.acq_rel.gpu;" ::: "memory"); }
__device__ __forceinline__ void tag_check(uint4& v, const uint4* p, uint32_t tag) {
  int n = 0;
  while ((v.x ^ tag) & 1) {
    asm volatile("ld.relaxed.gpu.global.v4.b32 {%0,%1,%2,%3}, [%4];" : "=r"(v.x), "=r"(v.y), "=r"(v.z), "=r"(v.w) : "l"(p) : "memory");
    if (++n > 2000000) __trap();
  }
}
template <int N> __device__ __forceinline__ void cs(int n, float& c, float& s) {
  n = ((n + N / 2) & (N - 1)) - N / 2;
  float a = (float)n * (6.283185307179586f / N);
  c = __cosf(a); s = __sinf(a);
}
constexpr float ALPHA = 1.13288f;
struct FftC { uint32_t ar[2][2], ai[2][2], p[4], q1, q3; float tc[2][4], ts[2][4]; };
constexpr uint32_t NEG = 0x80008000u;

__device__ __forceinline__ void fft_s1(const FftC& K, const uint32_t (&in)[4][2], float (&cr)[2][4], float (&ci)[2][4]) {
#pragma unroll
  for (int h = 0; h < 2; h++) {
    mma0(cr[h], K.ar[0][0], K.ar[1][0], K.ar[0][1], K.ar[1][1], in[0][h], in[1][h]);
    mma0(ci[h], K.ai[0][0], K.ai[1][0], K.ai[0][1], K.ai[1][1], in[0][h], in[1][h]);
  }
#pragma unroll
  for (int h = 0; h < 2; h++) {
    mma(cr[h], K.ar[0][0], K.ar[1][0] ^ NEG, K.ar[0][1], K.ar[1][1] ^ NEG, in[2][h], in[3][h]);
    mma(ci[h], K.ai[0][0], K.ai[1][0] ^ NEG, K.ai[0][1], K.ai[1][1] ^ NEG, in[2][h], in[3][h]);
  }
}
__device__ __forceinline__ void fft_s2(const FftC& K, const float (&cr)[2][4], const float (&ci)[2][4], float (&o)[4][4]) {
  uint32_t a[2][4];
#pragma unroll
  for (int h = 0; h < 2; h++)
#pragma unroll
    for (int i = 0; i < 4; i++) {
      float xr = cr[i & 1][2 * h + (i >> 1)], xi = ci[i & 1][2 * h + (i >> 1)];
      a[h][i] = pk(xr * K.tc[h][i] + xi * K.ts[h][i], xi * K.tc[h][i] - xr * K.ts[h][i]);
    }
  mma0(o[0], a[0][0], a[1][0], a[0][1], a[1][1], K.p[0], K.p[1]);
  mma0(o[1], a[0][0], a[1][0], a[0][1], a[1][1], K.p[0], K.q1);
  mma0(o[2], a[0][0], a[1][0], a[0][1], a[1][1], K.p[0], K.p[1] ^ NEG);
  mma0(o[3], a[0][0], a[1][0], a[0][1], a[1][1], K.p[0], K.q1 ^ NEG);
  mma(o[0], a[0][2], a[1][2], a[0][3], a[1][3], K.p[2], K.p[3]);
  mma(o[1], a[0][2], a[1][2], a[0][3], a[1][3], K.p[2] ^ NEG, K.q3 ^ NEG);
  mma(o[2], a[0][2], a[1][2], a[0][3], a[1][3], K.p[2], K.p[3] ^ NEG);
  mma(o[3], a[0][2], a[1][2], a[0][3], a[1][3], K.p[2] ^ NEG, K.q3);
}
__device__ __forceinline__ int zphys(int k) { return k + 8 * (k >> 5); }
__device__ __forceinline__ float gelu(float u) {
  float z = u * (0.7978845608028654f + 0.035677408136300125f * u * u), th;
  asm("tanh.approx.f32 %0, %1;" : "=f"(th) : "f"(z));
  float hu = 0.5f * u;
  return fmaf(hu, th, hu);
}

extern "C" __global__ void __cluster_dims__(2, 1, 1) __launch_bounds__(384, 1)
fused_kernel(const __grid_constant__ CUtensorMap tmW1, const __grid_constant__ CUtensorMap tmW2, const uint2* __restrict__ x, const unsigned short* __restrict__ wr,
             const unsigned short* __restrict__ wi, const char* __restrict__ w1, const uint32_t* __restrict__ b1,
             const char* __restrict__ w2, const unsigned short* __restrict__ b2, uint4* __restrict__ out) {
  extern __shared__ __align__(1024) char smem[];
  const uint32_t sb = (uint32_t)__cvta_generic_to_shared(smem);
  const uint32_t mb = sb + BAR_OFF;
  const int b = blockIdx.x, rank = b & 1, pr = b >> 1, dt = pr & 3, ot = pr >> 2;
  const int warp = __shfl_sync(0xffffffffu, threadIdx.x >> 5, 0), lane = threadIdx.x & 31;
  const int g = lane >> 2, t = lane & 3;

  if (warp < 8) {
    const int tid = threadIdx.x;
    uint32_t xw[2][4][2];
    {
      const uint2* xp = x + (size_t)(256 * warp + 2 * b) * 128 + 8 * t + g;
#pragma unroll
      for (int a = 0; a < 2; a++)
#pragma unroll
        for (int j = 0; j < 4; j++) { uint2 v = __ldg(xp + a * 128 + 32 * j); xw[a][j][0] = v.x; xw[a][j][1] = v.y; }
    }
    STAMP(0);
    asm volatile("barrier.cluster.arrive.relaxed.aligned;" ::: "memory");
    const int rep = ot & (NREP - 1);
    const unsigned base = __ldcg(&g_cnt[(1 * NREP + rep) * 64]);
    const uint32_t tag = (~base >> 7) & 1;
    FftC K;
    {
      float c, s;
#pragma unroll
      for (int h = 0; h < 2; h++)
#pragma unroll
        for (int j = 0; j < 2; j++) {
          cs<16>((2 * g + h) * (t + 4 * j), c, s);
          K.ar[h][j] = pk(ALPHA * c, ALPHA * s); K.ai[h][j] = pk(-ALPHA * s, ALPHA * c);
        }
#pragma unroll
      for (int i = 0; i < 4; i++) {
        cs<16>((4 * t + i) * (g >> 1) + 4 * (g & 1), c, s);
        K.p[i] = pk(ALPHA * c, ALPHA * s);
        if (i == 1) K.q1 = pk(-ALPHA * s, ALPHA * c);
        if (i == 3) K.q3 = pk(-ALPHA * s, ALPHA * c);
      }
#pragma unroll
      for (int h = 0; h < 2; h++)
#pragma unroll
        for (int i = 0; i < 4; i++) {
          cs<256>((2 * g + h) * (4 * t + i), c, s);
          K.tc[h][i] = c * (1.f / (ALPHA * ALPHA)); K.ts[h][i] = s * (1.f / (ALPHA * ALPHA));
        }
    }
    const int key = ((b >> 3) & 3) * 2 + (b & 1);
    const uint32_t zb = sb + XCH_OFF;
    float mean[2];
    {
      uint32_t a8[2][4]; float vc[4], vs[4];
#pragma unroll
      for (int a = 0; a < 2; a++)
#pragma unroll
        for (int u = 0; u < 2; u++) {
          float c, s; cs<2048>(g * (256 * (t + 4 * u) + 2 * b + a), c, s);
          a8[a][2 * u] = pk(c, s); a8[a][2 * u + 1] = pk(-s, c);
        }
#pragma unroll
      for (int i = 0; i < 4; i++) cs<512>(16 * warp + 8 * (i >> 1) + 2 * t + (i & 1) + 128, vc[i], vs[i]);
#pragma unroll
      for (int a = 0; a < 2; a++) {
        float cr[2][4], ci[2][4], o[4][4];
        fft_s1(K, xw[a], cr, ci);
        float sm = ((cr[0][0] + cr[0][1]) + (cr[1][0] + cr[1][1])) + ((ci[0][0] + ci[0][1]) + (ci[1][0] + ci[1][1]));
        sm += __shfl_xor_sync(0xffffffffu, sm, 1); sm += __shfl_xor_sync(0xffffffffu, sm, 2);
        sm = g == 0 ? sm * (1.f / 32.f) : 0.f;
#pragma unroll
        for (int h = 0; h < 2; h++) { cr[h][0] -= sm; cr[h][1] -= sm; ci[h][0] -= sm; ci[h][1] -= sm; }
        mean[a] = __shfl_sync(0xffffffffu, sm, 0) * (1.f / (16.f * 1.1328125f));
        float q = 0.f, q2 = 0.f;
#pragma unroll
        for (int i = 0; i < 4; i++) { q = fmaf(cr[0][i], cr[0][i], q); q2 = fmaf(cr[1][i], cr[1][i], q2); q = fmaf(ci[0][i], ci[0][i], q); q2 = fmaf(ci[1][i], ci[1][i], q2); }
        q += q2;
#pragma unroll
        for (int m = 1; m < 32; m <<= 1) q += __shfl_xor_sync(0xffffffffu, q, m);
        float r = rsqrtf(q * (1.f / (512.f * 16.f * ALPHA * ALPHA)) + 1e-5f) * 4.76837158203125e-7f;
        fft_s2(K, cr, ci, o);
#pragma unroll
        for (int j = 0; j < 4; j++)
          sts64(zb + ((a * 8 + warp) * ZROW + zphys(16 * t + 64 * j) + 2 * g) * 4, pk(o[j][0] * r, o[j][1] * r), pk(o[j][2] * r, o[j][3] * r));
      }
      wbar();
      uint4* tp = g_T1 + (size_t)(g * 16 + warp) * 1024 + b * 8;
#pragma unroll
      for (int nt = 0; nt < 2; nt++) {
        const int k = 16 * warp + 8 * nt + g, km = k == 0 ? 128 : 256 - k;
        uint32_t lo[4], hi[4];
#pragma unroll
        for (int a = 0; a < 2; a++) {
          const uint32_t rb = zb + (a * 8 + t) * ZROW * 4;
          float A[4], B[4];
          mma0(A, a8[a][0], a8[a][1], a8[a][2], a8[a][3], lds32(rb + zphys(k) * 4), lds32(rb + (4 * ZROW + zphys(k)) * 4));
          mma0(B, a8[a][0] ^ 0x80000000u, a8[a][1] ^ 0x80000000u, a8[a][2] ^ 0x80000000u, a8[a][3] ^ 0x80000000u,
               lds32(rb + zphys(km) * 4), lds32(rb + (4 * ZROW + zphys(km)) * 4));
#pragma unroll
          for (int e = 0; e < 2; e++) {
            float sr = A[e] + B[e], si = A[2 + e] + B[2 + e], dr = A[e] - B[e], di = A[2 + e] - B[2 + e];
            float c = vc[2 * nt + e], s = vs[2 * nt + e];
            float gr = dr * c + di * s, gi = di * c - dr * s;
            float lr = sr + gr, li = si + gi, hr = sr - gr, hii = si - gi;
            if (nt == 0 && e == 0) {
              const bool sp = warp == 0 && t == 0;
              lr = sp ? 2.f * B[0] : lr; li = sp ? 2.f * B[2] : li;
              hr = sp ? 2.f * (A[0] - A[2]) : hr; hii = sp ? 2.f * (A[0] + A[2]) : hii;
            }
            lo[2 * a + e] = pk(lr, li); hi[2 * a + e] = pk(hr, hii);
          }
        }
        const int w = (t + 4 * nt) ^ key;
        tp[w] = make_uint4((lo[0] & ~1u) | tag, lo[1], lo[2], lo[3]);
        tp[8 * 1024 + w] = make_uint4((hi[0] & ~1u) | tag, hi[1], hi[2], hi[3]);
      }
      wbar();
      STAMP(1);
      if (warp == 0) cnt_arrive(0, lane);
    }
    {
      const uint32_t off = (8 * t + g) * 128 + ((warp ^ (2 * t + (g & 1))) << 4);
      asm volatile("barrier.cluster.wait.aligned;" ::: "memory");
      mbar_wait(mb + MB_FILT * 8, 0);
      if (tid == 0) cnt_wait<false>(0, rep, base + NCTA);
      wbar();
#pragma unroll
      for (int j = 0; j < 4; j++)
        asm volatile("cp.async.cg.shared.global [%0], [%1], 16;" :: "r"(zb + j * 4096 + tid * 16), "l"(g_T1 + (size_t)b * 1024 + j * 256 + tid) : "memory");
      STAMP(2);
      uint32_t in[2][4][2], fw[2][4][2];
#pragma unroll
      for (int j = 0; j < 4; j++) {
        uint4 v = lds128(sb + FILT_OFF + off + j * 4096);
        fw[0][j][0] = v.x; fw[1][j][0] = v.y; fw[0][j][1] = v.z; fw[1][j][1] = v.w;
      }
      asm volatile("cp.async.wait_all;" ::: "memory");
      wbar();
      STAMP(3);
      uint4 iv[4];
#pragma unroll
      for (int j = 0; j < 4; j++) iv[j] = lds128(zb + off + j * 4096);
      if (((iv[0].x ^ tag) | (iv[1].x ^ tag) | (iv[2].x ^ tag) | (iv[3].x ^ tag)) & 1) {
#pragma unroll
        for (int j = 0; j < 4; j++) tag_check(iv[j], g_T1 + (size_t)b * 1024 + j * 256 + (off >> 4), tag);
      }
      __syncwarp();
#pragma unroll
      for (int j = 0; j < 4; j++) { in[0][j][0] = iv[j].x; in[1][j][0] = iv[j].y; in[0][j][1] = iv[j].z; in[1][j][1] = iv[j].w; }
#pragma unroll
      for (int sg = 0; sg < 2; sg++) {
        float cr[2][4], ci[2][4], o[4][4];
        fft_s1(K, in[sg], cr, ci);
        fft_s2(K, cr, ci, o);
#pragma unroll
        for (int j = 0; j < 4; j++)
#pragma unroll
          for (int h = 0; h < 2; h++) {
            float fr = blo(fw[sg][j][h]), fi = bhi(fw[sg][j][h]), xr = o[j][2 * h], xi = o[j][2 * h + 1];
            in[sg][j][h] = pk(xr * fi + xi * fr, xr * fr - xi * fi);
          }
        fft_s1(K, in[sg], cr, ci);
        fft_s2(K, cr, ci, o);
#pragma unroll
        for (int j = 0; j < 4; j++) { in[sg][j][0] = pk(o[j][0], o[j][1]); in[sg][j][1] = pk(o[j][2], o[j][3]); }
      }
#pragma unroll
      for (int j = 0; j < 4; j++) sts128(zb + off + j * 4096, make_uint4((in[0][j][0] & ~1u) | tag, in[1][j][0], in[0][j][1], in[1][j][1]));
      wbar();
#pragma unroll
      for (int j = 0; j < 4; j++) g_T2[(size_t)b * 1024 + j * 256 + tid] = lds128(zb + j * 4096 + tid * 16);
      wbar();
      STAMP(4);
      if (warp == 0) cnt_arrive(1, lane);
    }
    {
      uint32_t a8[2][4]; float vc[4], vs[4];
#pragma unroll
      for (int a = 0; a < 2; a++)
#pragma unroll
        for (int u = 0; u < 2; u++) {
          float c, s; cs<2048>((t + 4 * u) * (256 * g + 2 * b + a), c, s);
          a8[a][2 * u] = pk(c, s); a8[a][2 * u + 1] = pk(-s, c);
        }
#pragma unroll
      for (int i = 0; i < 4; i++) cs<512>(16 * warp + 4 * t + i + 128, vc[i], vs[i]);
      if (tid == 0) cnt_wait<false>(1, rep, base + NCTA);
      wbar();
      STAMP(5);
      const uint4* tp = g_T2 + (size_t)(t * 16 + warp) * 1024 + b * 8 + (g ^ key);
      uint4 L0 = ldcg128(tp), L1 = ldcg128(tp + 64 * 1024), H0 = ldcg128(tp + 8 * 1024), H1 = ldcg128(tp + 72 * 1024);
      if (((L0.x ^ tag) | (L1.x ^ tag) | (H0.x ^ tag) | (H1.x ^ tag)) & 1) {
        tag_check(L0, tp, tag); tag_check(L1, tp + 64 * 1024, tag); tag_check(H0, tp + 8 * 1024, tag); tag_check(H1, tp + 72 * 1024, tag);
      }
      __syncwarp();
      const uint32_t l0[4] = {L0.x, L0.y, L0.z, L0.w}, l1[4] = {L1.x, L1.y, L1.z, L1.w}, h0[4] = {H0.x, H0.y, H0.z, H0.w}, h1[4] = {H1.x, H1.y, H1.z, H1.w};
#pragma unroll
      for (int a = 0; a < 2; a++) {
        uint32_t zf[4], zm[4];
#pragma unroll
        for (int sg = 0; sg < 2; sg++) {
          float A[4], B[4];
          mma0(A, a8[a][0], a8[a][1], a8[a][2], a8[a][3], l0[2 * a + sg], l1[2 * a + sg]);
          mma0(B, a8[a][0], a8[a][1], a8[a][2], a8[a][3], h0[2 * a + sg], h1[2 * a + sg]);
#pragma unroll
          for (int e = 0; e < 2; e++) {
            const int i = 2 * e + sg;
            float sr = A[2 + e] + B[2 + e], si = A[e] + B[e], dr = A[2 + e] - B[2 + e], di = A[e] - B[e];
            float gr = dr * vc[i] - di * vs[i], gi = di * vc[i] + dr * vs[i];
            float fr = sr + gr, fi = si + gi, mr = sr - gr, mi = gi - si;
            if (i == 0) {
              const bool sp = warp == 0 && t == 0;
              fr = sp ? B[2] : fr; fi = sp ? -B[2] : fi;
              mr = sp ? 2.f * A[2] : mr; mi = sp ? -2.f * A[0] : mi;
            }
            zf[i] = pk(fi, fr); zm[i] = pk(mi, mr);
          }
        }
        const uint32_t rb = zb + (a * 8 + g) * ZROW * 4;
        const int k0 = 16 * warp + 4 * t;
        sts128(rb + zphys(k0) * 4, make_uint4(zf[0], zf[1], zf[2], zf[3]));
        sts32(rb + zphys(k0 == 0 ? 128 : 256 - k0) * 4, zm[0]);
        sts32(rb + zphys(255 - k0) * 4, zm[1]);
        sts32(rb + zphys(254 - k0) * 4, zm[2]);
        sts32(rb + zphys(253 - k0) * 4, zm[3]);
      }
      wbar();
#pragma unroll
      for (int a = 0; a < 2; a++) {
        uint32_t in[4][2];
#pragma unroll
        for (int j = 0; j < 4; j++) { uint2 v = lds64(zb + ((a * 8 + warp) * ZROW + zphys(16 * t + 64 * j) + 2 * g) * 4); in[j][0] = v.x; in[j][1] = v.y; }
        float cr[2][4], ci[2][4], o[4][4];
        fft_s1(K, in, cr, ci);
        fft_s2(K, cr, ci, o);
        float s1 = 0.f, s2 = 0.f;
        uint2* hp = (uint2*)g_h + (size_t)(256 * warp + 2 * b + a) * 128 + 8 * t + g;
#pragma unroll
        for (int j = 0; j < 4; j++) {
          uint32_t hw[2];
#pragma unroll
          for (int h = 0; h < 2; h++) {
            uint32_t y = pk(o[j][2 * h + 1], o[j][2 * h]);
            hw[h] = pk(blo(xw[a][j][h]) + blo(y), bhi(xw[a][j][h]) + bhi(y));
            float u0 = blo(hw[h]) - mean[a], u1 = bhi(hw[h]) - mean[a];
            o[j][2 * h] = u0; o[j][2 * h + 1] = u1;
            s1 += u0 + u1; s2 = fmaf(u0, u0, fmaf(u1, u1, s2));
          }
          hp[32 * j] = make_uint2(hw[0], hw[1]);
        }
#pragma unroll
        for (int m = 1; m < 32; m <<= 1) { s1 += __shfl_xor_sync(0xffffffffu, s1, m); s2 += __shfl_xor_sync(0xffffffffu, s2, m); }
        const float mu = s1 * (1.f / 512.f), var = fmaxf(s2 * (1.f / 512.f) - mu * mu, 0.f);
        const float r1 = rsqrtf(var + 1e-5f);
        const float r = r1 * rsqrtf(var * r1 * r1 + 1e-5f);
        char* np = (char*)g_Hn + (size_t)b * 4096 + (t >> 1) * 2048 + a * 1024 + warp * 128 + ((((t & 1) * 4 + (g >> 1)) ^ warp) << 4) + (g & 1) * 8;
#pragma unroll
        for (int j = 0; j < 4; j++)
          *(uint2*)(np + (size_t)j * 128 * 4096) = make_uint2(pk((o[j][0] - mu) * r, (o[j][1] - mu) * r), pk((o[j][2] - mu) * r, (o[j][3] - mu) * r));
      }
      asm volatile("fence.proxy.async.shared::cta;" ::: "memory");
      wbar();
      STAMP(6);
      if (warp == 0) { fence_gpu(); cnt_arrive(2 + (b >> 6), lane); }
      if (tid == 32) { sts32(sb + BASE_OFF, base); mbar_arrive(mb + MB_P3DONE * 8); }
    }
    const int wg = warp >> 2;
    const uint32_t peer_sb = mapa(sb, rank ^ 1);
    {
      uint32_t bias[11];
#pragma unroll
      for (int j = 0; j < 11; j++) bias[j] = (11 * ot + j < 172) ? __ldg(b1 + (11 * ot + j) * 4 + t) : 0u;
      float acc[44];
      const uint32_t da0 = desc_lo(sb + RING_OFF + wg * 2048, 0);
      uint32_t da = da0, db = desc_lo(sb, 1408), bar = mb;
      mbar_wait(mb + MB_W1 * 8, 0);
#pragma unroll 1
      for (int i = 0; i < 32; i++) {
        mbar_wait(bar + MB_FULL * 8, 0);
        if (i == 0) STAMP(7);
        asm volatile("wgmma.fence.sync.aligned;" ::: "memory");
        wgmma_n88_ss<1, 1, HI_SW128, HI_NOSW>(acc, da, db, i);
        wgmma_n88_ss<1, 1, HI_SW128, HI_NOSW>(acc, da + 256, db + 176, 1);
        asm volatile("wgmma.commit_group.sync.aligned;" ::: "memory");
        da = da == da0 + 5 * 512 ? da0 : da + 512; db += 352;
        asm volatile("wgmma.wait_group.sync.aligned 1;" ::: "memory");
        if ((tid & 127) == 0) { if (i > 0) mbar_arrive(bar + (MB_EMPTY - 1) * 8); if (i == 4) mbar_arrive_cluster(peer_sb + BAR_OFF + MB_PEER1 * 8); }
        bar += 8;
      }
      asm volatile("wgmma.wait_group.sync.aligned 0;" ::: "memory");
#pragma unroll
      for (int i = 0; i < 44; i++) asm volatile("" : "+f"(acc[i]) :: "memory");
      if ((tid & 127) == 0) mbar_arrive(mb + (MB_EMPTY + 31) * 8);
      STAMP(8);
      float keep[22], send[22];
#pragma unroll
      for (int j = 0; j < 11; j++) {
        keep[2 * j] = rank ? acc[4 * j + 2] : acc[4 * j]; keep[2 * j + 1] = rank ? acc[4 * j + 3] : acc[4 * j + 1];
        send[2 * j] = rank ? acc[4 * j] : acc[4 * j + 2]; send[2 * j + 1] = rank ? acc[4 * j + 1] : acc[4 * j + 3];
      }
      mbar_wait_cluster(mb + MB_PEER1 * 8, 0);
#pragma unroll
      for (int j = 0; j < 5; j++) st_async4(peer_sb + j * 4096 + tid * 16, send[4 * j], send[4 * j + 1], send[4 * j + 2], send[4 * j + 3], peer_sb + BAR_OFF + MB_X1 * 8);
      st_async2(peer_sb + 5 * 4096 + tid * 8, send[20], send[21], peer_sb + BAR_OFF + MB_X1 * 8);
      mbar_wait_cluster(mb + MB_X1 * 8, 0);
#pragma unroll
      for (int j = 0; j < 5; j++) {
        uint4 v = lds128(sb + j * 4096 + tid * 16);
        keep[4 * j] += __uint_as_float(v.x); keep[4 * j + 1] += __uint_as_float(v.y); keep[4 * j + 2] += __uint_as_float(v.z); keep[4 * j + 3] += __uint_as_float(v.w);
      }
      { uint2 v = lds64(sb + 5 * 4096 + tid * 8); keep[20] += __uint_as_float(v.x); keep[21] += __uint_as_float(v.y); }
      uint32_t* up = (uint32_t*)g_U + ((size_t)dt * 172 + 11 * ot) * 512 + (4 * (warp >> 1) + (g >> 1)) * 32 + (2 * (2 * (warp & 1) + rank) + (g & 1)) * 4 + t;
#pragma unroll
      for (int j = 0; j < 11; j++) {
        uint32_t v = pk(gelu(keep[2 * j] + blo(bias[j])), gelu(keep[2 * j + 1] + bhi(bias[j])));
        if (11 * ot + j < 172) up[j * 512] = v;
      }
      asm volatile("fence.proxy.async.shared::cta;" ::: "memory");
      wbar();
      STAMP(9);
      if (warp == 0) { fence_gpu(); cnt_arrive(4 + dt, lane); }
      if (tid == 32) mbar_arrive(mb + MB_X1DONE * 8);
    }
    {
      const int srow = 128 * ot + 16 * warp + 8 * rank + g;
      float acc[64];
      const uint32_t da0 = desc_lo(sb + wg * 4096, 0), db0 = desc_lo(sb + RING_OFF, 2048);
      uint32_t da = da0 + 3 * 512, db = db0 + (32 % NST) * 512, bar = mb;
      uint4 hv[4];
#pragma unroll
      for (int j = 0; j < 4; j++) hv[j] = ldcg128(g_h + (size_t)srow * 64 + dt * 16 + 4 * j + t);
      const float bias2 = __uint_as_float((uint32_t)__ldg(b2 + srow) << 16);
#pragma unroll 1
      for (int i = 0; i < 21; i++) {
        mbar_wait(bar + MB_W2 * 8, 0);
        mbar_wait(bar + (MB_FULL + 32) * 8, 0);
        if (i == 0) STAMP(10);
        asm volatile("wgmma.fence.sync.aligned;" ::: "memory");
        wgmma_n128_ss<1, 0, HI_SW128, HI_NOSW>(acc, da, db, i);
        wgmma_n128_ss<1, 0, HI_SW128, HI_NOSW>(acc, da + 128, db + 256, 1);
        asm volatile("wgmma.commit_group.sync.aligned;" ::: "memory");
        da = i == 18 ? da0 : da + 512; db = db == db0 + 5 * 512 ? db0 : db + 512;
        asm volatile("wgmma.wait_group.sync.aligned 1;" ::: "memory");
        if ((tid & 127) == 0) { if (i > 0) mbar_arrive(bar + (MB_EMPTY + 31) * 8); if (i == 4) mbar_arrive_cluster(peer_sb + BAR_OFF + MB_PEER2 * 8); }
        bar += 8;
      }
      mbar_wait(bar + MB_W2 * 8, 0);
      mbar_wait(bar + (MB_FULL + 32) * 8, 0);
      asm volatile("wgmma.fence.sync.aligned;" ::: "memory");
      wgmma_n128_ss<1, 0, HI_SW128, HI_NOSW>(acc, da, db, 1);
      asm volatile("wgmma.commit_group.sync.aligned;" ::: "memory");
      asm volatile("wgmma.wait_group.sync.aligned 0;" ::: "memory");
#pragma unroll
      for (int i = 0; i < 64; i++) asm volatile("" : "+f"(acc[i]) :: "memory");
      STAMP(11);
      mbar_wait_cluster(mb + MB_PEER2 * 8, 0);
#pragma unroll
      for (int j = 0; j < 8; j++)
        st_async4(peer_sb + 3 * 8192 + j * 4096 + tid * 16, rank ? acc[8 * j] : acc[8 * j + 2], rank ? acc[8 * j + 1] : acc[8 * j + 3],
                  rank ? acc[8 * j + 4] : acc[8 * j + 6], rank ? acc[8 * j + 5] : acc[8 * j + 7], peer_sb + BAR_OFF + MB_X2 * 8);
      float keep[32];
#pragma unroll
      for (int j = 0; j < 16; j++) {
        const uint32_t hw = j % 4 == 0 ? hv[j / 4].x : j % 4 == 1 ? hv[j / 4].y : j % 4 == 2 ? hv[j / 4].z : hv[j / 4].w;
        keep[2 * j] = (rank ? acc[4 * j + 2] : acc[4 * j]) + (bias2 + blo(hw));
        keep[2 * j + 1] = (rank ? acc[4 * j + 3] : acc[4 * j + 1]) + (bias2 + bhi(hw));
      }
      mbar_wait_cluster(mb + MB_X2 * 8, 0);
#pragma unroll
      for (int j = 0; j < 4; j++) {
        uint4 v = lds128(sb + 3 * 8192 + (2 * j) * 4096 + tid * 16), w = lds128(sb + 3 * 8192 + (2 * j + 1) * 4096 + tid * 16);
        out[(size_t)srow * 64 + dt * 16 + 4 * j + t] =
            make_uint4(pk(keep[8 * j] + __uint_as_float(v.x), keep[8 * j + 1] + __uint_as_float(v.y)), pk(keep[8 * j + 2] + __uint_as_float(v.z), keep[8 * j + 3] + __uint_as_float(v.w)),
                       pk(keep[8 * j + 4] + __uint_as_float(w.x), keep[8 * j + 5] + __uint_as_float(w.y)), pk(keep[8 * j + 6] + __uint_as_float(w.z), keep[8 * j + 7] + __uint_as_float(w.w)));
      }
      STAMP(12);
    }
  } else {
    const int pw = warp - 8;
    if (pw < 3 && elect()) {
#pragma unroll
      for (int i = 0; i < 57; i++) mbar_init(mb + (pw * 57 + i) * 8, pw == 2 ? 2 : 1);
      if (pw == 1) { mbar_expect(mb + MB_X1 * 8, 22528); mbar_expect(mb + MB_X2 * 8, 32768); }
      asm volatile("fence.mbarrier_init.release.cluster;" ::: "memory");
    }
    __syncwarp();
    STAMP(0);
    asm volatile("bar.sync 2, 128;" ::: "memory");
    asm volatile("barrier.cluster.arrive.relaxed.aligned;" ::: "memory");
    auto w1_issue = [&](int i) {
      if (elect()) { mbar_expect(mb + (MB_W1T + i) * 8, 5632); tma3d(sb + i * 5632, &tmW1, 88 * ot, 0, 128 * rank + 4 * i, mb + (MB_W1T + i) * 8); }
      __syncwarp();
    };
    if (!W1_LATE && pw < W1_WARPS) for (int i = 0; i < W1_DEPTH; i++) w1_issue(pw + W1_WARPS * i);
    {
      const int j1 = b >> 4, q = b & 15, slot = lane & 15, h = lane >> 4;
      const bool hi = q >= 8;
      const int k = 16 * (q & 7) + slot, col = hi ? 256 - k : (k == 0 ? 128 : k);
#pragma unroll 1
      for (int it = 0; it < 2; it++) {
        uint32_t vr[16], vi[16];
#pragma unroll
        for (int n = 0; n < 16; n++) {
          const int c = pw * 32 + it * 16 + n;
          int j = j1 + 8 * (2 * c + h);
          if (hi) j = (2048 - j) & 2047;
          vr[n] = __ldg(wr + j * DF + col); vi[n] = __ldg(wi + j * DF + col);
        }
#pragma unroll
        for (int n = 0; n < 16; n++) {
          const int c = pw * 32 + it * 16 + n;
          sts32(sb + FILT_OFF + c * 128 + (((slot >> 1) ^ (((c >> 3) & 3) * 2 + (c & 1))) << 4) + h * 8 + (slot & 1) * 4,
                (vr[n] | (vi[n] << 16)) ^ (hi ? 0x80000000u : 0u));
        }
      }
      asm volatile("bar.sync 2, 128;" ::: "memory");
      if (threadIdx.x == 352) mbar_arrive(mb + MB_FILT * 8);
    }
    STAMP(1);
    {
      if (W1_LATE && pw < W1_WARPS) for (int i = 0; i < W1_DEPTH; i++) w1_issue(pw + W1_WARPS * i);
      const uint32_t rd = ((lane & 7) * 11 + (lane >> 3)) * 16, wr = lane * 16;
#pragma unroll 1
      for (int box = pw < W1_WARPS ? pw : 32; box < 32; box += W1_WARPS) {
        mbar_wait(mb + (MB_W1T + box) * 8, 0);
        if (box + W1_WARPS * W1_DEPTH < 32) w1_issue(box + W1_WARPS * W1_DEPTH);
        const uint32_t p = sb + box * 5632;
        uint4 v[4][3];
#pragma unroll
        for (int n = 0; n < 4; n++) { v[n][0] = lds128(p + n * 1408 + rd); v[n][1] = lds128(p + n * 1408 + rd + 64); if (lane < 24) v[n][2] = lds128(p + n * 1408 + rd + 128); }
        __syncwarp();
#pragma unroll
        for (int n = 0; n < 4; n++) { sts128(p + n * 1408 + wr, v[n][0]); sts128(p + n * 1408 + wr + 512, v[n][1]); if (lane < 24) sts128(p + n * 1408 + wr + 1024, v[n][2]); }
      }
      if (lane == 0) asm volatile("cp.async.bulk.prefetch.L2.global [%0], %1;" :: "l"(w2 + (size_t)(b * 4 + pw) * 11008), "r"(11008) : "memory");
      asm volatile("fence.proxy.async.shared::cta;" ::: "memory");
      asm volatile("bar.sync 2, 128;" ::: "memory");
      if (threadIdx.x == 352) mbar_arrive(mb + MB_W1 * 8);
    }
    STAMP(2);
    asm volatile("barrier.cluster.wait.aligned;" ::: "memory");
    if (pw == 3) {
#pragma unroll 1
      for (int n = 0; n < 22; n++) {
        if (n < W2_PRE) mbar_wait(mb + (MB_EMPTY + min(31, max(((n + 4) * 16 + 10) / 11 - 1, W2_START + n * W2_NUM / W2_DEN))) * 8, 0);
        else { mbar_wait(mb + MB_X1DONE * 8, 0); if (W2_PACE) mbar_wait(mb + (MB_FULL + 32 - W2_PRE + n) * 8, 0); }
        if (elect()) { mbar_expect(mb + (MB_W2 + n) * 8, 8192); tma3d(sb + (n < 19 ? n + 3 : n - 19) * 8192, &tmW2, 0, 688 * rank + 32 * n, 2 * ot, mb + (MB_W2 + n) * 8); }
      }
    } else {
      int i = pw;
      uint32_t dst = sb + RING_OFF + pw * 8192;
      const uint32_t dsum = 2 * dst + 3 * 8192;
      const char* src = (const char*)g_Hn + ((size_t)dt * 128 + 64 * rank) * 4096;
#pragma unroll 1
      for (int gm = 0; gm < 2; gm++) {
        if (pw == 0) {
          mbar_wait(mb + (gm ? MB_X1DONE : MB_P3DONE) * 8, 0);
          STAMP(3 + 2 * gm);
          if (lane == 0) cnt_wait<true>(gm ? 4 + dt : 2 + rank, ot & (NREP - 1), ((lds32(sb + BASE_OFF) >> 1) + 64) >> gm);
        }
        asm volatile("bar.sync 2, 96;" ::: "memory");
        STAMP(4 + 2 * gm);
        asm volatile("fence.proxy.async.global;" ::: "memory");
#pragma unroll 1
        for (; i < (gm ? 54 : 32); i += 3) {
          if (i >= NST) mbar_wait(mb + (MB_EMPTY - NST + i) * 8, 0);
          if (elect()) {
            const int bytes = i < 53 ? 8192 : 4096;
            mbar_expect(mb + (MB_FULL + i) * 8, bytes); bulk_ld(dst, src + i * 8192, bytes, mb + (MB_FULL + i) * 8);
          }
          dst = dsum - dst;
        }
        src = (const char*)g_U + ((size_t)dt * 172 + 86 * rank) * 2048 - 32 * 8192;
      }
      STAMP(7);
    }
  }
}

typedef CUresult (*EncodeFn)(CUtensorMap*, CUtensorMapDataType, cuuint32_t, void*, const cuuint64_t*, const cuuint64_t*, const cuuint32_t*,
                             const cuuint32_t*, CUtensorMapInterleave, CUtensorMapSwizzle, CUtensorMapL2promotion, CUtensorMapFloatOOBfill);

extern "C" void kernel_launch(void* const* d_in, const int* in_sizes, int n_in, void* d_out, int out_size) {
  static EncodeFn enc = nullptr;
  if (!enc) {
    void* fn = nullptr; cudaDriverEntryPointQueryResult st;
    cudaGetDriverEntryPoint("cuTensorMapEncodeTiled", &fn, cudaEnableDefault, &st);
    enc = (EncodeFn)fn;
    cudaFuncSetAttribute(fused_kernel, cudaFuncAttributeMaxDynamicSharedMemorySize, SMEM_BYTES);
  }
  CUtensorMap tm, tm1;
  {
    cuuint64_t dims[3] = {(cuuint64_t)F_, 8, 256}, strides[2] = {(cuuint64_t)256 * F_ * 2, F_ * 2};
    cuuint32_t box[3] = {88, 8, 4}, es[3] = {1, 1, 1};
    enc(&tm1, CU_TENSOR_MAP_DATA_TYPE_BFLOAT16, 3, d_in[4], dims, strides, box, es, CU_TENSOR_MAP_INTERLEAVE_NONE, CU_TENSOR_MAP_SWIZZLE_NONE,
        W1_PROMO, CU_TENSOR_MAP_FLOAT_OOB_FILL_NONE);
  }
  {
    cuuint64_t dims[3] = {64, (cuuint64_t)F_, S_ / 64}, strides[2] = {S_ * 2, 128};
    cuuint32_t box[3] = {64, 32, 2}, es[3] = {1, 1, 1};
    enc(&tm, CU_TENSOR_MAP_DATA_TYPE_BFLOAT16, 3, d_in[6], dims, strides, box, es, CU_TENSOR_MAP_INTERLEAVE_NONE, CU_TENSOR_MAP_SWIZZLE_128B,
        CU_TENSOR_MAP_L2_PROMOTION_L2_256B, CU_TENSOR_MAP_FLOAT_OOB_FILL_NONE);
  }
  fused_kernel<<<NCTA, 384, SMEM_BYTES, cudaStreamPerThread>>>(tm1, tm, (const uint2*)d_in[0], (const unsigned short*)d_in[1], (const unsigned short*)d_in[2],
                                          (const char*)d_in[4], (const uint32_t*)d_in[5], (const char*)d_in[6], (const unsigned short*)d_in[7], (uint4*)d_out);
}
```

```cpp
#include <cuda_runtime.h>
#include <cuda.h>
#include <cuda_bf16.h>
#include <stdint.h>
#define W1_LATE 1
#define W1_PROMO CU_TENSOR_MAP_L2_PROMOTION_NONE
#define W2_NUM 1
#define W2_DEN 1
#define PF_W1 0
#define W1_DEPTH 1
#define W1_WARPS 4
#define W2_PRE 12
#define W2_PACE 1
template<int TA, int TB, uint32_t HA, uint32_t HB> __device__ __forceinline__ void wgmma_n88_ss(float (&d)[44], uint32_t da, uint32_t db, int sd) {
  asm volatile("{\n.reg .pred p;\n.reg .b64 da, db;\nsetp.ne.b32 p, %46, 0;\nmov.b64 da, {%44, %49};\nmov.b64 db, {%45, %50};\n"
    "wgmma.mma_async.sync.aligned.m64n88k16.f32.bf16.bf16 {%0, %1, %2, %3, %4, %5, %6, %7, %8, %9, %10, %11, %12, %13, %14, %15, %16, %17, %18, %19, %20, %21, %22, %23, %24, %25, %26, %27, %28, %29, %30, %31, %32, %33, %34, %35, %36, %37, %38, %39, %40, %41, %42, %43}, da, db, p, 1, 1, %47, %48;\n}\n"
    : "+f"(d[0]), "+f"(d[1]), "+f"(d[2]), "+f"(d[3]), "+f"(d[4]), "+f"(d[5]), "+f"(d[6]), "+f"(d[7]), "+f"(d[8]), "+f"(d[9]), "+f"(d[10]), "+f"(d[11]), "+f"(d[12]), "+f"(d[13]), "+f"(d[14]), "+f"(d[15]), "+f"(d[16]), "+f"(d[17]), "+f"(d[18]), "+f"(d[19]), "+f"(d[20]), "+f"(d[21]), "+f"(d[22]), "+f"(d[23]), "+f"(d[24]), "+f"(d[25]), "+f"(d[26]), "+f"(d[27]), "+f"(d[28]), "+f"(d[29]), "+f"(d[30]), "+f"(d[31]), "+f"(d[32]), "+f"(d[33]), "+f"(d[34]), "+f"(d[35]), "+f"(d[36]), "+f"(d[37]), "+f"(d[38]), "+f"(d[39]), "+f"(d[40]), "+f"(d[41]), "+f"(d[42]), "+f"(d[43]) : "r"(da), "r"(db), "r"(sd), "n"(TA), "n"(TB), "n"(HA), "n"(HB));
}
template<int TA, int TB, uint32_t HA, uint32_t HB> __device__ __forceinline__ void wgmma_n128_ss(float (&d)[64], uint32_t da, uint32_t db, int sd) {
  asm volatile("{\n.reg .pred p;\n.reg .b64 da, db;\nsetp.ne.b32 p, %66, 0;\nmov.b64 da, {%64, %69};\nmov.b64 db, {%65, %70};\n"
    "wgmma.mma_async.sync.aligned.m64n128k16.f32.bf16.bf16 {%0, %1, %2, %3, %4, %5, %6, %7, %8, %9, %10, %11, %12, %13, %14, %15, %16, %17, %18, %19, %20, %21, %22, %23, %24, %25, %26, %27, %28, %29, %30, %31, %32, %33, %34, %35, %36, %37, %38, %39, %40, %41, %42, %43, %44, %45, %46, %47, %48, %49, %50, %51, %52, %53, %54, %55, %56, %57, %58, %59, %60, %61, %62, %63}, da, db, p, 1, 1, %67, %68;\n}\n"
    : "+f"(d[0]), "+f"(d[1]), "+f"(d[2]), "+f"(d[3]), "+f"(d[4]), "+f"(d[5]), "+f"(d[6]), "+f"(d[7]), "+f"(d[8]), "+f"(d[9]), "+f"(d[10]), "+f"(d[11]), "+f"(d[12]), "+f"(d[13]), "+f"(d[14]), "+f"(d[15]), "+f"(d[16]), "+f"(d[17]), "+f"(d[18]), "+f"(d[19]), "+f"(d[20]), "+f"(d[21]), "+f"(d[22]), "+f"(d[23]), "+f"(d[24]), "+f"(d[25]), "+f"(d[26]), "+f"(d[27]), "+f"(d[28]), "+f"(d[29]), "+f"(d[30]), "+f"(d[31]), "+f"(d[32]), "+f"(d[33]), "+f"(d[34]), "+f"(d[35]), "+f"(d[36]), "+f"(d[37]), "+f"(d[38]), "+f"(d[39]), "+f"(d[40]), "+f"(d[41]), "+f"(d[42]), "+f"(d[43]), "+f"(d[44]), "+f"(d[45]), "+f"(d[46]), "+f"(d[47]), "+f"(d[48]), "+f"(d[49]), "+f"(d[50]), "+f"(d[51]), "+f"(d[52]), "+f"(d[53]), "+f"(d[54]), "+f"(d[55]), "+f"(d[56]), "+f"(d[57]), "+f"(d[58]), "+f"(d[59]), "+f"(d[60]), "+f"(d[61]), "+f"(d[62]), "+f"(d[63]) : "r"(da), "r"(db), "r"(sd), "n"(TA), "n"(TB), "n"(HA), "n"(HB));
}

constexpr int S_ = 2048, D_ = 512, F_ = 1376, DF = 257;
constexpr int NCTA = 128;
constexpr int W_BYTES = 180224;
constexpr int RING_OFF = W_BYTES;
constexpr int NST = 6;
constexpr int BAR_OFF = RING_OFF + NST * 8192;
constexpr int SMEM_BYTES = BAR_OFF + 1536;
constexpr int FILT_OFF = RING_OFF;
constexpr int XCH_OFF = RING_OFF + 16384;
constexpr int ZROW = 328;
constexpr int MB_FULL = 0, MB_W2 = 54, MB_W1T = 76, MB_X1 = 108, MB_X2 = 109, MB_X1DONE = 110, MB_P3DONE = 111, MB_FILT = 112, MB_W1 = 113,
              MB_EMPTY = 114, MB_PEER1 = 168, MB_PEER2 = 169, MB_N = 171;
constexpr int BASE_OFF = BAR_OFF + MB_N * 8;
#define W2_START 24

__device__ uint4 g_T1[NCTA * 1024];
__device__ uint4 g_T2[NCTA * 1024];
__device__ uint4 g_h[S_ * D_ / 8];
__device__ uint4 g_Hn[4 * 128 * 256];
__device__ uint4 g_U[4 * 172 * 128];
__device__ unsigned g_cnt[8 * 4 * 64];
#define STAMP(i)

__device__ __forceinline__ void mbar_init(uint32_t b, int c) { asm volatile("mbarrier.init.shared::cta.b64 [%0], %1;" :: "r"(b), "r"(c) : "memory"); }
__device__ __forceinline__ void mbar_expect(uint32_t b, int bytes) { asm volatile("mbarrier.arrive.expect_tx.shared::cta.b64 _, [%0], %1;" :: "r"(b), "r"(bytes) : "memory"); }
__device__ __forceinline__ void mbar_arrive(uint32_t b) { asm volatile("mbarrier.arrive.shared::cta.b64 _, [%0];" :: "r"(b) : "memory"); }
__device__ __forceinline__ void mbar_arrive_cluster(uint32_t remote) { asm volatile("mbarrier.arrive.relaxed.cluster.shared::cluster.b64 _, [%0];" :: "r"(remote) : "memory"); }
__device__ __forceinline__ uint32_t mapa(uint32_t a, uint32_t cta) { uint32_t r; asm("mapa.shared::cluster.u32 %0, %1, %2;" : "=r"(r) : "r"(a), "r"(cta)); return r; }
__device__ __forceinline__ void mbar_wait(uint32_t b, int ph) {
  asm volatile("{\n.reg .pred p;\n.reg .u32 n;\nmov.u32 n, 0;\nL_W:\n"
               "mbarrier.try_wait.parity.shared::cta.b64 p, [%0], %1;\n@p bra L_D;\n"
               "add.u32 n, n, 1;\nsetp.lt.u32 p, n, 4000000;\n@p bra L_W;\ntrap;\nL_D:\n}" :: "r"(b), "r"(ph) : "memory");
}
__device__ __forceinline__ void mbar_wait_cluster(uint32_t b, int ph) {
  asm volatile("{\n.reg .pred p;\n.reg .u32 n;\nmov.u32 n, 0;\nL_W:\n"
               "mbarrier.try_wait.parity.acquire.cluster.shared::cta.b64 p, [%0], %1;\n@p bra L_D;\n"
               "add.u32 n, n, 1;\nsetp.lt.u32 p, n, 4000000;\n@p bra L_W;\ntrap;\nL_D:\n}" :: "r"(b), "r"(ph) : "memory");
}
__device__ __forceinline__ void bulk_ld(uint32_t dst, const void* src, int bytes, uint32_t bar) {
  asm volatile("cp.async.bulk.shared::cluster.global.mbarrier::complete_tx::bytes [%0], [%1], %2, [%3];" :: "r"(dst), "l"(src), "r"(bytes), "r"(bar) : "memory");
}
__device__ __forceinline__ void tma3d(uint32_t dst, const CUtensorMap* tm, int c0, int c1, int c2, uint32_t bar) {
  asm volatile("cp.async.bulk.tensor.3d.shared::cluster.global.mbarrier::complete_tx::bytes [%0], [%1, {%3, %4, %5}], [%2];"
               :: "r"(dst), "l"(tm), "r"(bar), "r"(c0), "r"(c1), "r"(c2) : "memory");
}
__device__ __forceinline__ bool elect() { uint32_t p; asm volatile("{.reg .pred p; elect.sync _|p, 0xffffffff; selp.b32 %0, 1, 0, p;}" : "=r"(p)); return p; }
__device__ __forceinline__ uint32_t desc_lo(uint32_t addr, uint32_t lbo) { return ((addr & 0x3FFFF) >> 4) | ((lbo >> 4) << 16); }
constexpr uint32_t HI_SW128 = (1024 >> 4) | (1u << 30), HI_NOSW = 128 >> 4;
__device__ __forceinline__ uint32_t pk(float lo, float hi) { uint32_t r; asm("cvt.rn.bf16x2.f32 %0, %1, %2;" : "=r"(r) : "f"(hi), "f"(lo)); return r; }
__device__ __forceinline__ float blo(uint32_t w) { return __uint_as_float(w << 16); }
__device__ __forceinline__ float bhi(uint32_t w) { return __uint_as_float(w & 0xffff0000u); }
__device__ __forceinline__ void mmac(float (&d)[4], const float (&c)[4], const uint32_t (&a)[4], uint32_t b0, uint32_t b1) {
  asm("mma.sync.aligned.m16n8k16.row.col.f32.bf16.bf16.f32 {%0,%1,%2,%3}, {%4,%5,%6,%7}, {%8,%9}, {%10,%11,%12,%13};"
      : "=f"(d[0]), "=f"(d[1]), "=f"(d[2]), "=f"(d[3]) : "r"(a[0]), "r"(a[1]), "r"(a[2]), "r"(a[3]), "r"(b0), "r"(b1), "f"(c[0]), "f"(c[1]), "f"(c[2]), "f"(c[3]));
}
__device__ __forceinline__ void mma0(float (&d)[4], const uint32_t (&a)[4], uint32_t b0, uint32_t b1) { const float z[4] = {0.f, 0.f, 0.f, 0.f}; mmac(d, z, a, b0, b1); }
__device__ __forceinline__ uint32_t pin(uint32_t v) { asm volatile("shfl.sync.bfly.b32 %0, %0, 0, 31, 0xffffffff;" : "+r"(v)); return v; }
__device__ __forceinline__ float pinf(float v) { asm volatile("" : "+f"(v)); return v; }
__device__ __forceinline__ void wbar() { asm volatile("bar.sync 1, 256;" ::: "memory"); }
__device__ __forceinline__ void sts32(uint32_t a, uint32_t v) { asm volatile("st.shared.b32 [%0], %1;" :: "r"(a), "r"(v) : "memory"); }
__device__ __forceinline__ void sts64(uint32_t a, uint32_t x, uint32_t y) { asm volatile("st.shared.v2.b32 [%0], {%1,%2};" :: "r"(a), "r"(x), "r"(y) : "memory"); }
__device__ __forceinline__ void sts128(uint32_t a, uint4 v) { asm volatile("st.shared.v4.b32 [%0], {%1,%2,%3,%4};" :: "r"(a), "r"(v.x), "r"(v.y), "r"(v.z), "r"(v.w) : "memory"); }
__device__ __forceinline__ uint32_t lds32(uint32_t a) { uint32_t v; asm volatile("ld.shared.b32 %0, [%1];" : "=r"(v) : "r"(a) : "memory"); return v; }
__device__ __forceinline__ uint2 lds64(uint32_t a) { uint2 v; asm volatile("ld.shared.v2.b32 {%0,%1}, [%2];" : "=r"(v.x), "=r"(v.y) : "r"(a) : "memory"); return v; }
__device__ __forceinline__ uint4 lds128(uint32_t a) { uint4 v; asm volatile("ld.shared.v4.b32 {%0,%1,%2,%3}, [%4];" : "=r"(v.x), "=r"(v.y), "=r"(v.z), "=r"(v.w) : "r"(a) : "memory"); return v; }
__device__ __forceinline__ uint4 ldcg128(const void* p) { uint4 v; asm volatile("ld.global.cg.v4.b32 {%0,%1,%2,%3}, [%4];" : "=r"(v.x), "=r"(v.y), "=r"(v.z), "=r"(v.w) : "l"(p) : "memory"); return v; }
__device__ __forceinline__ void st_async4(uint32_t a, float x, float y, float z, float w, uint32_t bar) {
  asm volatile("st.async.weak.shared::cluster.mbarrier::complete_tx::bytes.v4.f32 [%0], {%1,%2,%3,%4}, [%5];" :: "r"(a), "f"(x), "f"(y), "f"(z), "f"(w), "r"(bar) : "memory");
}
__device__ __forceinline__ void st_async2(uint32_t a, float x, float y, uint32_t bar) {
  asm volatile("st.async.weak.shared::cluster.mbarrier::complete_tx::bytes.v2.f32 [%0], {%1,%2}, [%3];" :: "r"(a), "f"(x), "f"(y), "r"(bar) : "memory");
}
constexpr int NREP = 4;
__device__ __forceinline__ void cnt_arrive(int i, int lane) {
  if (lane < NREP) asm volatile("red.relaxed.gpu.global.add.u32 [%0], 1;" :: "l"(&g_cnt[(i * NREP + lane) * 64]) : "memory");
}
template <bool ACQ> __device__ __forceinline__ void cnt_wait(int i, int rep, unsigned target) {
  unsigned v; int n = 0;
  do {
    if (ACQ) asm volatile("ld.acquire.gpu.global.u32 %0, [%1];" : "=r"(v) : "l"(&g_cnt[(i * NREP + rep) * 64]) : "memory");
    else asm volatile("ld.relaxed.gpu.global.u32 %0, [%1];" : "=r"(v) : "l"(&g_cnt[(i * NREP + rep) * 64]) : "memory");
    if (++n > 2000000) __trap(); } while ((int)(v - target) < 0);
}
__device__ __forceinline__ void fence_gpu() { asm volatile("fence.acq_rel.gpu;" ::: "memory"); }
__device__ __forceinline__ void tag_check(uint4& v, const uint4* p, uint32_t tag) {
  int n = 0;
  while ((v.x ^ tag) & 1) {
    asm volatile("ld.relaxed.gpu.global.v4.b32 {%0,%1,%2,%3}, [%4];" : "=r"(v.x), "=r"(v.y), "=r"(v.z), "=r"(v.w) : "l"(p) : "memory");
    if (++n > 2000000) __trap();
  }
}
template <int N> __device__ __forceinline__ void cs(int n, float& c, float& s) {
  n = ((n + N / 2) & (N - 1)) - N / 2;
  float a = (float)n * (6.283185307179586f / N);
  c = __cosf(a); s = __sinf(a);
}
constexpr float ALPHA = 1.13288f;
struct FftC { uint32_t a[4][4], b[8][2]; float tc[2][4], ts[2][4]; };
constexpr uint32_t NEG = 0x80008000u;

__device__ __forceinline__ void fft_s1(const FftC& K, const uint32_t (&in)[4][2], float (&cr)[2][4], float (&ci)[2][4]) {
#pragma unroll
  for (int h = 0; h < 2; h++) { mma0(cr[h], K.a[0], in[0][h], in[1][h]); mma0(ci[h], K.a[1], in[0][h], in[1][h]); }
#pragma unroll
  for (int h = 0; h < 2; h++) { mmac(cr[h], cr[h], K.a[2], in[2][h], in[3][h]); mmac(ci[h], ci[h], K.a[3], in[2][h], in[3][h]); }
}
__device__ __forceinline__ void fft_s2(const FftC& K, const float (&cr)[2][4], const float (&ci)[2][4], float (&o)[4][4]) {
  uint32_t a[2][4];
#pragma unroll
  for (int h = 0; h < 2; h++)
#pragma unroll
    for (int i = 0; i < 4; i++) {
      float xr = cr[i & 1][2 * h + (i >> 1)], xi = ci[i & 1][2 * h + (i >> 1)];
      a[i >> 1][2 * (i & 1) + h] = pk(xr * K.tc[h][i] + xi * K.ts[h][i], xi * K.tc[h][i] - xr * K.ts[h][i]);
    }
#pragma unroll
  for (int j = 0; j < 4; j++) mma0(o[j], a[0], K.b[j][0], K.b[j][1]);
#pragma unroll
  for (int j = 0; j < 4; j++) mmac(o[j], o[j], a[1], K.b[4 + j][0], K.b[4 + j][1]);
}
__device__ __forceinline__ int zphys(int k) { return k + 8 * (k >> 5); }
__device__ __forceinline__ float gelu(float u) {
  float z = u * (0.7978845608028654f + 0.035677408136300125f * u * u), th;
  asm("tanh.approx.f32 %0, %1;" : "=f"(th) : "f"(z));
  float hu = 0.5f * u;
  return fmaf(hu, th, hu);
}

extern "C" __global__ void __cluster_dims__(2, 1, 1) __launch_bounds__(384, 1)
fused_kernel(const __grid_constant__ CUtensorMap tmW1, const __grid_constant__ CUtensorMap tmW2, const uint2* __restrict__ x, const unsigned short* __restrict__ wr,
             const unsigned short* __restrict__ wi, const char* __restrict__ w1, const uint32_t* __restrict__ b1,
             const char* __restrict__ w2, const unsigned short* __restrict__ b2, uint4* __restrict__ out) {
  extern __shared__ __align__(1024) char smem[];
  const uint32_t sb = (uint32_t)__cvta_generic_to_shared(smem);
  const uint32_t mb = sb + BAR_OFF;
  const int b = blockIdx.x, rank = b & 1, pr = b >> 1, dt = pr & 3, ot = pr >> 2;
  const int warp = __shfl_sync(0xffffffffu, threadIdx.x >> 5, 0), lane = threadIdx.x & 31;
  const int g = lane >> 2, t = lane & 3;

  if (warp < 8) {
    const int tid = threadIdx.x;
    uint32_t xw[2][4][2];
    {
      const uint2* xp = x + (size_t)(256 * warp + 2 * b) * 128 + 8 * t + g;
#pragma unroll
      for (int a = 0; a < 2; a++)
#pragma unroll
        for (int j = 0; j < 4; j++) { uint2 v = __ldg(xp + a * 128 + 32 * j); xw[a][j][0] = v.x; xw[a][j][1] = v.y; }
    }
    STAMP(0);
    asm volatile("barrier.cluster.arrive.relaxed.aligned;" ::: "memory");
    const int rep = ot & (NREP - 1);
    const unsigned base = __ldcg(&g_cnt[(1 * NREP + rep) * 64]);
    const uint32_t tag = (~base >> 7) & 1;
    FftC K;
    {
      float c, s;
#pragma unroll
      for (int h = 0; h < 2; h++)
#pragma unroll
        for (int j = 0; j < 2; j++) {
          cs<16>((2 * g + h) * (t + 4 * j), c, s);
          const uint32_t re = pk(ALPHA * c, ALPHA * s), im = pk(-ALPHA * s, ALPHA * c);
          K.a[0][2 * j + h] = re; K.a[1][2 * j + h] = im; K.a[2][2 * j + h] = pin(h ? re ^ NEG : re); K.a[3][2 * j + h] = pin(h ? im ^ NEG : im);
        }
#pragma unroll
      for (int i = 0; i < 4; i++) {
        cs<16>((4 * t + i) * (g >> 1) + 4 * (g & 1), c, s);
        const uint32_t P = pk(ALPHA * c, ALPHA * s), Q = pk(-ALPHA * s, ALPHA * c);
#pragma unroll
        for (int jj = 0; jj < 4; jj++) { const uint32_t v = ((i * jj) & 1 ? Q : P) ^ ((i * jj) & 2 ? NEG : 0u); K.b[4 * (i >> 1) + jj][i & 1] = jj ? pin(v) : v; }
      }
#pragma unroll
      for (int h = 0; h < 2; h++)
#pragma unroll
        for (int i = 0; i < 4; i++) {
          cs<256>((2 * g + h) * (4 * t + i), c, s);
          K.tc[h][i] = c * (1.f / (ALPHA * ALPHA)); K.ts[h][i] = s * (1.f / (ALPHA * ALPHA));
        }
    }
    const int key = ((b >> 3) & 3) * 2 + (b & 1);
    const uint32_t zb = sb + XCH_OFF;
    float mean[2];
    {
      uint32_t a8[2][4], a8c[2][4], a8n[2][4]; float vc[4], vs[4];
#pragma unroll
      for (int a = 0; a < 2; a++)
#pragma unroll
        for (int u = 0; u < 4; u++) {
          float c, s; cs<2048>(g * (256 * (t + 4 * (u >> 1)) + 2 * b + a), c, s);
          a8[a][u] = u & 1 ? pk(-s, c) : pk(c, s);
          a8c[a][u] = pin(a8[a][u] ^ 0x80000000u); a8n[a][u] = pin(a8[a][u] ^ 0x00008000u);
        }
#pragma unroll
      for (int i = 0; i < 4; i++) { cs<512>(16 * warp + 8 * (i >> 1) + 2 * t + (i & 1) + 128, vc[i], vs[i]); vc[i] = pinf(vc[i]); vs[i] = pinf(vs[i]); }
#pragma unroll
      for (int a = 0; a < 2; a++) {
        float cr[2][4], ci[2][4], o[4][4];
        fft_s1(K, xw[a], cr, ci);
        float sm = ((cr[0][0] + cr[0][1]) + (cr[1][0] + cr[1][1])) + ((ci[0][0] + ci[0][1]) + (ci[1][0] + ci[1][1]));
        sm += __shfl_xor_sync(0xffffffffu, sm, 1); sm += __shfl_xor_sync(0xffffffffu, sm, 2);
        sm = g == 0 ? sm * (1.f / 32.f) : 0.f;
#pragma unroll
        for (int h = 0; h < 2; h++) { cr[h][0] -= sm; cr[h][1] -= sm; ci[h][0] -= sm; ci[h][1] -= sm; }
        mean[a] = __shfl_sync(0xffffffffu, sm, 0) * (1.f / (16.f * 1.1328125f));
        float q = 0.f, q2 = 0.f;
#pragma unroll
        for (int i = 0; i < 4; i++) { q = fmaf(cr[0][i], cr[0][i], q); q2 = fmaf(cr[1][i], cr[1][i], q2); q = fmaf(ci[0][i], ci[0][i], q); q2 = fmaf(ci[1][i], ci[1][i], q2); }
        q += q2;
#pragma unroll
        for (int m = 1; m < 32; m <<= 1) q += __shfl_xor_sync(0xffffffffu, q, m);
        float r = rsqrtf(q * (1.f / (512.f * 16.f * ALPHA * ALPHA)) + 1e-5f) * 4.76837158203125e-7f;
        fft_s2(K, cr, ci, o);
#pragma unroll
        for (int j = 0; j < 4; j++)
          sts64(zb + ((a * 8 + warp) * ZROW + zphys(16 * t + 64 * j) + 2 * g) * 4, pk(o[j][0] * r, o[j][1] * r), pk(o[j][2] * r, o[j][3] * r));
      }
      wbar();
      uint4* tp = g_T1 + (size_t)(g * 16 + warp) * 1024 + b * 8;
#pragma unroll
      for (int nt = 0; nt < 2; nt++) {
        const int k = 16 * warp + 8 * nt + g, km = k == 0 ? 128 : 256 - k;
        uint32_t lo[4], hi[4];
#pragma unroll
        for (int a = 0; a < 2; a++) {
          const uint32_t rb = zb + (a * 8 + t) * ZROW * 4;
          float A[4], S[4], D[4];
          const uint32_t m0 = lds32(rb + zphys(km) * 4), m1 = lds32(rb + (4 * ZROW + zphys(km)) * 4);
          mma0(A, a8[a], lds32(rb + zphys(k) * 4), lds32(rb + (4 * ZROW + zphys(k)) * 4));
          mmac(S, A, a8c[a], m0, m1);
          mmac(D, A, a8n[a], m0, m1);
#pragma unroll
          for (int e = 0; e < 2; e++) {
            const float c = vc[2 * nt + e], s = vs[2 * nt + e];
            float lr = fmaf(D[2 + e], s, fmaf(D[e], c, S[e])), li = fmaf(-D[e], s, fmaf(D[2 + e], c, S[2 + e]));
            float hr = fmaf(2.f, S[e], -lr), hii = fmaf(2.f, S[2 + e], -li);
            if (nt == 0 && e == 0) {
              const bool sp = warp == 0 && t == 0;
              lr = sp ? S[0] - D[0] : lr; li = sp ? S[2] - D[2] : li;
              hr = sp ? 2.f * (A[0] - A[2]) : hr; hii = sp ? 2.f * (A[0] + A[2]) : hii;
            }
            lo[2 * a + e] = pk(lr, li); hi[2 * a + e] = pk(hr, hii);
          }
        }
        const int w = (t + 4 * nt) ^ key;
        tp[w] = make_uint4((lo[0] & ~1u) | tag, lo[1], lo[2], lo[3]);
        tp[8 * 1024 + w] = make_uint4((hi[0] & ~1u) | tag, hi[1], hi[2], hi[3]);
      }
      wbar();
      STAMP(1);
      if (warp == 0) cnt_arrive(0, lane);
    }
    {
      const uint32_t off = (8 * t + g) * 128 + ((warp ^ (2 * t + (g & 1))) << 4);
      asm volatile("barrier.cluster.wait.aligned;" ::: "memory");
      mbar_wait(mb + MB_FILT * 8, 0);
      if (tid == 0) cnt_wait<false>(0, rep, base + NCTA);
      wbar();
#pragma unroll
      for (int j = 0; j < 4; j++)
        asm volatile("cp.async.cg.shared.global [%0], [%1], 16;" :: "r"(zb + j * 4096 + tid * 16), "l"(g_T1 + (size_t)b * 1024 + j * 256 + tid) : "memory");
      STAMP(2);
      uint32_t in[2][4][2], fw[2][4][2];
#pragma unroll
      for (int j = 0; j < 4; j++) {
        uint4 v = lds128(sb + FILT_OFF + off + j * 4096);
        fw[0][j][0] = v.x; fw[1][j][0] = v.y; fw[0][j][1] = v.z; fw[1][j][1] = v.w;
      }
      asm volatile("cp.async.wait_all;" ::: "memory");
      wbar();
      STAMP(3);
      uint4 iv[4];
#pragma unroll
      for (int j = 0; j < 4; j++) iv[j] = lds128(zb + off + j * 4096);
      if (((iv[0].x ^ tag) | (iv[1].x ^ tag) | (iv[2].x ^ tag) | (iv[3].x ^ tag)) & 1) {
#pragma unroll
        for (int j = 0; j < 4; j++) tag_check(iv[j], g_T1 + (size_t)b * 1024 + j * 256 + (off >> 4), tag);
      }
      __syncwarp();
#pragma unroll
      for (int j = 0; j < 4; j++) { in[0][j][0] = iv[j].x; in[1][j][0] = iv[j].y; in[0][j][1] = iv[j].z; in[1][j][1] = iv[j].w; }
#pragma unroll
      for (int sg = 0; sg < 2; sg++) {
        float cr[2][4], ci[2][4], o[4][4];
        fft_s1(K, in[sg], cr, ci);
        fft_s2(K, cr, ci, o);
#pragma unroll
        for (int j = 0; j < 4; j++)
#pragma unroll
          for (int h = 0; h < 2; h++) {
            float fr = blo(fw[sg][j][h]), fi = bhi(fw[sg][j][h]), xr = o[j][2 * h], xi = o[j][2 * h + 1];
            in[sg][j][h] = pk(xr * fi + xi * fr, xr * fr - xi * fi);
          }
        fft_s1(K, in[sg], cr, ci);
        fft_s2(K, cr, ci, o);
#pragma unroll
        for (int j = 0; j < 4; j++) { in[sg][j][0] = pk(o[j][0], o[j][1]); in[sg][j][1] = pk(o[j][2], o[j][3]); }
      }
#pragma unroll
      for (int j = 0; j < 4; j++) sts128(zb + off + j * 4096, make_uint4((in[0][j][0] & ~1u) | tag, in[1][j][0], in[0][j][1], in[1][j][1]));
      wbar();
#pragma unroll
      for (int j = 0; j < 4; j++) g_T2[(size_t)b * 1024 + j * 256 + tid] = lds128(zb + j * 4096 + tid * 16);
      wbar();
      STAMP(4);
      if (warp == 0) cnt_arrive(1, lane);
    }
    {
      uint32_t a8[2][4], a8n[2][4]; float vc[4], vs[4];
#pragma unroll
      for (int a = 0; a < 2; a++)
#pragma unroll
        for (int u = 0; u < 4; u++) {
          float c, s; cs<2048>((t + 4 * (u >> 1)) * (256 * g + 2 * b + a), c, s);
          a8[a][u] = u & 1 ? pk(-s, c) : pk(c, s);
          a8n[a][u] = pin(a8[a][u] ^ NEG);
        }
#pragma unroll
      for (int i = 0; i < 4; i++) { cs<512>(16 * warp + 4 * t + i + 128, vc[i], vs[i]); vc[i] = pinf(vc[i]); vs[i] = pinf(vs[i]); }
      if (tid == 0) cnt_wait<false>(1, rep, base + NCTA);
      wbar();
      STAMP(5);
      const uint4* tp = g_T2 + (size_t)(t * 16 + warp) * 1024 + b * 8 + (g ^ key);
      uint4 L0 = ldcg128(tp), L1 = ldcg128(tp + 64 * 1024), H0 = ldcg128(tp + 8 * 1024), H1 = ldcg128(tp + 72 * 1024);
      if (((L0.x ^ tag) | (L1.x ^ tag) | (H0.x ^ tag) | (H1.x ^ tag)) & 1) {
        tag_check(L0, tp, tag); tag_check(L1, tp + 64 * 1024, tag); tag_check(H0, tp + 8 * 1024, tag); tag_check(H1, tp + 72 * 1024, tag);
      }
      __syncwarp();
      const uint32_t l0[4] = {L0.x, L0.y, L0.z, L0.w}, l1[4] = {L1.x, L1.y, L1.z, L1.w}, h0[4] = {H0.x, H0.y, H0.z, H0.w}, h1[4] = {H1.x, H1.y, H1.z, H1.w};
#pragma unroll
      for (int a = 0; a < 2; a++) {
        uint32_t zf[4], zm[4];
#pragma unroll
        for (int sg = 0; sg < 2; sg++) {
          float A[4], S[4], D[4];
          mma0(A, a8[a], l0[2 * a + sg], l1[2 * a + sg]);
          mmac(S, A, a8[a], h0[2 * a + sg], h1[2 * a + sg]);
          mmac(D, A, a8n[a], h0[2 * a + sg], h1[2 * a + sg]);
#pragma unroll
          for (int e = 0; e < 2; e++) {
            const int i = 2 * e + sg;
            float fr = fmaf(-D[e], vs[i], fmaf(D[2 + e], vc[i], S[2 + e])), fi = fmaf(D[2 + e], vs[i], fmaf(D[e], vc[i], S[e]));
            float mr = fmaf(2.f, S[2 + e], -fr), mi = fmaf(-2.f, S[e], fi);
            if (i == 0) {
              const bool sp = warp == 0 && t == 0;
              fr = sp ? S[2] - A[2] : fr; fi = sp ? A[2] - S[2] : fi;
              mr = sp ? 2.f * A[2] : mr; mi = sp ? -2.f * A[0] : mi;
            }
            zf[i] = pk(fi, fr); zm[i] = pk(mi, mr);
          }
        }
        const uint32_t rb = zb + (a * 8 + g) * ZROW * 4;
        const int k0 = 16 * warp + 4 * t;
        sts128(rb + zphys(k0) * 4, make_uint4(zf[0], zf[1], zf[2], zf[3]));
        sts32(rb + zphys(k0 == 0 ? 128 : 256 - k0) * 4, zm[0]);
        sts32(rb + zphys(255 - k0) * 4, zm[1]);
        sts32(rb + zphys(254 - k0) * 4, zm[2]);
        sts32(rb + zphys(253 - k0) * 4, zm[3]);
      }
      wbar();
#pragma unroll
      for (int a = 0; a < 2; a++) {
        uint32_t in[4][2];
#pragma unroll
        for (int j = 0; j < 4; j++) { uint2 v = lds64(zb + ((a * 8 + warp) * ZROW + zphys(16 * t + 64 * j) + 2 * g) * 4); in[j][0] = v.x; in[j][1] = v.y; }
        float cr[2][4], ci[2][4], o[4][4];
        fft_s1(K, in, cr, ci);
        fft_s2(K, cr, ci, o);
        float s1 = 0.f, s2 = 0.f;
        uint2* hp = (uint2*)g_h + (size_t)(256 * warp + 2 * b + a) * 128 + 8 * t + g;
#pragma unroll
        for (int j = 0; j < 4; j++) {
          uint32_t hw[2];
#pragma unroll
          for (int h = 0; h < 2; h++) {
            asm("add.rn.bf16x2 %0, %1, %2;" : "=r"(hw[h]) : "r"(xw[a][j][h]), "r"(pk(o[j][2 * h + 1], o[j][2 * h])));
            float u0 = blo(hw[h]) - mean[a], u1 = bhi(hw[h]) - mean[a];
            o[j][2 * h] = u0; o[j][2 * h + 1] = u1;
            s1 = fmaf(u0, u0, s1); s2 = fmaf(u1, u1, s2);
          }
          hp[32 * j] = make_uint2(hw[0], hw[1]);
        }
        s2 += s1;
#pragma unroll
        for (int m = 1; m < 32; m <<= 1) s2 += __shfl_xor_sync(0xffffffffu, s2, m);
        const float var = s2 * (1.f / 512.f), r1 = rsqrtf(var + 1e-5f);
        const float r = r1 * rsqrtf(var * r1 * r1 + 1e-5f);
        char* np = (char*)g_Hn + (size_t)b * 4096 + (t >> 1) * 2048 + a * 1024 + warp * 128 + ((((t & 1) * 4 + (g >> 1)) ^ warp ^ (b >> 6)) << 4) + (g & 1) * 8;
#pragma unroll
        for (int j = 0; j < 4; j++)
          *(uint2*)(np + (size_t)j * 128 * 4096) = make_uint2(pk(o[j][0] * r, o[j][1] * r), pk(o[j][2] * r, o[j][3] * r));
      }
      asm volatile("fence.proxy.async.shared::cta;" ::: "memory");
      wbar();
      STAMP(6);
      if (warp == 0) { fence_gpu(); cnt_arrive(2 + (b >> 6), lane); }
      if (tid == 32) { sts32(sb + BASE_OFF, base); mbar_arrive(mb + MB_P3DONE * 8); }
    }
    const int wg = warp >> 2;
    const uint32_t peer_sb = mapa(sb, rank ^ 1);
    {
      float acc[44];
#pragma unroll
      for (int j = 0; j < 11; j++) {
        const uint32_t bw = __ldg(b1 + min(11 * ot + j, 171) * 4 + t);
        acc[4 * j] = blo(bw); acc[4 * j + 1] = bhi(bw); acc[4 * j + 2] = 0.f; acc[4 * j + 3] = 0.f;
      }
      const uint32_t da0 = desc_lo(sb + RING_OFF + wg * 2048, 0);
      uint32_t da = da0, db = desc_lo(sb, 1408), bar = mb;
      mbar_wait(mb + MB_W1 * 8, 0);
#pragma unroll 1
      for (int i = 0; i < 32; i++) {
        mbar_wait(bar + MB_FULL * 8, 0);
        if (i == 0) STAMP(7);
        asm volatile("wgmma.fence.sync.aligned;" ::: "memory");
        wgmma_n88_ss<1, 1, HI_SW128, HI_NOSW>(acc, da, db, 1);
        wgmma_n88_ss<1, 1, HI_SW128, HI_NOSW>(acc, da + 256, db + 176, 1);
        asm volatile("wgmma.commit_group.sync.aligned;" ::: "memory");
        da = da == da0 + 5 * 512 ? da0 : da + 512; db += 352;
        asm volatile("wgmma.wait_group.sync.aligned 1;" ::: "memory");
        if ((tid & 127) == 0) { if (i > 0) mbar_arrive(bar + (MB_EMPTY - 1) * 8); if (i == 4) mbar_arrive_cluster(peer_sb + BAR_OFF + MB_PEER1 * 8); }
        bar += 8;
      }
      asm volatile("wgmma.wait_group.sync.aligned 0;" ::: "memory");
#pragma unroll
      for (int i = 0; i < 44; i++) asm volatile("" : "+f"(acc[i]) :: "memory");
      if ((tid & 127) == 0) mbar_arrive(mb + (MB_EMPTY + 31) * 8);
      STAMP(8);
      mbar_wait_cluster(mb + MB_PEER1 * 8, 0);
#pragma unroll
      for (int j = 0; j < 5; j++) st_async4(peer_sb + j * 4096 + tid * 16, acc[8 * j + 2], acc[8 * j + 3], acc[8 * j + 6], acc[8 * j + 7], peer_sb + BAR_OFF + MB_X1 * 8);
      st_async2(peer_sb + 5 * 4096 + tid * 8, acc[42], acc[43], peer_sb + BAR_OFF + MB_X1 * 8);
      const int uo = (4 * (warp >> 1) + (g >> 1)) * 32 + (2 * (2 * (warp & 1) + rank) + (g & 1)) * 4 + t;
      uint32_t* const ub = (uint32_t*)g_U + ((size_t)dt * 172 + 11 * ot) * 512;
      uint32_t *upa = ub + (uo ^ (ot >= 8 ? 256 : 0)), *upb = ub + (uo ^ (ot >= 7 ? 256 : 0));
      mbar_wait_cluster(mb + MB_X1 * 8, 0);
#pragma unroll
      for (int j = 0; j < 5; j++) {
        uint4 v = lds128(sb + j * 4096 + tid * 16);
        acc[8 * j] += __uint_as_float(v.x); acc[8 * j + 1] += __uint_as_float(v.y); acc[8 * j + 4] += __uint_as_float(v.z); acc[8 * j + 5] += __uint_as_float(v.w);
      }
      { uint2 v = lds64(sb + 5 * 4096 + tid * 8); acc[40] += __uint_as_float(v.x); acc[41] += __uint_as_float(v.y); }
#pragma unroll
      for (int j = 0; j < 11; j++) {
        uint32_t v = pk(gelu(acc[4 * j]), gelu(acc[4 * j + 1]));
        if (j < 7 || ot < 15) (j < 9 ? upa : upb)[j * 512] = v;
      }
      asm volatile("fence.proxy.async.shared::cta;" ::: "memory");
      wbar();
      STAMP(9);
      if (warp == 0) { fence_gpu(); cnt_arrive(4 + dt, lane); }
      if (tid == 32) mbar_arrive(mb + MB_X1DONE * 8);
    }
    {
      const int srow = 128 * ot + 16 * warp + g, oo = srow * 64 + dt * 16 + 8 * rank + t;
      float acc[64];
      const uint32_t da0 = desc_lo(sb + wg * 4096, 0), db0 = desc_lo(sb + RING_OFF, 2048);
      uint32_t da = da0 + 3 * 512, db = db0 + (32 % NST) * 512, bar = mb;
#pragma unroll
      for (int u = 0; u < 2; u++) {
        const float bias2 = __uint_as_float((uint32_t)__ldg(b2 + srow + 8 * u) << 16);
#pragma unroll
        for (int jj = 0; jj < 2; jj++) {
          const uint4 v = ldcg128(g_h + oo + u * 512 + 4 * jj);
          const uint32_t w[4] = {v.x, v.y, v.z, v.w};
#pragma unroll
          for (int j = 0; j < 4; j++) { acc[16 * jj + 4 * j + 2 * u] = blo(w[j]) + bias2; acc[16 * jj + 4 * j + 2 * u + 1] = bhi(w[j]) + bias2; }
        }
      }
#pragma unroll
      for (int j = 32; j < 64; j++) acc[j] = 0.f;
#pragma unroll 1
      for (int i = 0; i < 21; i++) {
        mbar_wait(bar + MB_W2 * 8, 0);
        mbar_wait(bar + (MB_FULL + 32) * 8, 0);
        if (i == 0) STAMP(10);
        asm volatile("wgmma.fence.sync.aligned;" ::: "memory");
        wgmma_n128_ss<1, 0, HI_SW128, HI_NOSW>(acc, da, db, 1);
        wgmma_n128_ss<1, 0, HI_SW128, HI_NOSW>(acc, da + 128, db + 256, 1);
        asm volatile("wgmma.commit_group.sync.aligned;" ::: "memory");
        da = i == 18 ? da0 : da + 512; db = db == db0 + 5 * 512 ? db0 : db + 512;
        asm volatile("wgmma.wait_group.sync.aligned 1;" ::: "memory");
        if ((tid & 127) == 0) { if (i > 0) mbar_arrive(bar + (MB_EMPTY + 31) * 8); if (i == 4) mbar_arrive_cluster(peer_sb + BAR_OFF + MB_PEER2 * 8); }
        bar += 8;
      }
      mbar_wait(bar + MB_W2 * 8, 0);
      mbar_wait(bar + (MB_FULL + 32) * 8, 0);
      asm volatile("wgmma.fence.sync.aligned;" ::: "memory");
      wgmma_n128_ss<1, 0, HI_SW128, HI_NOSW>(acc, da, db, 1);
      asm volatile("wgmma.commit_group.sync.aligned;" ::: "memory");
      asm volatile("wgmma.wait_group.sync.aligned 0;" ::: "memory");
#pragma unroll
      for (int i = 0; i < 64; i++) asm volatile("" : "+f"(acc[i]) :: "memory");
      STAMP(11);
      mbar_wait_cluster(mb + MB_PEER2 * 8, 0);
#pragma unroll
      for (int j = 0; j < 8; j++)
        st_async4(peer_sb + 3 * 8192 + j * 4096 + tid * 16, acc[32 + 4 * j], acc[33 + 4 * j], acc[34 + 4 * j], acc[35 + 4 * j], peer_sb + BAR_OFF + MB_X2 * 8);
      mbar_wait_cluster(mb + MB_X2 * 8, 0);
#pragma unroll
      for (int jj = 0; jj < 2; jj++) {
        uint32_t w[2][4];
#pragma unroll
        for (int j = 0; j < 4; j++) {
          const uint4 v = lds128(sb + 3 * 8192 + (4 * jj + j) * 4096 + tid * 16);
          w[0][j] = pk(acc[16 * jj + 4 * j] + __uint_as_float(v.x), acc[16 * jj + 4 * j + 1] + __uint_as_float(v.y));
          w[1][j] = pk(acc[16 * jj + 4 * j + 2] + __uint_as_float(v.z), acc[16 * jj + 4 * j + 3] + __uint_as_float(v.w));
        }
        out[oo + 4 * jj] = make_uint4(w[0][0], w[0][1], w[0][2], w[0][3]);
        out[oo + 512 + 4 * jj] = make_uint4(w[1][0], w[1][1], w[1][2], w[1][3]);
      }
      STAMP(12);
    }
  } else {
    const int pw = warp - 8;
    if (pw < 3 && elect()) {
#pragma unroll
      for (int i = 0; i < 57; i++) mbar_init(mb + (pw * 57 + i) * 8, pw == 2 ? 2 : 1);
      if (pw == 1) { mbar_expect(mb + MB_X1 * 8, 22528); mbar_expect(mb + MB_X2 * 8, 32768); }
      asm volatile("fence.mbarrier_init.release.cluster;" ::: "memory");
    }
    __syncwarp();
    STAMP(0);
    asm volatile("bar.sync 2, 128;" ::: "memory");
    asm volatile("barrier.cluster.arrive.relaxed.aligned;" ::: "memory");
    auto w1_issue = [&](int i) {
      if (elect()) { mbar_expect(mb + (MB_W1T + i) * 8, 5632); tma3d(sb + i * 5632, &tmW1, 88 * ot, 0, 128 * rank + 4 * i, mb + (MB_W1T + i) * 8); }
      __syncwarp();
    };
    if (!W1_LATE && pw < W1_WARPS) for (int i = 0; i < W1_DEPTH; i++) w1_issue(pw + W1_WARPS * i);
    {
      const int j1 = b >> 4, q = b & 15, slot = lane & 15, h = lane >> 4;
      const bool hi = q >= 8;
      const int k = 16 * (q & 7) + slot, col = hi ? 256 - k : (k == 0 ? 128 : k);
      const int j0 = j1 + 8 * h + 512 * pw, o0 = (hi ? 2048 - 31 * 16 - j0 : j0) * DF + col, o31 = hi && j0 == 0 ? o0 - 2048 * DF : o0;
      uint32_t vr[32], vi[32];
#pragma unroll
      for (int n = 0; n < 32; n++) { vr[n] = __ldg(wr + (n == 31 ? o31 : o0) + n * 16 * DF); vi[n] = __ldg(wi + (n == 31 ? o31 : o0) + n * 16 * DF); }
      const uint32_t f0 = sb + FILT_OFF + pw * 4096 + (hi ? 31 * 128 : 0) + h * 8 + (slot & 1) * 4, sw = ((slot >> 1) ^ (hi ? 7 : 0)) << 4;
      const int st = hi ? -128 : 128;
#pragma unroll
      for (int n = 0; n < 32; n++)
        sts32(f0 + n * st + (sw ^ ((((n >> 3) & 3) * 2 + (n & 1)) << 4)), __byte_perm(vr[n], vi[n], 0x5410) ^ (hi ? 0x80000000u : 0u));
      asm volatile("bar.sync 2, 128;" ::: "memory");
      if (threadIdx.x == 352) mbar_arrive(mb + MB_FILT * 8);
    }
    if (PF_W1 && elect()) asm volatile("cp.async.bulk.prefetch.L2.global [%0], %1;" :: "l"(w1 + (size_t)(b * 4 + pw) * 11008), "r"(11008) : "memory");
    __syncwarp();
    STAMP(1);
    {
      if (W1_LATE && pw < W1_WARPS) for (int i = 0; i < W1_DEPTH; i++) w1_issue(pw + W1_WARPS * i);
      const uint32_t rd = ((lane & 7) * 11 + (lane >> 3)) * 16, wr = lane * 16;
#pragma unroll 1
      for (int box = pw < W1_WARPS ? pw : 32; box < 32; box += W1_WARPS) {
        mbar_wait(mb + (MB_W1T + box) * 8, 0);
        if (box + W1_WARPS * W1_DEPTH < 32) w1_issue(box + W1_WARPS * W1_DEPTH);
        const uint32_t p = sb + box * 5632;
        uint4 v[4][3];
#pragma unroll
        for (int n = 0; n < 4; n++) { v[n][0] = lds128(p + n * 1408 + rd); v[n][1] = lds128(p + n * 1408 + rd + 64); if (lane < 24) v[n][2] = lds128(p + n * 1408 + rd + 128); }
        __syncwarp();
#pragma unroll
        for (int n = 0; n < 4; n++) { sts128(p + n * 1408 + wr, v[n][0]); sts128(p + n * 1408 + wr + 512, v[n][1]); if (lane < 24) sts128(p + n * 1408 + wr + 1024, v[n][2]); }
      }
      if (lane == 0) asm volatile("cp.async.bulk.prefetch.L2.global [%0], %1;" :: "l"(w2 + (size_t)(b * 4 + pw) * 11008), "r"(11008) : "memory");
      asm volatile("fence.proxy.async.shared::cta;" ::: "memory");
      asm volatile("bar.sync 2, 128;" ::: "memory");
      if (threadIdx.x == 352) mbar_arrive(mb + MB_W1 * 8);
    }
    STAMP(2);
    asm volatile("barrier.cluster.wait.aligned;" ::: "memory");
    if (pw == 3) {
#pragma unroll 1
      for (int n = 0; n < 22; n++) {
        if (n < W2_PRE) mbar_wait(mb + (MB_EMPTY + min(31, max(((n + 4) * 16 + 10) / 11 - 1, W2_START + n * W2_NUM / W2_DEN))) * 8, 0);
        else { mbar_wait(mb + MB_X1DONE * 8, 0); if (W2_PACE) mbar_wait(mb + (MB_FULL + 32 - W2_PRE + n) * 8, 0); }
        if (elect()) { mbar_expect(mb + (MB_W2 + n) * 8, 8192); tma3d(sb + (n < 19 ? n + 3 : n - 19) * 8192, &tmW2, 0, 688 * rank + 32 * n, 2 * ot, mb + (MB_W2 + n) * 8); }
      }
    } else {
      int i = pw;
      uint32_t dst = sb + RING_OFF + pw * 8192;
      const uint32_t dsum = 2 * dst + 3 * 8192;
      const char* src = (const char*)g_Hn + ((size_t)dt * 128 + 64 * rank) * 4096;
#pragma unroll 1
      for (int gm = 0; gm < 2; gm++) {
        if (pw == 0) {
          mbar_wait(mb + (gm ? MB_X1DONE : MB_P3DONE) * 8, 0);
          STAMP(3 + 2 * gm);
          if (lane == 0) cnt_wait<true>(gm ? 4 + dt : 2 + rank, ot & (NREP - 1), ((lds32(sb + BASE_OFF) >> 1) + 64) >> gm);
        }
        asm volatile("bar.sync 2, 96;" ::: "memory");
        STAMP(4 + 2 * gm);
        asm volatile("fence.proxy.async.global;" ::: "memory");
#pragma unroll 1
        for (; i < (gm ? 54 : 32); i += 3) {
          if (i >= NST) mbar_wait(mb + (MB_EMPTY - NST + i) * 8, 0);
          if (elect()) {
            const int bytes = i < 53 ? 8192 : 4096;
            mbar_expect(mb + (MB_FULL + i) * 8, bytes); bulk_ld(dst, src + i * 8192, bytes, mb + (MB_FULL + i) * 8);
          }
          dst = dsum - dst;
        }
        src = (const char*)g_U + ((size_t)dt * 172 + 86 * rank) * 2048 - 32 * 8192;
      }
      STAMP(7);
    }
  }
}

typedef CUresult (*EncodeFn)(CUtensorMap*, CUtensorMapDataType, cuuint32_t, void*, const cuuint64_t*, const cuuint64_t*, const cuuint32_t*,
                             const cuuint32_t*, CUtensorMapInterleave, CUtensorMapSwizzle, CUtensorMapL2promotion, CUtensorMapFloatOOBfill);

extern "C" void kernel_launch(void* const* d_in, const int* in_sizes, int n_in, void* d_out, int out_size) {
  static EncodeFn enc = nullptr;
  if (!enc) {
    void* fn = nullptr; cudaDriverEntryPointQueryResult st;
    cudaGetDriverEntryPoint("cuTensorMapEncodeTiled", &fn, cudaEnableDefault, &st);
    enc = (EncodeFn)fn;
    cudaFuncSetAttribute(fused_kernel, cudaFuncAttributeMaxDynamicSharedMemorySize, SMEM_BYTES);
  }
  CUtensorMap tm, tm1;
  {
    cuuint64_t dims[3] = {(cuuint64_t)F_, 8, 256}, strides[2] = {(cuuint64_t)256 * F_ * 2, F_ * 2};
    cuuint32_t box[3] = {88, 8, 4}, es[3] = {1, 1, 1};
    enc(&tm1, CU_TENSOR_MAP_DATA_TYPE_BFLOAT16, 3, d_in[4], dims, strides, box, es, CU_TENSOR_MAP_INTERLEAVE_NONE, CU_TENSOR_MAP_SWIZZLE_NONE,
        W1_PROMO, CU_TENSOR_MAP_FLOAT_OOB_FILL_NONE);
  }
  {
    cuuint64_t dims[3] = {64, (cuuint64_t)F_, S_ / 64}, strides[2] = {S_ * 2, 128};
    cuuint32_t box[3] = {64, 32, 2}, es[3] = {1, 1, 1};
    enc(&tm, CU_TENSOR_MAP_DATA_TYPE_BFLOAT16, 3, d_in[6], dims, strides, box, es, CU_TENSOR_MAP_INTERLEAVE_NONE, CU_TENSOR_MAP_SWIZZLE_128B,
        CU_TENSOR_MAP_L2_PROMOTION_L2_256B, CU_TENSOR_MAP_FLOAT_OOB_FILL_NONE);
  }
  fused_kernel<<<NCTA, 384, SMEM_BYTES, cudaStreamPerThread>>>(tm1, tm, (const uint2*)d_in[0], (const unsigned short*)d_in[1], (const unsigned short*)d_in[2],
                                          (const char*)d_in[4], (const uint32_t*)d_in[5], (const char*)d_in[6], (const unsigned short*)d_in[7], (uint4*)d_out);
}
```

```cpp
#include <cuda_runtime.h>
#include <cuda.h>
#include <cuda_bf16.h>
#include <stdint.h>
#define W1_LATE 1
#define W1_PROMO CU_TENSOR_MAP_L2_PROMOTION_NONE
#define W2_NUM 1
#define W2_DEN 1
#define PF_W1 0
#define W1_DEPTH 1
#define W1_WARPS 4
#define W2_PRE 12
#define W2_PACE 1
#define FILT_LATE 1
#define W1_END 32
template<int TA, int TB, uint32_t HA, uint32_t HB> __device__ __forceinline__ void wgmma_n88_ss(float (&d)[44], uint32_t da, uint32_t db, int sd) {
  asm volatile("{\n.reg .pred p;\n.reg .b64 da, db;\nsetp.ne.b32 p, %46, 0;\nmov.b64 da, {%44, %49};\nmov.b64 db, {%45, %50};\n"
    "wgmma.mma_async.sync.aligned.m64n88k16.f32.bf16.bf16 {%0, %1, %2, %3, %4, %5, %6, %7, %8, %9, %10, %11, %12, %13, %14, %15, %16, %17, %18, %19, %20, %21, %22, %23, %24, %25, %26, %27, %28, %29, %30, %31, %32, %33, %34, %35, %36, %37, %38, %39, %40, %41, %42, %43}, da, db, p, 1, 1, %47, %48;\n}\n"
    : "+f"(d[0]), "+f"(d[1]), "+f"(d[2]), "+f"(d[3]), "+f"(d[4]), "+f"(d[5]), "+f"(d[6]), "+f"(d[7]), "+f"(d[8]), "+f"(d[9]), "+f"(d[10]), "+f"(d[11]), "+f"(d[12]), "+f"(d[13]), "+f"(d[14]), "+f"(d[15]), "+f"(d[16]), "+f"(d[17]), "+f"(d[18]), "+f"(d[19]), "+f"(d[20]), "+f"(d[21]), "+f"(d[22]), "+f"(d[23]), "+f"(d[24]), "+f"(d[25]), "+f"(d[26]), "+f"(d[27]), "+f"(d[28]), "+f"(d[29]), "+f"(d[30]), "+f"(d[31]), "+f"(d[32]), "+f"(d[33]), "+f"(d[34]), "+f"(d[35]), "+f"(d[36]), "+f"(d[37]), "+f"(d[38]), "+f"(d[39]), "+f"(d[40]), "+f"(d[41]), "+f"(d[42]), "+f"(d[43]) : "r"(da), "r"(db), "r"(sd), "n"(TA), "n"(TB), "n"(HA), "n"(HB));
}
template<int TA, int TB, uint32_t HA, uint32_t HB> __device__ __forceinline__ void wgmma_n128_ss(float (&d)[64], uint32_t da, uint32_t db, int sd) {
  asm volatile("{\n.reg .pred p;\n.reg .b64 da, db;\nsetp.ne.b32 p, %66, 0;\nmov.b64 da, {%64, %69};\nmov.b64 db, {%65, %70};\n"
    "wgmma.mma_async.sync.aligned.m64n128k16.f32.bf16.bf16 {%0, %1, %2, %3, %4, %5, %6, %7, %8, %9, %10, %11, %12, %13, %14, %15, %16, %17, %18, %19, %20, %21, %22, %23, %24, %25, %26, %27, %28, %29, %30, %31, %32, %33, %34, %35, %36, %37, %38, %39, %40, %41, %42, %43, %44, %45, %46, %47, %48, %49, %50, %51, %52, %53, %54, %55, %56, %57, %58, %59, %60, %61, %62, %63}, da, db, p, 1, 1, %67, %68;\n}\n"
    : "+f"(d[0]), "+f"(d[1]), "+f"(d[2]), "+f"(d[3]), "+f"(d[4]), "+f"(d[5]), "+f"(d[6]), "+f"(d[7]), "+f"(d[8]), "+f"(d[9]), "+f"(d[10]), "+f"(d[11]), "+f"(d[12]), "+f"(d[13]), "+f"(d[14]), "+f"(d[15]), "+f"(d[16]), "+f"(d[17]), "+f"(d[18]), "+f"(d[19]), "+f"(d[20]), "+f"(d[21]), "+f"(d[22]), "+f"(d[23]), "+f"(d[24]), "+f"(d[25]), "+f"(d[26]), "+f"(d[27]), "+f"(d[28]), "+f"(d[29]), "+f"(d[30]), "+f"(d[31]), "+f"(d[32]), "+f"(d[33]), "+f"(d[34]), "+f"(d[35]), "+f"(d[36]), "+f"(d[37]), "+f"(d[38]), "+f"(d[39]), "+f"(d[40]), "+f"(d[41]), "+f"(d[42]), "+f"(d[43]), "+f"(d[44]), "+f"(d[45]), "+f"(d[46]), "+f"(d[47]), "+f"(d[48]), "+f"(d[49]), "+f"(d[50]), "+f"(d[51]), "+f"(d[52]), "+f"(d[53]), "+f"(d[54]), "+f"(d[55]), "+f"(d[56]), "+f"(d[57]), "+f"(d[58]), "+f"(d[59]), "+f"(d[60]), "+f"(d[61]), "+f"(d[62]), "+f"(d[63]) : "r"(da), "r"(db), "r"(sd), "n"(TA), "n"(TB), "n"(HA), "n"(HB));
}

constexpr int S_ = 2048, D_ = 512, F_ = 1376, DF = 257;
constexpr int NCTA = 128;
constexpr int W_BYTES = 180224;
constexpr int RING_OFF = W_BYTES;
constexpr int NST = 6;
constexpr int BAR_OFF = RING_OFF + NST * 8192;
constexpr int SMEM_BYTES = BAR_OFF + 1536;
constexpr int FILT_OFF = RING_OFF;
constexpr int XCH_OFF = RING_OFF + 16384;
constexpr int ZROW = 328;
constexpr int MB_FULL = 0, MB_W2 = 54, MB_W1T = 76, MB_X1 = 108, MB_X2 = 109, MB_X1DONE = 110, MB_P3DONE = 111, MB_FILT = 112, MB_W1 = 113,
              MB_EMPTY = 114, MB_PEER1 = 168, MB_PEER2 = 169, MB_N = 171;
constexpr int BASE_OFF = BAR_OFF + MB_N * 8;
#define W2_START 24

__device__ uint4 g_T1[NCTA * 1024];
__device__ uint4 g_T2[NCTA * 1024];
__device__ float2 g_st[S_];
__device__ uint4 g_Hn[4 * 128 * 256];
__device__ uint4 g_U[4 * 172 * 128];
__device__ unsigned g_cnt[8 * 4 * 64];
#define STAMP(i)

__device__ __forceinline__ void mbar_init(uint32_t b, int c) { asm volatile("mbarrier.init.shared::cta.b64 [%0], %1;" :: "r"(b), "r"(c) : "memory"); }
__device__ __forceinline__ void mbar_expect(uint32_t b, int bytes) { asm volatile("mbarrier.arrive.expect_tx.shared::cta.b64 _, [%0], %1;" :: "r"(b), "r"(bytes) : "memory"); }
__device__ __forceinline__ void mbar_arrive(uint32_t b) { asm volatile("mbarrier.arrive.shared::cta.b64 _, [%0];" :: "r"(b) : "memory"); }
__device__ __forceinline__ void mbar_arrive_cluster(uint32_t remote) { asm volatile("mbarrier.arrive.relaxed.cluster.shared::cluster.b64 _, [%0];" :: "r"(remote) : "memory"); }
__device__ __forceinline__ uint32_t mapa(uint32_t a, uint32_t cta) { uint32_t r; asm("mapa.shared::cluster.u32 %0, %1, %2;" : "=r"(r) : "r"(a), "r"(cta)); return r; }
__device__ __forceinline__ void mbar_wait(uint32_t b, int ph) {
  asm volatile("{\n.reg .pred p;\n.reg .u32 n;\nmov.u32 n, 0;\nL_W:\n"
               "mbarrier.try_wait.parity.shared::cta.b64 p, [%0], %1;\n@p bra L_D;\n"
               "add.u32 n, n, 1;\nsetp.lt.u32 p, n, 4000000;\n@p bra L_W;\ntrap;\nL_D:\n}" :: "r"(b), "r"(ph) : "memory");
}
__device__ __forceinline__ void mbar_wait_cluster(uint32_t b, int ph) {
  asm volatile("{\n.reg .pred p;\n.reg .u32 n;\nmov.u32 n, 0;\nL_W:\n"
               "mbarrier.try_wait.parity.acquire.cluster.shared::cta.b64 p, [%0], %1;\n@p bra L_D;\n"
               "add.u32 n, n, 1;\nsetp.lt.u32 p, n, 4000000;\n@p bra L_W;\ntrap;\nL_D:\n}" :: "r"(b), "r"(ph) : "memory");
}
__device__ __forceinline__ void bulk_ld(uint32_t dst, const void* src, int bytes, uint32_t bar) {
  asm volatile("cp.async.bulk.shared::cluster.global.mbarrier::complete_tx::bytes [%0], [%1], %2, [%3];" :: "r"(dst), "l"(src), "r"(bytes), "r"(bar) : "memory");
}
__device__ __forceinline__ void tma3d(uint32_t dst, const CUtensorMap* tm, int c0, int c1, int c2, uint32_t bar) {
  asm volatile("cp.async.bulk.tensor.3d.shared::cluster.global.mbarrier::complete_tx::bytes [%0], [%1, {%3, %4, %5}], [%2];"
               :: "r"(dst), "l"(tm), "r"(bar), "r"(c0), "r"(c1), "r"(c2) : "memory");
}
__device__ __forceinline__ bool elect() { uint32_t p; asm volatile("{.reg .pred p; elect.sync _|p, 0xffffffff; selp.b32 %0, 1, 0, p;}" : "=r"(p)); return p; }
__device__ __forceinline__ uint32_t desc_lo(uint32_t addr, uint32_t lbo) { return ((addr & 0x3FFFF) >> 4) | ((lbo >> 4) << 16); }
constexpr uint32_t HI_SW128 = (1024 >> 4) | (1u << 30), HI_NOSW = 128 >> 4;
__device__ __forceinline__ uint32_t pk(float lo, float hi) { uint32_t r; asm("cvt.rn.bf16x2.f32 %0, %1, %2;" : "=r"(r) : "f"(hi), "f"(lo)); return r; }
__device__ __forceinline__ float blo(uint32_t w) { return __uint_as_float(w << 16); }
__device__ __forceinline__ float bhi(uint32_t w) { return __uint_as_float(w & 0xffff0000u); }
__device__ __forceinline__ void mmac(float (&d)[4], const float (&c)[4], const uint32_t (&a)[4], uint32_t b0, uint32_t b1) {
  asm("mma.sync.aligned.m16n8k16.row.col.f32.bf16.bf16.f32 {%0,%1,%2,%3}, {%4,%5,%6,%7}, {%8,%9}, {%10,%11,%12,%13};"
      : "=f"(d[0]), "=f"(d[1]), "=f"(d[2]), "=f"(d[3]) : "r"(a[0]), "r"(a[1]), "r"(a[2]), "r"(a[3]), "r"(b0), "r"(b1), "f"(c[0]), "f"(c[1]), "f"(c[2]), "f"(c[3]));
}
__device__ __forceinline__ void mma0(float (&d)[4], const uint32_t (&a)[4], uint32_t b0, uint32_t b1) { const float z[4] = {0.f, 0.f, 0.f, 0.f}; mmac(d, z, a, b0, b1); }
__device__ __forceinline__ uint32_t pin(uint32_t v) { asm volatile("shfl.sync.bfly.b32 %0, %0, 0, 31, 0xffffffff;" : "+r"(v)); return v; }
__device__ __forceinline__ float pinf(float v) { asm volatile("" : "+f"(v)); return v; }
__device__ __forceinline__ void wbar() { asm volatile("bar.sync 1, 256;" ::: "memory"); }
__device__ __forceinline__ void sts32(uint32_t a, uint32_t v) { asm volatile("st.shared.b32 [%0], %1;" :: "r"(a), "r"(v) : "memory"); }
__device__ __forceinline__ void sts64(uint32_t a, uint32_t x, uint32_t y) { asm volatile("st.shared.v2.b32 [%0], {%1,%2};" :: "r"(a), "r"(x), "r"(y) : "memory"); }
__device__ __forceinline__ void sts128(uint32_t a, uint4 v) { asm volatile("st.shared.v4.b32 [%0], {%1,%2,%3,%4};" :: "r"(a), "r"(v.x), "r"(v.y), "r"(v.z), "r"(v.w) : "memory"); }
__device__ __forceinline__ uint32_t lds32(uint32_t a) { uint32_t v; asm volatile("ld.shared.b32 %0, [%1];" : "=r"(v) : "r"(a) : "memory"); return v; }
__device__ __forceinline__ uint2 lds64(uint32_t a) { uint2 v; asm volatile("ld.shared.v2.b32 {%0,%1}, [%2];" : "=r"(v.x), "=r"(v.y) : "r"(a) : "memory"); return v; }
__device__ __forceinline__ uint4 lds128(uint32_t a) { uint4 v; asm volatile("ld.shared.v4.b32 {%0,%1,%2,%3}, [%4];" : "=r"(v.x), "=r"(v.y), "=r"(v.z), "=r"(v.w) : "r"(a) : "memory"); return v; }
__device__ __forceinline__ uint4 ldcg128(const void* p) { uint4 v; asm volatile("ld.global.cg.v4.b32 {%0,%1,%2,%3}, [%4];" : "=r"(v.x), "=r"(v.y), "=r"(v.z), "=r"(v.w) : "l"(p) : "memory"); return v; }
__device__ __forceinline__ void st_async4(uint32_t a, uint32_t x, uint32_t y, uint32_t z, uint32_t w, uint32_t bar) {
  asm volatile("st.async.weak.shared::cluster.mbarrier::complete_tx::bytes.v4.b32 [%0], {%1,%2,%3,%4}, [%5];" :: "r"(a), "r"(x), "r"(y), "r"(z), "r"(w), "r"(bar) : "memory");
}
constexpr int NREP = 4;
__device__ __forceinline__ void cnt_arrive(int i, int lane) {
  if (lane < NREP) asm volatile("red.relaxed.gpu.global.add.u32 [%0], 1;" :: "l"(&g_cnt[(i * NREP + lane) * 64]) : "memory");
}
template <bool ACQ> __device__ __forceinline__ void cnt_wait(int i, int rep, unsigned target) {
  unsigned v; int n = 0;
  do {
    if (ACQ) asm volatile("ld.acquire.gpu.global.u32 %0, [%1];" : "=r"(v) : "l"(&g_cnt[(i * NREP + rep) * 64]) : "memory");
    else asm volatile("ld.relaxed.gpu.global.u32 %0, [%1];" : "=r"(v) : "l"(&g_cnt[(i * NREP + rep) * 64]) : "memory");
    if (++n > 2000000) __trap(); } while ((int)(v - target) < 0);
}
__device__ __forceinline__ void fence_gpu() { asm volatile("fence.acq_rel.gpu;" ::: "memory"); }
__device__ __forceinline__ void tag_check(uint4& v, const uint4* p, uint32_t tag) {
  int n = 0;
  while ((v.x ^ tag) & 1) {
    asm volatile("ld.relaxed.gpu.global.v4.b32 {%0,%1,%2,%3}, [%4];" : "=r"(v.x), "=r"(v.y), "=r"(v.z), "=r"(v.w) : "l"(p) : "memory");
    if (++n > 2000000) __trap();
  }
}
template <int N> __device__ __forceinline__ void cs(int n, float& c, float& s) {
  n = ((n + N / 2) & (N - 1)) - N / 2;
  float a = (float)n * (6.283185307179586f / N);
  c = __cosf(a); s = __sinf(a);
}
constexpr float ALPHA = 1.13288f;
struct FftC { uint32_t a[4][4], b[8][2]; float tc[2][4], ts[2][4]; };
constexpr uint32_t NEG = 0x80008000u;

__device__ __forceinline__ void fft_s1(const FftC& K, const uint32_t (&in)[4][2], float (&cr)[2][4], float (&ci)[2][4]) {
#pragma unroll
  for (int h = 0; h < 2; h++) { mma0(cr[h], K.a[0], in[0][h], in[1][h]); mma0(ci[h], K.a[1], in[0][h], in[1][h]); }
#pragma unroll
  for (int h = 0; h < 2; h++) { mmac(cr[h], cr[h], K.a[2], in[2][h], in[3][h]); mmac(ci[h], ci[h], K.a[3], in[2][h], in[3][h]); }
}
__device__ __forceinline__ void fft_s2(const FftC& K, const float (&cr)[2][4], const float (&ci)[2][4], float (&o)[4][4]) {
  uint32_t a[2][4];
#pragma unroll
  for (int h = 0; h < 2; h++)
#pragma unroll
    for (int i = 0; i < 4; i++) {
      float xr = cr[i & 1][2 * h + (i >> 1)], xi = ci[i & 1][2 * h + (i >> 1)];
      a[i >> 1][2 * (i & 1) + h] = pk(xr * K.tc[h][i] + xi * K.ts[h][i], xi * K.tc[h][i] - xr * K.ts[h][i]);
    }
#pragma unroll
  for (int j = 0; j < 4; j++) mma0(o[j], a[0], K.b[j][0], K.b[j][1]);
#pragma unroll
  for (int j = 0; j < 4; j++) mmac(o[j], o[j], a[1], K.b[4 + j][0], K.b[4 + j][1]);
}
__device__ __forceinline__ int zphys(int k) { return k + 8 * (k >> 5); }
__device__ __forceinline__ float gelu(float u) {
  float z = u * (0.7978845608028654f + 0.035677408136300125f * u * u), th;
  asm("tanh.approx.f32 %0, %1;" : "=f"(th) : "f"(z));
  float hu = 0.5f * u;
  return fmaf(hu, th, hu);
}

extern "C" __global__ void __cluster_dims__(2, 1, 1) __launch_bounds__(384, 1)
fused_kernel(const __grid_constant__ CUtensorMap tmW1, const __grid_constant__ CUtensorMap tmW2, const uint2* __restrict__ x, const unsigned short* __restrict__ wr,
             const unsigned short* __restrict__ wi, const char* __restrict__ w1, const uint32_t* __restrict__ b1,
             const char* __restrict__ w2, const unsigned short* __restrict__ b2, uint4* __restrict__ out) {
  extern __shared__ __align__(1024) char smem[];
  const uint32_t sb = (uint32_t)__cvta_generic_to_shared(smem);
  const uint32_t mb = sb + BAR_OFF;
  const int b = blockIdx.x, rank = b & 1, pr = b >> 1, dt = pr & 3, ot = pr >> 2;
  const int warp = __shfl_sync(0xffffffffu, threadIdx.x >> 5, 0), lane = threadIdx.x & 31;
  const int g = lane >> 2, t = lane & 3;

  if (warp < 8) {
    const int tid = threadIdx.x;
    uint32_t xw[2][4][2];
    {
      const uint2* xp = x + (size_t)(256 * warp + 2 * b) * 128 + 8 * t + g;
#pragma unroll
      for (int a = 0; a < 2; a++)
#pragma unroll
        for (int j = 0; j < 4; j++) { uint2 v = __ldg(xp + a * 128 + 32 * j); xw[a][j][0] = v.x; xw[a][j][1] = v.y; }
    }
    STAMP(0);
    asm volatile("barrier.cluster.arrive.relaxed.aligned;" ::: "memory");
    const int rep = ot & (NREP - 1);
    const unsigned base = __ldcg(&g_cnt[(1 * NREP + rep) * 64]);
    const uint32_t tag = (~base >> 7) & 1;
    FftC K;
    {
      float c, s;
#pragma unroll
      for (int h = 0; h < 2; h++)
#pragma unroll
        for (int j = 0; j < 2; j++) {
          cs<16>((2 * g + h) * (t + 4 * j), c, s);
          const uint32_t re = pk(ALPHA * c, ALPHA * s), im = pk(-ALPHA * s, ALPHA * c);
          K.a[0][2 * j + h] = re; K.a[1][2 * j + h] = im; K.a[2][2 * j + h] = pin(h ? re ^ NEG : re); K.a[3][2 * j + h] = pin(h ? im ^ NEG : im);
        }
#pragma unroll
      for (int i = 0; i < 4; i++) {
        cs<16>((4 * t + i) * (g >> 1) + 4 * (g & 1), c, s);
        const uint32_t P = pk(ALPHA * c, ALPHA * s), Q = pk(-ALPHA * s, ALPHA * c);
#pragma unroll
        for (int jj = 0; jj < 4; jj++) { const uint32_t v = ((i * jj) & 1 ? Q : P) ^ ((i * jj) & 2 ? NEG : 0u); K.b[4 * (i >> 1) + jj][i & 1] = jj ? pin(v) : v; }
      }
#pragma unroll
      for (int h = 0; h < 2; h++)
#pragma unroll
        for (int i = 0; i < 4; i++) {
          cs<256>((2 * g + h) * (4 * t + i), c, s);
          K.tc[h][i] = c * (1.f / (ALPHA * ALPHA)); K.ts[h][i] = s * (1.f / (ALPHA * ALPHA));
        }
    }
    const int key = ((b >> 3) & 3) * 2 + (b & 1);
    const uint32_t zb = sb + XCH_OFF;
    float mean[2];
    {
      uint32_t a8[2][4], a8c[2][4], a8n[2][4]; float vc[4], vs[4];
#pragma unroll
      for (int a = 0; a < 2; a++)
#pragma unroll
        for (int u = 0; u < 4; u++) {
          float c, s; cs<2048>(g * (256 * (t + 4 * (u >> 1)) + 2 * b + a), c, s);
          a8[a][u] = u & 1 ? pk(-s, c) : pk(c, s);
          a8c[a][u] = pin(a8[a][u] ^ 0x80000000u); a8n[a][u] = pin(a8[a][u] ^ 0x00008000u);
        }
#pragma unroll
      for (int i = 0; i < 4; i++) { cs<512>(16 * warp + 8 * (i >> 1) + 2 * t + (i & 1) + 128, vc[i], vs[i]); vc[i] = pinf(vc[i]); vs[i] = pinf(vs[i]); }
#pragma unroll
      for (int a = 0; a < 2; a++) {
        float cr[2][4], ci[2][4], o[4][4];
        if (a == 0) { STAMP(13); if (xw[0][0][0] == 0x12345678u && xw[1][3][1] == 0x12345679u) STAMP(31); STAMP(14); }
        fft_s1(K, xw[a], cr, ci);
        if (FILT_LATE && a == 0 && warp == 0) asm volatile("bar.arrive 3, 160;" :: "f"(cr[0][0]) : "memory");
        float sm = ((cr[0][0] + cr[0][1]) + (cr[1][0] + cr[1][1])) + ((ci[0][0] + ci[0][1]) + (ci[1][0] + ci[1][1]));
        sm += __shfl_xor_sync(0xffffffffu, sm, 1); sm += __shfl_xor_sync(0xffffffffu, sm, 2);
        sm = g == 0 ? sm * (1.f / 32.f) : 0.f;
#pragma unroll
        for (int h = 0; h < 2; h++) { cr[h][0] -= sm; cr[h][1] -= sm; ci[h][0] -= sm; ci[h][1] -= sm; }
        mean[a] = __shfl_sync(0xffffffffu, sm, 0) * (1.f / (16.f * 1.1328125f));
        float q = 0.f, q2 = 0.f;
#pragma unroll
        for (int i = 0; i < 4; i++) { q = fmaf(cr[0][i], cr[0][i], q); q2 = fmaf(cr[1][i], cr[1][i], q2); q = fmaf(ci[0][i], ci[0][i], q); q2 = fmaf(ci[1][i], ci[1][i], q2); }
        q += q2;
#pragma unroll
        for (int m = 1; m < 32; m <<= 1) q += __shfl_xor_sync(0xffffffffu, q, m);
        float r = rsqrtf(q * (1.f / (512.f * 16.f * ALPHA * ALPHA)) + 1e-5f) * 4.76837158203125e-7f;
        fft_s2(K, cr, ci, o);
#pragma unroll
        for (int j = 0; j < 4; j++)
          sts64(zb + ((a * 8 + warp) * ZROW + zphys(16 * t + 64 * j) + 2 * g) * 4, pk(o[j][0] * r, o[j][1] * r), pk(o[j][2] * r, o[j][3] * r));
      }
      STAMP(15);
      wbar();
      uint4* tp = g_T1 + (size_t)(g * 16 + warp) * 1024 + b * 8;
#pragma unroll
      for (int nt = 0; nt < 2; nt++) {
        const int k = 16 * warp + 8 * nt + g, km = k == 0 ? 128 : 256 - k;
        uint32_t lo[4], hi[4];
#pragma unroll
        for (int a = 0; a < 2; a++) {
          const uint32_t rb = zb + (a * 8 + t) * ZROW * 4;
          float A[4], S[4], D[4];
          const uint32_t m0 = lds32(rb + zphys(km) * 4), m1 = lds32(rb + (4 * ZROW + zphys(km)) * 4);
          mma0(A, a8[a], lds32(rb + zphys(k) * 4), lds32(rb + (4 * ZROW + zphys(k)) * 4));
          mmac(S, A, a8c[a], m0, m1);
          mmac(D, A, a8n[a], m0, m1);
#pragma unroll
          for (int e = 0; e < 2; e++) {
            const float c = vc[2 * nt + e], s = vs[2 * nt + e];
            float lr = fmaf(D[2 + e], s, fmaf(D[e], c, S[e])), li = fmaf(-D[e], s, fmaf(D[2 + e], c, S[2 + e]));
            float hr = fmaf(2.f, S[e], -lr), hii = fmaf(2.f, S[2 + e], -li);
            if (nt == 0 && e == 0) {
              const bool sp = warp == 0 && t == 0;
              lr = sp ? S[0] - D[0] : lr; li = sp ? S[2] - D[2] : li;
              hr = sp ? 2.f * (A[0] - A[2]) : hr; hii = sp ? 2.f * (A[0] + A[2]) : hii;
            }
            lo[2 * a + e] = pk(lr, li); hi[2 * a + e] = pk(hr, hii);
          }
        }
        const int w = (t + 4 * nt) ^ key;
        tp[w] = make_uint4((lo[0] & ~1u) | tag, lo[1], lo[2], lo[3]);
        tp[8 * 1024 + w] = make_uint4((hi[0] & ~1u) | tag, hi[1], hi[2], hi[3]);
      }
      wbar();
      STAMP(1);
      if (warp == 0) cnt_arrive(0, lane);
    }
    {
      const uint32_t off = (8 * t + g) * 128 + ((warp ^ (2 * t + (g & 1))) << 4);
      asm volatile("barrier.cluster.wait.aligned;" ::: "memory");
      mbar_wait(mb + MB_FILT * 8, 0);
      if (tid == 0) cnt_wait<false>(0, rep, base + NCTA);
      wbar();
#pragma unroll
      for (int j = 0; j < 4; j++)
        asm volatile("cp.async.cg.shared.global [%0], [%1], 16;" :: "r"(zb + j * 4096 + tid * 16), "l"(g_T1 + (size_t)b * 1024 + j * 256 + tid) : "memory");
      STAMP(2);
      uint32_t in[2][4][2], fw[2][4][2];
#pragma unroll
      for (int j = 0; j < 4; j++) {
        uint4 v = lds128(sb + FILT_OFF + off + j * 4096);
        fw[0][j][0] = v.x; fw[1][j][0] = v.y; fw[0][j][1] = v.z; fw[1][j][1] = v.w;
      }
      asm volatile("cp.async.wait_all;" ::: "memory");
      wbar();
      STAMP(3);
      uint4 iv[4];
#pragma unroll
      for (int j = 0; j < 4; j++) iv[j] = lds128(zb + off + j * 4096);
      if (((iv[0].x ^ tag) | (iv[1].x ^ tag) | (iv[2].x ^ tag) | (iv[3].x ^ tag)) & 1) {
#pragma unroll
        for (int j = 0; j < 4; j++) tag_check(iv[j], g_T1 + (size_t)b * 1024 + j * 256 + (off >> 4), tag);
      }
      __syncwarp();
#pragma unroll
      for (int j = 0; j < 4; j++) { in[0][j][0] = iv[j].x; in[1][j][0] = iv[j].y; in[0][j][1] = iv[j].z; in[1][j][1] = iv[j].w; }
#pragma unroll
      for (int sg = 0; sg < 2; sg++) {
        float cr[2][4], ci[2][4], o[4][4];
        fft_s1(K, in[sg], cr, ci);
        fft_s2(K, cr, ci, o);
#pragma unroll
        for (int j = 0; j < 4; j++)
#pragma unroll
          for (int h = 0; h < 2; h++) {
            float fr = blo(fw[sg][j][h]), fi = bhi(fw[sg][j][h]), xr = o[j][2 * h], xi = o[j][2 * h + 1];
            in[sg][j][h] = pk(xr * fi + xi * fr, xr * fr - xi * fi);
          }
        fft_s1(K, in[sg], cr, ci);
        fft_s2(K, cr, ci, o);
#pragma unroll
        for (int j = 0; j < 4; j++) { in[sg][j][0] = pk(o[j][0], o[j][1]); in[sg][j][1] = pk(o[j][2], o[j][3]); }
      }
#pragma unroll
      for (int j = 0; j < 4; j++) sts128(zb + off + j * 4096, make_uint4((in[0][j][0] & ~1u) | tag, in[1][j][0], in[0][j][1], in[1][j][1]));
      STAMP(16);
      wbar();
#pragma unroll
      for (int j = 0; j < 4; j++) g_T2[(size_t)b * 1024 + j * 256 + tid] = lds128(zb + j * 4096 + tid * 16);
      wbar();
      STAMP(4);
      if (warp == 0) cnt_arrive(1, lane);
    }
    {
      uint32_t a8[2][4], a8n[2][4]; float vc[4], vs[4];
#pragma unroll
      for (int a = 0; a < 2; a++)
#pragma unroll
        for (int u = 0; u < 4; u++) {
          float c, s; cs<2048>((t + 4 * (u >> 1)) * (256 * g + 2 * b + a), c, s);
          a8[a][u] = u & 1 ? pk(-s, c) : pk(c, s);
          a8n[a][u] = pin(a8[a][u] ^ NEG);
        }
#pragma unroll
      for (int i = 0; i < 4; i++) { cs<512>(16 * warp + 4 * t + i + 128, vc[i], vs[i]); vc[i] = pinf(vc[i]); vs[i] = pinf(vs[i]); }
      if (tid == 0) cnt_wait<false>(1, rep, base + NCTA);
      wbar();
      STAMP(5);
      const uint4* tp = g_T2 + (size_t)(t * 16 + warp) * 1024 + b * 8 + (g ^ key);
      uint4 L0 = ldcg128(tp), L1 = ldcg128(tp + 64 * 1024), H0 = ldcg128(tp + 8 * 1024), H1 = ldcg128(tp + 72 * 1024);
      if (((L0.x ^ tag) | (L1.x ^ tag) | (H0.x ^ tag) | (H1.x ^ tag)) & 1) {
        tag_check(L0, tp, tag); tag_check(L1, tp + 64 * 1024, tag); tag_check(H0, tp + 8 * 1024, tag); tag_check(H1, tp + 72 * 1024, tag);
      }
      __syncwarp();
      STAMP(17);
      const uint32_t l0[4] = {L0.x, L0.y, L0.z, L0.w}, l1[4] = {L1.x, L1.y, L1.z, L1.w}, h0[4] = {H0.x, H0.y, H0.z, H0.w}, h1[4] = {H1.x, H1.y, H1.z, H1.w};
#pragma unroll
      for (int a = 0; a < 2; a++) {
        uint32_t zf[4], zm[4];
#pragma unroll
        for (int sg = 0; sg < 2; sg++) {
          float A[4], S[4], D[4];
          mma0(A, a8[a], l0[2 * a + sg], l1[2 * a + sg]);
          mmac(S, A, a8[a], h0[2 * a + sg], h1[2 * a + sg]);
          mmac(D, A, a8n[a], h0[2 * a + sg], h1[2 * a + sg]);
#pragma unroll
          for (int e = 0; e < 2; e++) {
            const int i = 2 * e + sg;
            float fr = fmaf(-D[e], vs[i], fmaf(D[2 + e], vc[i], S[2 + e])), fi = fmaf(D[2 + e], vs[i], fmaf(D[e], vc[i], S[e]));
            float mr = fmaf(2.f, S[2 + e], -fr), mi = fmaf(-2.f, S[e], fi);
            if (i == 0) {
              const bool sp = warp == 0 && t == 0;
              fr = sp ? S[2] - A[2] : fr; fi = sp ? A[2] - S[2] : fi;
              mr = sp ? 2.f * A[2] : mr; mi = sp ? -2.f * A[0] : mi;
            }
            zf[i] = pk(fi, fr); zm[i] = pk(mi, mr);
          }
        }
        const uint32_t rb = zb + (a * 8 + g) * ZROW * 4;
        const int k0 = 16 * warp + 4 * t;
        sts128(rb + zphys(k0) * 4, make_uint4(zf[0], zf[1], zf[2], zf[3]));
        sts32(rb + zphys(k0 == 0 ? 128 : 256 - k0) * 4, zm[0]);
        sts32(rb + zphys(255 - k0) * 4, zm[1]);
        sts32(rb + zphys(254 - k0) * 4, zm[2]);
        sts32(rb + zphys(253 - k0) * 4, zm[3]);
      }
      STAMP(18);
      wbar();
#pragma unroll
      for (int a = 0; a < 2; a++) {
        uint32_t in[4][2];
#pragma unroll
        for (int j = 0; j < 4; j++) { uint2 v = lds64(zb + ((a * 8 + warp) * ZROW + zphys(16 * t + 64 * j) + 2 * g) * 4); in[j][0] = v.x; in[j][1] = v.y; }
        float cr[2][4], ci[2][4], o[4][4];
        fft_s1(K, in, cr, ci);
        fft_s2(K, cr, ci, o);
        float s1 = 0.f, s2 = 0.f;
#pragma unroll
        for (int j = 0; j < 4; j++) {
          uint32_t hw[2];
#pragma unroll
          for (int h = 0; h < 2; h++) {
            asm("add.rn.bf16x2 %0, %1, %2;" : "=r"(hw[h]) : "r"(xw[a][j][h]), "r"(pk(o[j][2 * h + 1], o[j][2 * h])));
            float u0 = blo(hw[h]) - mean[a], u1 = bhi(hw[h]) - mean[a];
            o[j][2 * h] = u0; o[j][2 * h + 1] = u1;
            s1 = fmaf(u0, u0, s1); s2 = fmaf(u1, u1, s2);
          }
        }
        s2 += s1;
#pragma unroll
        for (int m = 1; m < 32; m <<= 1) s2 += __shfl_xor_sync(0xffffffffu, s2, m);
        const float var = s2 * (1.f / 512.f), r1 = rsqrtf(var + 1e-5f);
        const float r = r1 * rsqrtf(var * r1 * r1 + 1e-5f);
        if (lane == 0) g_st[256 * warp + 2 * b + a] = make_float2(1.f / r, mean[a]);
        char* np = (char*)g_Hn + (size_t)b * 4096 + (t >> 1) * 2048 + a * 1024 + warp * 128 + ((((t & 1) * 4 + (g >> 1)) ^ warp ^ (b >> 6)) << 4) + (g & 1) * 8;
#pragma unroll
        for (int j = 0; j < 4; j++)
          *(uint2*)(np + (size_t)j * 128 * 4096) = make_uint2(pk(o[j][0] * r, o[j][1] * r), pk(o[j][2] * r, o[j][3] * r));
      }
      STAMP(19);
      asm volatile("fence.proxy.async.shared::cta;" ::: "memory");
      wbar();
      STAMP(6);
      if (warp == 0) { fence_gpu(); cnt_arrive(2 + (b >> 6), lane); STAMP(25); }
      if (tid == 32) { sts32(sb + BASE_OFF, base); mbar_arrive(mb + MB_P3DONE * 8); }
    }
    const int wg = warp >> 2;
    const uint32_t peer_sb = mapa(sb, rank ^ 1);
    {
      float acc[44];
#pragma unroll
      for (int j = 0; j < 11; j++) {
        const uint32_t bw = __ldg(b1 + min(11 * ot + j, 171) * 4 + t);
        acc[4 * j] = blo(bw); acc[4 * j + 1] = bhi(bw); acc[4 * j + 2] = 0.f; acc[4 * j + 3] = 0.f;
      }
      const uint32_t da0 = desc_lo(sb + RING_OFF + wg * 2048, 0);
      uint32_t da = da0, db = desc_lo(sb, 1408), bar = mb;
      mbar_wait(mb + MB_W1 * 8, 0);
#pragma unroll 1
      for (int i = 0; i < 32; i++) {
        mbar_wait(bar + MB_FULL * 8, 0);
        if (i == 0) STAMP(7);
        asm volatile("wgmma.fence.sync.aligned;" ::: "memory");
        wgmma_n88_ss<1, 1, HI_SW128, HI_NOSW>(acc, da, db, 1);
        wgmma_n88_ss<1, 1, HI_SW128, HI_NOSW>(acc, da + 256, db + 176, 1);
        asm volatile("wgmma.commit_group.sync.aligned;" ::: "memory");
        da = da == da0 + 5 * 512 ? da0 : da + 512; db += 352;
        asm volatile("wgmma.wait_group.sync.aligned 1;" ::: "memory");
        if ((tid & 127) == 0) { if (i > 0) mbar_arrive(bar + (MB_EMPTY - 1) * 8); if (i == 4) mbar_arrive_cluster(peer_sb + BAR_OFF + MB_PEER1 * 8); }
        bar += 8;
      }
      asm volatile("wgmma.wait_group.sync.aligned 0;" ::: "memory");
#pragma unroll
      for (int i = 0; i < 44; i++) asm volatile("" : "+f"(acc[i]) :: "memory");
      if ((tid & 127) == 0) mbar_arrive(mb + (MB_EMPTY + 31) * 8);
      STAMP(8);
      mbar_wait_cluster(mb + MB_PEER1 * 8, 0);
#pragma unroll
      for (int j = 0; j < 3; j++)
        st_async4(peer_sb + j * 4096 + tid * 16, pk(acc[16 * j + 2], acc[16 * j + 3]), pk(acc[16 * j + 6], acc[16 * j + 7]), pk(acc[16 * j + 10], acc[16 * j + 11]),
                  j < 2 ? pk(acc[16 * j + 14], acc[16 * j + 15]) : 0u, peer_sb + BAR_OFF + MB_X1 * 8);
      const int uo = (4 * (warp >> 1) + (g >> 1)) * 32 + (2 * (2 * (warp & 1) + rank) + (g & 1)) * 4 + t;
      uint32_t* const ub = (uint32_t*)g_U + ((size_t)dt * 172 + 11 * ot) * 512;
      uint32_t *upa = ub + (uo ^ (ot >= 8 ? 256 : 0)), *upb = ub + (uo ^ (ot >= 7 ? 256 : 0));
      STAMP(20);
      mbar_wait_cluster(mb + MB_X1 * 8, 0);
      STAMP(21);
      uint32_t pv[12];
#pragma unroll
      for (int j = 0; j < 3; j++) { const uint4 v = lds128(sb + j * 4096 + tid * 16); pv[4 * j] = v.x; pv[4 * j + 1] = v.y; pv[4 * j + 2] = v.z; pv[4 * j + 3] = v.w; }
#pragma unroll
      for (int j = 0; j < 11; j++) {
        uint32_t v = pk(gelu(acc[4 * j] + blo(pv[j])), gelu(acc[4 * j + 1] + bhi(pv[j])));
        if (j < 7 || ot < 15) (j < 9 ? upa : upb)[j * 512] = v;
      }
      STAMP(22);
      asm volatile("fence.proxy.async.shared::cta;" ::: "memory");
      wbar();
      STAMP(9);
      if (warp == 0) { fence_gpu(); cnt_arrive(4 + dt, lane); STAMP(26); }
      if (tid == 32) mbar_arrive(mb + MB_X1DONE * 8);
    }
    {
      const int srow = 128 * ot + 16 * warp + g, oo = srow * 64 + dt * 16 + 8 * rank + t;
      float acc[64];
      const uint32_t da0 = desc_lo(sb + wg * 4096, 0), db0 = desc_lo(sb + RING_OFF, 2048);
      uint32_t da = da0 + 3 * 512, db = db0 + (32 % NST) * 512, bar = mb;
#pragma unroll
      for (int u = 0; u < 2; u++) {
        const int sr = srow + 8 * u, s1 = ot >> 1;
        const float2 st = __ldcg(g_st + sr);
        const float off = st.y + __uint_as_float((uint32_t)__ldg(b2 + sr) << 16);
#pragma unroll
        for (int jj = 0; jj < 2; jj++) {
          const uint4 v = ldcg128(g_Hn + (dt * 128 + ((sr & 255) >> 1)) * 256 + rank * 128 + (sr & 1) * 64 + s1 * 8 + ((4 * jj + t) ^ s1 ^ (ot & 1)));
          const uint32_t w[4] = {v.x, v.y, v.z, v.w};
#pragma unroll
          for (int j = 0; j < 4; j++) { acc[16 * jj + 4 * j + 2 * u] = fmaf(blo(w[j]), st.x, off); acc[16 * jj + 4 * j + 2 * u + 1] = fmaf(bhi(w[j]), st.x, off); }
        }
      }
#pragma unroll
      for (int j = 32; j < 64; j++) acc[j] = 0.f;
#pragma unroll 1
      for (int i = 0; i < 21; i++) {
        mbar_wait(bar + MB_W2 * 8, 0);
        mbar_wait(bar + (MB_FULL + 32) * 8, 0);
        if (i == 0) STAMP(10);
        asm volatile("wgmma.fence.sync.aligned;" ::: "memory");
        wgmma_n128_ss<1, 0, HI_SW128, HI_NOSW>(acc, da, db, 1);
        wgmma_n128_ss<1, 0, HI_SW128, HI_NOSW>(acc, da + 128, db + 256, 1);
        asm volatile("wgmma.commit_group.sync.aligned;" ::: "memory");
        da = i == 18 ? da0 : da + 512; db = db == db0 + 5 * 512 ? db0 : db + 512;
        asm volatile("wgmma.wait_group.sync.aligned 1;" ::: "memory");
        if ((tid & 127) == 0) { if (i > 0) mbar_arrive(bar + (MB_EMPTY + 31) * 8); if (i == 4) mbar_arrive_cluster(peer_sb + BAR_OFF + MB_PEER2 * 8); }
        bar += 8;
      }
      mbar_wait(bar + MB_W2 * 8, 0);
      mbar_wait(bar + (MB_FULL + 32) * 8, 0);
      asm volatile("wgmma.fence.sync.aligned;" ::: "memory");
      wgmma_n128_ss<1, 0, HI_SW128, HI_NOSW>(acc, da, db, 1);
      asm volatile("wgmma.commit_group.sync.aligned;" ::: "memory");
      asm volatile("wgmma.wait_group.sync.aligned 0;" ::: "memory");
#pragma unroll
      for (int i = 0; i < 64; i++) asm volatile("" : "+f"(acc[i]) :: "memory");
      STAMP(11);
      mbar_wait_cluster(mb + MB_PEER2 * 8, 0);
#pragma unroll
      for (int j = 0; j < 4; j++) {
        const int o = 32 + 16 * (j >> 1) + 2 * (j & 1);
        st_async4(peer_sb + 3 * 8192 + j * 4096 + tid * 16, pk(acc[o], acc[o + 1]), pk(acc[o + 4], acc[o + 5]), pk(acc[o + 8], acc[o + 9]), pk(acc[o + 12], acc[o + 13]),
                  peer_sb + BAR_OFF + MB_X2 * 8);
      }
      STAMP(23);
      mbar_wait_cluster(mb + MB_X2 * 8, 0);
      STAMP(24);
#pragma unroll
      for (int j = 0; j < 4; j++) {
        const int o = 16 * (j >> 1) + 2 * (j & 1);
        const uint4 v = lds128(sb + 3 * 8192 + j * 4096 + tid * 16);
        out[oo + 4 * (j >> 1) + 512 * (j & 1)] = make_uint4(pk(acc[o] + blo(v.x), acc[o + 1] + bhi(v.x)), pk(acc[o + 4] + blo(v.y), acc[o + 5] + bhi(v.y)),
                                                            pk(acc[o + 8] + blo(v.z), acc[o + 9] + bhi(v.z)), pk(acc[o + 12] + blo(v.w), acc[o + 13] + bhi(v.w)));
      }
      STAMP(12);
    }
  } else {
    const int pw = warp - 8;
    if (pw < 3 && elect()) {
#pragma unroll
      for (int i = 0; i < 57; i++) mbar_init(mb + (pw * 57 + i) * 8, pw == 2 ? 2 : 1);
      if (pw == 1) { mbar_expect(mb + MB_X1 * 8, 12288); mbar_expect(mb + MB_X2 * 8, 16384); }
      asm volatile("fence.mbarrier_init.release.cluster;" ::: "memory");
    }
    __syncwarp();
    STAMP(0);
    asm volatile("bar.sync 2, 128;" ::: "memory");
    asm volatile("barrier.cluster.arrive.relaxed.aligned;" ::: "memory");
    auto w1_issue = [&](int i) {
      if (elect()) { mbar_expect(mb + (MB_W1T + i) * 8, 5632); tma3d(sb + i * 5632, &tmW1, 88 * ot, 0, 128 * rank + 4 * i, mb + (MB_W1T + i) * 8); }
      __syncwarp();
    };
    if (!W1_LATE && pw < W1_WARPS) for (int i = 0; i < W1_DEPTH; i++) w1_issue(pw + W1_WARPS * i);
    {
      const int j1 = b >> 4, q = b & 15, slot = lane & 15, h = lane >> 4;
      const bool hi = q >= 8;
      const int k = 16 * (q & 7) + slot, col = hi ? 256 - k : (k == 0 ? 128 : k);
      const int j0 = j1 + 8 * h + 512 * pw, o0 = (hi ? 2048 - 31 * 16 - j0 : j0) * DF + col, o31 = hi && j0 == 0 ? o0 - 2048 * DF : o0;
      uint32_t vr[32], vi[32];
      if (FILT_LATE) { asm volatile("bar.sync 3, 160;" ::: "memory"); asm volatile("" : "+l"(wr), "+l"(wi)); }
#pragma unroll
      for (int n = 0; n < 32; n++) { vr[n] = __ldg(wr + (n == 31 ? o31 : o0) + n * 16 * DF); vi[n] = __ldg(wi + (n == 31 ? o31 : o0) + n * 16 * DF); }
      const uint32_t f0 = sb + FILT_OFF + pw * 4096 + (hi ? 31 * 128 : 0) + h * 8 + (slot & 1) * 4, sw = ((slot >> 1) ^ (hi ? 7 : 0)) << 4;
      const int st = hi ? -128 : 128;
#pragma unroll
      for (int n = 0; n < 32; n++)
        sts32(f0 + n * st + (sw ^ ((((n >> 3) & 3) * 2 + (n & 1)) << 4)), __byte_perm(vr[n], vi[n], 0x5410) ^ (hi ? 0x80000000u : 0u));
      asm volatile("bar.sync 2, 128;" ::: "memory");
      if (threadIdx.x == 352) mbar_arrive(mb + MB_FILT * 8);
    }
    if (PF_W1 && elect()) asm volatile("cp.async.bulk.prefetch.L2.global [%0], %1;" :: "l"(w1 + (size_t)(b * 4 + pw) * 11008), "r"(11008) : "memory");
    __syncwarp();
    STAMP(1);
    {
      if (W1_LATE && pw < W1_WARPS) for (int i = 0; i < W1_DEPTH; i++) w1_issue(pw + W1_WARPS * i);
      const uint32_t rd = ((lane & 7) * 11 + (lane >> 3)) * 16, wr = lane * 16;
#pragma unroll 1
      for (int box = pw < W1_WARPS ? pw : 32; box < W1_END; box += W1_WARPS) {
        mbar_wait(mb + (MB_W1T + box) * 8, 0);
        if (box + W1_WARPS * W1_DEPTH < 32) w1_issue(box + W1_WARPS * W1_DEPTH);
        const uint32_t p = sb + box * 5632;
        uint4 v[4][3];
#pragma unroll
        for (int n = 0; n < 4; n++) { v[n][0] = lds128(p + n * 1408 + rd); v[n][1] = lds128(p + n * 1408 + rd + 64); if (lane < 24) v[n][2] = lds128(p + n * 1408 + rd + 128); }
        __syncwarp();
#pragma unroll
        for (int n = 0; n < 4; n++) { sts128(p + n * 1408 + wr, v[n][0]); sts128(p + n * 1408 + wr + 512, v[n][1]); if (lane < 24) sts128(p + n * 1408 + wr + 1024, v[n][2]); }
      }
      if (lane == 0) asm volatile("cp.async.bulk.prefetch.L2.global [%0], %1;" :: "l"(w2 + (size_t)(b * 4 + pw) * 11008), "r"(11008) : "memory");
      asm volatile("fence.proxy.async.shared::cta;" ::: "memory");
      asm volatile("bar.sync 2, 128;" ::: "memory");
      if (threadIdx.x == 352) mbar_arrive(mb + MB_W1 * 8);
    }
    STAMP(2);
    asm volatile("barrier.cluster.wait.aligned;" ::: "memory");
    if (pw == 3) {
#pragma unroll 1
      for (int n = 0; n < 22; n++) {
        if (n < W2_PRE) mbar_wait(mb + (MB_EMPTY + min(31, max(((n + 4) * 16 + 10) / 11 - 1, W2_START + n * W2_NUM / W2_DEN))) * 8, 0);
        else { mbar_wait(mb + MB_X1DONE * 8, 0); if (W2_PACE) mbar_wait(mb + (MB_FULL + 32 - W2_PRE + n) * 8, 0); }
        if (elect()) { mbar_expect(mb + (MB_W2 + n) * 8, 8192); tma3d(sb + (n < 19 ? n + 3 : n - 19) * 8192, &tmW2, 0, 688 * rank + 32 * n, 2 * ot, mb + (MB_W2 + n) * 8); }
      }
    } else {
      int i = pw;
      uint32_t dst = sb + RING_OFF + pw * 8192;
      const uint32_t dsum = 2 * dst + 3 * 8192;
      const char* src = (const char*)g_Hn + ((size_t)dt * 128 + 64 * rank) * 4096;
#pragma unroll 1
      for (int gm = 0; gm < 2; gm++) {
        if (pw == 0) {
          mbar_wait(mb + (gm ? MB_X1DONE : MB_P3DONE) * 8, 0);
          STAMP(3 + 2 * gm);
          if (lane == 0) cnt_wait<true>(gm ? 4 + dt : 2 + rank, ot & (NREP - 1), ((lds32(sb + BASE_OFF) >> 1) + 64) >> gm);
        }
        asm volatile("bar.sync 2, 96;" ::: "memory");
        STAMP(4 + 2 * gm);
        asm volatile("fence.proxy.async.global;" ::: "memory");
#pragma unroll 1
        for (; i < (gm ? 54 : 32); i += 3) {
          if (i >= NST) mbar_wait(mb + (MB_EMPTY - NST + i) * 8, 0);
          if (elect()) {
            const int bytes = i < 53 ? 8192 : 4096;
            mbar_expect(mb + (MB_FULL + i) * 8, bytes); bulk_ld(dst, src + i * 8192, bytes, mb + (MB_FULL + i) * 8);
          }
          dst = dsum - dst;
        }
        src = (const char*)g_U + ((size_t)dt * 172 + 86 * rank) * 2048 - 32 * 8192;
      }
      STAMP(7);
    }
  }
}

typedef CUresult (*EncodeFn)(CUtensorMap*, CUtensorMapDataType, cuuint32_t, void*, const cuuint64_t*, const cuuint64_t*, const cuuint32_t*,
                             const cuuint32_t*, CUtensorMapInterleave, CUtensorMapSwizzle, CUtensorMapL2promotion, CUtensorMapFloatOOBfill);

extern "C" void kernel_launch(void* const* d_in, const int* in_sizes, int n_in, void* d_out, int out_size) {
  static EncodeFn enc = nullptr;
  if (!enc) {
    void* fn = nullptr; cudaDriverEntryPointQueryResult st;
    cudaGetDriverEntryPoint("cuTensorMapEncodeTiled", &fn, cudaEnableDefault, &st);
    enc = (EncodeFn)fn;
    cudaFuncSetAttribute(fused_kernel, cudaFuncAttributeMaxDynamicSharedMemorySize, SMEM_BYTES);
  }
  CUtensorMap tm, tm1;
  {
    cuuint64_t dims[3] = {(cuuint64_t)F_, 8, 256}, strides[2] = {(cuuint64_t)256 * F_ * 2, F_ * 2};
    cuuint32_t box[3] = {88, 8, 4}, es[3] = {1, 1, 1};
    enc(&tm1, CU_TENSOR_MAP_DATA_TYPE_BFLOAT16, 3, d_in[4], dims, strides, box, es, CU_TENSOR_MAP_INTERLEAVE_NONE, CU_TENSOR_MAP_SWIZZLE_NONE,
        W1_PROMO, CU_TENSOR_MAP_FLOAT_OOB_FILL_NONE);
  }
  {
    cuuint64_t dims[3] = {64, (cuuint64_t)F_, S_ / 64}, strides[2] = {S_ * 2, 128};
    cuuint32_t box[3] = {64, 32, 2}, es[3] = {1, 1, 1};
    enc(&tm, CU_TENSOR_MAP_DATA_TYPE_BFLOAT16, 3, d_in[6], dims, strides, box, es, CU_TENSOR_MAP_INTERLEAVE_NONE, CU_TENSOR_MAP_SWIZZLE_128B,
        CU_TENSOR_MAP_L2_PROMOTION_L2_256B, CU_TENSOR_MAP_FLOAT_OOB_FILL_NONE);
  }
  fused_kernel<<<NCTA, 384, SMEM_BYTES, cudaStreamPerThread>>>(tm1, tm, (const uint2*)d_in[0], (const unsigned short*)d_in[1], (const unsigned short*)d_in[2],
                                          (const char*)d_in[4], (const uint32_t*)d_in[5], (const char*)d_in[6], (const unsigned short*)d_in[7], (uint4*)d_out);
}
```

```cpp
#include <cuda_runtime.h>
#include <cuda.h>
#include <cuda_bf16.h>
#include <stdint.h>
#define W1_LATE 1
#define W1_PROMO CU_TENSOR_MAP_L2_PROMOTION_NONE
#define W2_NUM 1
#define W2_DEN 1
#define PF_W1 0
#define W1_DEPTH 1
#define W1_WARPS 4
#define W2_PRE 12
#define W2_PACE 1
#define FILT_LATE 1
#define W1_END 32
template<int TA, int TB, uint32_t HA, uint32_t HB> __device__ __forceinline__ void wgmma_n88_ss(float (&d)[44], uint32_t da, uint32_t db, int sd) {
  asm volatile("{\n.reg .pred p;\n.reg .b64 da, db;\nsetp.ne.b32 p, %46, 0;\nmov.b64 da, {%44, %49};\nmov.b64 db, {%45, %50};\n"
    "wgmma.mma_async.sync.aligned.m64n88k16.f32.bf16.bf16 {%0, %1, %2, %3, %4, %5, %6, %7, %8, %9, %10, %11, %12, %13, %14, %15, %16, %17, %18, %19, %20, %21, %22, %23, %24, %25, %26, %27, %28, %29, %30, %31, %32, %33, %34, %35, %36, %37, %38, %39, %40, %41, %42, %43}, da, db, p, 1, 1, %47, %48;\n}\n"
    : "+f"(d[0]), "+f"(d[1]), "+f"(d[2]), "+f"(d[3]), "+f"(d[4]), "+f"(d[5]), "+f"(d[6]), "+f"(d[7]), "+f"(d[8]), "+f"(d[9]), "+f"(d[10]), "+f"(d[11]), "+f"(d[12]), "+f"(d[13]), "+f"(d[14]), "+f"(d[15]), "+f"(d[16]), "+f"(d[17]), "+f"(d[18]), "+f"(d[19]), "+f"(d[20]), "+f"(d[21]), "+f"(d[22]), "+f"(d[23]), "+f"(d[24]), "+f"(d[25]), "+f"(d[26]), "+f"(d[27]), "+f"(d[28]), "+f"(d[29]), "+f"(d[30]), "+f"(d[31]), "+f"(d[32]), "+f"(d[33]), "+f"(d[34]), "+f"(d[35]), "+f"(d[36]), "+f"(d[37]), "+f"(d[38]), "+f"(d[39]), "+f"(d[40]), "+f"(d[41]), "+f"(d[42]), "+f"(d[43]) : "r"(da), "r"(db), "r"(sd), "n"(TA), "n"(TB), "n"(HA), "n"(HB));
}
template<int TA, int TB, uint32_t HA, uint32_t HB> __device__ __forceinline__ void wgmma_n128_ss(float (&d)[64], uint32_t da, uint32_t db, int sd) {
  asm volatile("{\n.reg .pred p;\n.reg .b64 da, db;\nsetp.ne.b32 p, %66, 0;\nmov.b64 da, {%64, %69};\nmov.b64 db, {%65, %70};\n"
    "wgmma.mma_async.sync.aligned.m64n128k16.f32.bf16.bf16 {%0, %1, %2, %3, %4, %5, %6, %7, %8, %9, %10, %11, %12, %13, %14, %15, %16, %17, %18, %19, %20, %21, %22, %23, %24, %25, %26, %27, %28, %29, %30, %31, %32, %33, %34, %35, %36, %37, %38, %39, %40, %41, %42, %43, %44, %45, %46, %47, %48, %49, %50, %51, %52, %53, %54, %55, %56, %57, %58, %59, %60, %61, %62, %63}, da, db, p, 1, 1, %67, %68;\n}\n"
    : "+f"(d[0]), "+f"(d[1]), "+f"(d[2]), "+f"(d[3]), "+f"(d[4]), "+f"(d[5]), "+f"(d[6]), "+f"(d[7]), "+f"(d[8]), "+f"(d[9]), "+f"(d[10]), "+f"(d[11]), "+f"(d[12]), "+f"(d[13]), "+f"(d[14]), "+f"(d[15]), "+f"(d[16]), "+f"(d[17]), "+f"(d[18]), "+f"(d[19]), "+f"(d[20]), "+f"(d[21]), "+f"(d[22]), "+f"(d[23]), "+f"(d[24]), "+f"(d[25]), "+f"(d[26]), "+f"(d[27]), "+f"(d[28]), "+f"(d[29]), "+f"(d[30]), "+f"(d[31]), "+f"(d[32]), "+f"(d[33]), "+f"(d[34]), "+f"(d[35]), "+f"(d[36]), "+f"(d[37]), "+f"(d[38]), "+f"(d[39]), "+f"(d[40]), "+f"(d[41]), "+f"(d[42]), "+f"(d[43]), "+f"(d[44]), "+f"(d[45]), "+f"(d[46]), "+f"(d[47]), "+f"(d[48]), "+f"(d[49]), "+f"(d[50]), "+f"(d[51]), "+f"(d[52]), "+f"(d[53]), "+f"(d[54]), "+f"(d[55]), "+f"(d[56]), "+f"(d[57]), "+f"(d[58]), "+f"(d[59]), "+f"(d[60]), "+f"(d[61]), "+f"(d[62]), "+f"(d[63]) : "r"(da), "r"(db), "r"(sd), "n"(TA), "n"(TB), "n"(HA), "n"(HB));
}

constexpr int S_ = 2048, F_ = 1376, DF = 257;
constexpr int NCTA = 128;
constexpr int W_BYTES = 180224;
constexpr int RING_OFF = W_BYTES;
constexpr int NST = 6;
constexpr int BAR_OFF = RING_OFF + NST * 8192;
constexpr int SMEM_BYTES = BAR_OFF + 1536;
constexpr int FILT_OFF = RING_OFF;
constexpr int XCH_OFF = RING_OFF + 16384;
constexpr int ZROW = 328;
constexpr int MB_FULL = 0, MB_W2 = 54, MB_W1T = 76, MB_X1 = 108, MB_X2 = 109, MB_X1DONE = 110, MB_P3DONE = 111, MB_FILT = 112, MB_W1 = 113,
              MB_EMPTY = 114, MB_PEER1 = 168, MB_PEER2 = 169, MB_N = 171;
constexpr int BASE_OFF = BAR_OFF + MB_N * 8;
#define W2_START 24

struct Scratch {
  uint4 T1[NCTA * 1024], T2[NCTA * 1024], Hn[4 * 128 * 256], U[4 * 172 * 128];
  float2 st[S_];
  unsigned cnt[8 * 4 * 64];
};
__device__ __align__(1024) Scratch g_scr;
#define g_T1 (scr->T1)
#define g_T2 (scr->T2)
#define g_Hn (scr->Hn)
#define g_U (scr->U)
#define g_st (scr->st)
#define g_cnt (scr->cnt)
#define STAMP(i)

__device__ __forceinline__ void mbar_init(uint32_t b, int c) { asm volatile("mbarrier.init.shared::cta.b64 [%0], %1;" :: "r"(b), "r"(c) : "memory"); }
__device__ __forceinline__ void mbar_expect(uint32_t b, int bytes) { asm volatile("mbarrier.arrive.expect_tx.shared::cta.b64 _, [%0], %1;" :: "r"(b), "r"(bytes) : "memory"); }
__device__ __forceinline__ void mbar_arrive(uint32_t b) { asm volatile("mbarrier.arrive.shared::cta.b64 _, [%0];" :: "r"(b) : "memory"); }
__device__ __forceinline__ void mbar_arrive_cluster(uint32_t remote) { asm volatile("mbarrier.arrive.relaxed.cluster.shared::cluster.b64 _, [%0];" :: "r"(remote) : "memory"); }
__device__ __forceinline__ uint32_t mapa(uint32_t a, uint32_t cta) { uint32_t r; asm("mapa.shared::cluster.u32 %0, %1, %2;" : "=r"(r) : "r"(a), "r"(cta)); return r; }
__device__ __forceinline__ void mbar_wait(uint32_t b, int ph) {
  asm volatile("{\n.reg .pred p;\n.reg .u32 n;\nmov.u32 n, 0;\nL_W:\n"
               "mbarrier.try_wait.parity.shared::cta.b64 p, [%0], %1;\n@p bra L_D;\n"
               "add.u32 n, n, 1;\nsetp.lt.u32 p, n, 4000000;\n@p bra L_W;\ntrap;\nL_D:\n}" :: "r"(b), "r"(ph) : "memory");
}
__device__ __forceinline__ void mbar_wait_cluster(uint32_t b, int ph) {
  asm volatile("{\n.reg .pred p;\n.reg .u32 n;\nmov.u32 n, 0;\nL_W:\n"
               "mbarrier.try_wait.parity.acquire.cluster.shared::cta.b64 p, [%0], %1;\n@p bra L_D;\n"
               "add.u32 n, n, 1;\nsetp.lt.u32 p, n, 4000000;\n@p bra L_W;\ntrap;\nL_D:\n}" :: "r"(b), "r"(ph) : "memory");
}
__device__ __forceinline__ void bulk_ld(uint32_t dst, const void* src, int bytes, uint32_t bar) {
  asm volatile("cp.async.bulk.shared::cluster.global.mbarrier::complete_tx::bytes [%0], [%1], %2, [%3];" :: "r"(dst), "l"(src), "r"(bytes), "r"(bar) : "memory");
}
__device__ __forceinline__ void tma3d(uint32_t dst, const CUtensorMap* tm, int c0, int c1, int c2, uint32_t bar) {
  asm volatile("cp.async.bulk.tensor.3d.shared::cluster.global.mbarrier::complete_tx::bytes [%0], [%1, {%3, %4, %5}], [%2];"
               :: "r"(dst), "l"(tm), "r"(bar), "r"(c0), "r"(c1), "r"(c2) : "memory");
}
__device__ __forceinline__ bool elect() { uint32_t p; asm volatile("{.reg .pred p; elect.sync _|p, 0xffffffff; selp.b32 %0, 1, 0, p;}" : "=r"(p)); return p; }
__device__ __forceinline__ uint32_t desc_lo(uint32_t addr, uint32_t lbo) { return ((addr & 0x3FFFF) >> 4) | ((lbo >> 4) << 16); }
constexpr uint32_t HI_SW128 = (1024 >> 4) | (1u << 30), HI_NOSW = 128 >> 4;
__device__ __forceinline__ uint32_t pk(float lo, float hi) { uint32_t r; asm("cvt.rn.bf16x2.f32 %0, %1, %2;" : "=r"(r) : "f"(hi), "f"(lo)); return r; }
__device__ __forceinline__ float blo(uint32_t w) { return __uint_as_float(w << 16); }
__device__ __forceinline__ float bhi(uint32_t w) { return __uint_as_float(w & 0xffff0000u); }
__device__ __forceinline__ void mmac(float (&d)[4], const float (&c)[4], const uint32_t (&a)[4], uint32_t b0, uint32_t b1) {
  asm("mma.sync.aligned.m16n8k16.row.col.f32.bf16.bf16.f32 {%0,%1,%2,%3}, {%4,%5,%6,%7}, {%8,%9}, {%10,%11,%12,%13};"
      : "=f"(d[0]), "=f"(d[1]), "=f"(d[2]), "=f"(d[3]) : "r"(a[0]), "r"(a[1]), "r"(a[2]), "r"(a[3]), "r"(b0), "r"(b1), "f"(c[0]), "f"(c[1]), "f"(c[2]), "f"(c[3]));
}
__device__ __forceinline__ void mma0(float (&d)[4], const uint32_t (&a)[4], uint32_t b0, uint32_t b1) { const float z[4] = {0.f, 0.f, 0.f, 0.f}; mmac(d, z, a, b0, b1); }
__device__ __forceinline__ uint32_t pin(uint32_t v) { asm volatile("shfl.sync.bfly.b32 %0, %0, 0, 31, 0xffffffff;" : "+r"(v)); return v; }
__device__ __forceinline__ float pinf(float v) { asm volatile("" : "+f"(v)); return v; }
__device__ __forceinline__ void wbar() { asm volatile("bar.sync 1, 256;" ::: "memory"); }
__device__ __forceinline__ void sts32(uint32_t a, uint32_t v) { asm volatile("st.shared.b32 [%0], %1;" :: "r"(a), "r"(v) : "memory"); }
__device__ __forceinline__ void sts64(uint32_t a, uint32_t x, uint32_t y) { asm volatile("st.shared.v2.b32 [%0], {%1,%2};" :: "r"(a), "r"(x), "r"(y) : "memory"); }
__device__ __forceinline__ void sts128(uint32_t a, uint4 v) { asm volatile("st.shared.v4.b32 [%0], {%1,%2,%3,%4};" :: "r"(a), "r"(v.x), "r"(v.y), "r"(v.z), "r"(v.w) : "memory"); }
__device__ __forceinline__ uint32_t lds32(uint32_t a) { uint32_t v; asm volatile("ld.shared.b32 %0, [%1];" : "=r"(v) : "r"(a) : "memory"); return v; }
__device__ __forceinline__ uint2 lds64(uint32_t a) { uint2 v; asm volatile("ld.shared.v2.b32 {%0,%1}, [%2];" : "=r"(v.x), "=r"(v.y) : "r"(a) : "memory"); return v; }
__device__ __forceinline__ uint4 lds128(uint32_t a) { uint4 v; asm volatile("ld.shared.v4.b32 {%0,%1,%2,%3}, [%4];" : "=r"(v.x), "=r"(v.y), "=r"(v.z), "=r"(v.w) : "r"(a) : "memory"); return v; }
__device__ __forceinline__ uint4 ldcg128(const void* p) { uint4 v; asm volatile("ld.global.cg.v4.b32 {%0,%1,%2,%3}, [%4];" : "=r"(v.x), "=r"(v.y), "=r"(v.z), "=r"(v.w) : "l"(p) : "memory"); return v; }
__device__ __forceinline__ void st_async4(uint32_t a, uint32_t x, uint32_t y, uint32_t z, uint32_t w, uint32_t bar) {
  asm volatile("st.async.weak.shared::cluster.mbarrier::complete_tx::bytes.v4.b32 [%0], {%1,%2,%3,%4}, [%5];" :: "r"(a), "r"(x), "r"(y), "r"(z), "r"(w), "r"(bar) : "memory");
}
constexpr int NREP = 4;
__device__ __forceinline__ void cnt_arrive(Scratch* scr, int i, int lane) {
  if (lane < NREP) asm volatile("red.relaxed.gpu.global.add.u32 [%0], 1;" :: "l"(&g_cnt[(i * NREP + lane) * 64]) : "memory");
}
template <bool ACQ> __device__ __forceinline__ void cnt_wait(Scratch* scr, int i, int rep, unsigned target) {
  unsigned v; int n = 0;
  do {
    if (ACQ) asm volatile("ld.acquire.gpu.global.u32 %0, [%1];" : "=r"(v) : "l"(&g_cnt[(i * NREP + rep) * 64]) : "memory");
    else asm volatile("ld.relaxed.gpu.global.u32 %0, [%1];" : "=r"(v) : "l"(&g_cnt[(i * NREP + rep) * 64]) : "memory");
    if (++n > 2000000) __trap(); } while ((int)(v - target) < 0);
}
__device__ __forceinline__ void fence_gpu() { asm volatile("fence.acq_rel.gpu;" ::: "memory"); }
__device__ __forceinline__ void tag_check(uint4& v, const uint4* p, uint32_t tag) {
  int n = 0;
  while ((v.x ^ tag) & 1) {
    asm volatile("ld.relaxed.gpu.global.v4.b32 {%0,%1,%2,%3}, [%4];" : "=r"(v.x), "=r"(v.y), "=r"(v.z), "=r"(v.w) : "l"(p) : "memory");
    if (++n > 2000000) __trap();
  }
}
template <int N> __device__ __forceinline__ void cs(int n, float& c, float& s) {
  n = ((n + N / 2) & (N - 1)) - N / 2;
  float a = (float)n * (6.283185307179586f / N);
  c = __cosf(a); s = __sinf(a);
}
constexpr float ALPHA = 1.13288f;
struct FftC { uint32_t a[4][4], b[8][2]; float tc[2][4], ts[2][4]; };
constexpr uint32_t NEG = 0x80008000u;

__device__ __forceinline__ void fft_s1(const FftC& K, const uint32_t (&in)[4][2], float (&cr)[2][4], float (&ci)[2][4]) {
#pragma unroll
  for (int h = 0; h < 2; h++) { mma0(cr[h], K.a[0], in[0][h], in[1][h]); mma0(ci[h], K.a[1], in[0][h], in[1][h]); }
#pragma unroll
  for (int h = 0; h < 2; h++) { mmac(cr[h], cr[h], K.a[2], in[2][h], in[3][h]); mmac(ci[h], ci[h], K.a[3], in[2][h], in[3][h]); }
}
__device__ __forceinline__ void fft_s2(const FftC& K, const float (&cr)[2][4], const float (&ci)[2][4], float (&o)[4][4]) {
  uint32_t a[2][4];
#pragma unroll
  for (int h = 0; h < 2; h++)
#pragma unroll
    for (int i = 0; i < 4; i++) {
      float xr = cr[i & 1][2 * h + (i >> 1)], xi = ci[i & 1][2 * h + (i >> 1)];
      a[i >> 1][2 * (i & 1) + h] = pk(xr * K.tc[h][i] + xi * K.ts[h][i], xi * K.tc[h][i] - xr * K.ts[h][i]);
    }
#pragma unroll
  for (int j = 0; j < 4; j++) mma0(o[j], a[0], K.b[j][0], K.b[j][1]);
#pragma unroll
  for (int j = 0; j < 4; j++) mmac(o[j], o[j], a[1], K.b[4 + j][0], K.b[4 + j][1]);
}
__device__ __forceinline__ int zphys(int k) { return k + 8 * (k >> 5); }
__device__ __forceinline__ float gelu(float u) {
  float z = u * (0.7978845608028654f + 0.035677408136300125f * u * u), th;
  asm("tanh.approx.f32 %0, %1;" : "=f"(th) : "f"(z));
  float hu = 0.5f * u;
  return fmaf(hu, th, hu);
}

extern "C" __global__ void __cluster_dims__(2, 1, 1) __launch_bounds__(384, 1)
fused_kernel(const uint2* __restrict__ x, Scratch* scr, const unsigned short* __restrict__ wr, const unsigned short* __restrict__ wi,
             const uint32_t* __restrict__ b1, const unsigned short* __restrict__ b2, uint4* __restrict__ out, const char* __restrict__ w2,
             const __grid_constant__ CUtensorMap tmW1, const __grid_constant__ CUtensorMap tmW2) {
  extern __shared__ __align__(1024) char smem[];
  const uint32_t sb = (uint32_t)__cvta_generic_to_shared(smem);
  const uint32_t mb = sb + BAR_OFF;
  const int b = blockIdx.x, rank = b & 1, pr = b >> 1, dt = pr & 3, ot = pr >> 2;
  const int warp = __shfl_sync(0xffffffffu, threadIdx.x >> 5, 0), lane = threadIdx.x & 31;
  const int g = lane >> 2, t = lane & 3;

  if (warp < 8) {
    const int tid = threadIdx.x;
    uint32_t xw[2][4][2];
    {
      const uint2* xp = x + (size_t)(256 * warp + 2 * b) * 128 + 8 * t + g;
#pragma unroll
      for (int a = 0; a < 2; a++)
#pragma unroll
        for (int j = 0; j < 4; j++) { uint2 v = __ldg(xp + a * 128 + 32 * j); xw[a][j][0] = v.x; xw[a][j][1] = v.y; }
    }
    STAMP(0);
    asm volatile("barrier.cluster.arrive.relaxed.aligned;" ::: "memory");
    const int rep = ot & (NREP - 1);
    const unsigned base = __ldcg(&g_cnt[(1 * NREP + rep) * 64]);
    const uint32_t tag = (~base >> 7) & 1;
    FftC K;
    {
      float c, s;
#pragma unroll
      for (int h = 0; h < 2; h++)
#pragma unroll
        for (int j = 0; j < 2; j++) {
          cs<16>((2 * g + h) * (t + 4 * j), c, s);
          const uint32_t re = pk(ALPHA * c, ALPHA * s), im = pk(-ALPHA * s, ALPHA * c);
          K.a[0][2 * j + h] = re; K.a[1][2 * j + h] = im; K.a[2][2 * j + h] = pin(h ? re ^ NEG : re); K.a[3][2 * j + h] = pin(h ? im ^ NEG : im);
        }
#pragma unroll
      for (int i = 0; i < 4; i++) {
        cs<16>((4 * t + i) * (g >> 1) + 4 * (g & 1), c, s);
        const uint32_t P = pk(ALPHA * c, ALPHA * s), Q = pk(-ALPHA * s, ALPHA * c);
#pragma unroll
        for (int jj = 0; jj < 4; jj++) { const uint32_t v = ((i * jj) & 1 ? Q : P) ^ ((i * jj) & 2 ? NEG : 0u); K.b[4 * (i >> 1) + jj][i & 1] = jj ? pin(v) : v; }
      }
#pragma unroll
      for (int h = 0; h < 2; h++)
#pragma unroll
        for (int i = 0; i < 4; i++) {
          cs<256>((2 * g + h) * (4 * t + i), c, s);
          K.tc[h][i] = c * (1.f / (ALPHA * ALPHA)); K.ts[h][i] = s * (1.f / (ALPHA * ALPHA));
        }
    }
    const int key = ((b >> 3) & 3) * 2 + (b & 1);
    const uint32_t zb = sb + XCH_OFF;
    float mean[2];
    {
      uint32_t a8[2][4], a8c[2][4], a8n[2][4]; float vc[4], vs[4];
#pragma unroll
      for (int a = 0; a < 2; a++)
#pragma unroll
        for (int u = 0; u < 4; u++) {
          float c, s; cs<2048>(g * (256 * (t + 4 * (u >> 1)) + 2 * b + a), c, s);
          a8[a][u] = u & 1 ? pk(-s, c) : pk(c, s);
          a8c[a][u] = pin(a8[a][u] ^ 0x80000000u); a8n[a][u] = pin(a8[a][u] ^ 0x00008000u);
        }
#pragma unroll
      for (int i = 0; i < 4; i++) { cs<512>(16 * warp + 8 * (i >> 1) + 2 * t + (i & 1) + 128, vc[i], vs[i]); vc[i] = pinf(vc[i]); vs[i] = pinf(vs[i]); }
#pragma unroll
      for (int a = 0; a < 2; a++) {
        float cr[2][4], ci[2][4], o[4][4];
        if (a == 0) { STAMP(13); if (xw[0][0][0] == 0x12345678u && xw[1][3][1] == 0x12345679u) STAMP(31); STAMP(14); }
        fft_s1(K, xw[a], cr, ci);
        if (FILT_LATE && a == 0 && warp == 0) asm volatile("bar.arrive 3, 160;" :: "f"(cr[0][0]) : "memory");
        float sm = ((cr[0][0] + cr[0][1]) + (cr[1][0] + cr[1][1])) + ((ci[0][0] + ci[0][1]) + (ci[1][0] + ci[1][1]));
        sm += __shfl_xor_sync(0xffffffffu, sm, 1); sm += __shfl_xor_sync(0xffffffffu, sm, 2);
        sm = g == 0 ? sm * (1.f / 32.f) : 0.f;
#pragma unroll
        for (int h = 0; h < 2; h++) { cr[h][0] -= sm; cr[h][1] -= sm; ci[h][0] -= sm; ci[h][1] -= sm; }
        mean[a] = __shfl_sync(0xffffffffu, sm, 0) * (1.f / (16.f * 1.1328125f));
        float q = 0.f, q2 = 0.f;
#pragma unroll
        for (int i = 0; i < 4; i++) { q = fmaf(cr[0][i], cr[0][i], q); q2 = fmaf(cr[1][i], cr[1][i], q2); q = fmaf(ci[0][i], ci[0][i], q); q2 = fmaf(ci[1][i], ci[1][i], q2); }
        q += q2;
#pragma unroll
        for (int m = 1; m < 32; m <<= 1) q += __shfl_xor_sync(0xffffffffu, q, m);
        float r = rsqrtf(q * (1.f / (512.f * 16.f * ALPHA * ALPHA)) + 1e-5f) * 4.76837158203125e-7f;
        fft_s2(K, cr, ci, o);
#pragma unroll
        for (int j = 0; j < 4; j++)
          sts64(zb + ((a * 8 + warp) * ZROW + zphys(16 * t + 64 * j) + 2 * g) * 4, pk(o[j][0] * r, o[j][1] * r), pk(o[j][2] * r, o[j][3] * r));
      }
      STAMP(15);
      wbar();
      uint4* tp = g_T1 + (size_t)(g * 16 + warp) * 1024 + b * 8;
#pragma unroll
      for (int nt = 0; nt < 2; nt++) {
        const int k = 16 * warp + 8 * nt + g, km = k == 0 ? 128 : 256 - k;
        uint32_t lo[4], hi[4];
#pragma unroll
        for (int a = 0; a < 2; a++) {
          const uint32_t rb = zb + (a * 8 + t) * ZROW * 4;
          float A[4], S[4], D[4];
          const uint32_t m0 = lds32(rb + zphys(km) * 4), m1 = lds32(rb + (4 * ZROW + zphys(km)) * 4);
          mma0(A, a8[a], lds32(rb + zphys(k) * 4), lds32(rb + (4 * ZROW + zphys(k)) * 4));
          mmac(S, A, a8c[a], m0, m1);
          mmac(D, A, a8n[a], m0, m1);
#pragma unroll
          for (int e = 0; e < 2; e++) {
            const float c = vc[2 * nt + e], s = vs[2 * nt + e];
            float lr = fmaf(D[2 + e], s, fmaf(D[e], c, S[e])), li = fmaf(-D[e], s, fmaf(D[2 + e], c, S[2 + e]));
            float hr = fmaf(2.f, S[e], -lr), hii = fmaf(2.f, S[2 + e], -li);
            if (nt == 0 && e == 0) {
              const bool sp = warp == 0 && t == 0;
              lr = sp ? S[0] - D[0] : lr; li = sp ? S[2] - D[2] : li;
              hr = sp ? 2.f * (A[0] - A[2]) : hr; hii = sp ? 2.f * (A[0] + A[2]) : hii;
            }
            lo[2 * a + e] = pk(lr, li); hi[2 * a + e] = pk(hr, hii);
          }
        }
        const int w = (t + 4 * nt) ^ key;
        tp[w] = make_uint4((lo[0] & ~1u) | tag, lo[1], lo[2], lo[3]);
        tp[8 * 1024 + w] = make_uint4((hi[0] & ~1u) | tag, hi[1], hi[2], hi[3]);
      }
      wbar();
      STAMP(1);
      if (warp == 0) cnt_arrive(scr, 0, lane);
    }
    {
      const uint32_t off = (8 * t + g) * 128 + ((warp ^ (2 * t + (g & 1))) << 4);
      asm volatile("barrier.cluster.wait.aligned;" ::: "memory");
      mbar_wait(mb + MB_FILT * 8, 0);
      if (tid == 0) cnt_wait<false>(scr, 0, rep, base + NCTA);
      wbar();
#pragma unroll
      for (int j = 0; j < 4; j++)
        asm volatile("cp.async.cg.shared.global [%0], [%1], 16;" :: "r"(zb + j * 4096 + tid * 16), "l"(g_T1 + (size_t)b * 1024 + j * 256 + tid) : "memory");
      STAMP(2);
      uint32_t in[2][4][2], fw[2][4][2];
#pragma unroll
      for (int j = 0; j < 4; j++) {
        uint4 v = lds128(sb + FILT_OFF + off + j * 4096);
        fw[0][j][0] = v.x; fw[1][j][0] = v.y; fw[0][j][1] = v.z; fw[1][j][1] = v.w;
      }
      asm volatile("cp.async.wait_all;" ::: "memory");
      wbar();
      STAMP(3);
      uint4 iv[4];
#pragma unroll
      for (int j = 0; j < 4; j++) iv[j] = lds128(zb + off + j * 4096);
      if (((iv[0].x ^ tag) | (iv[1].x ^ tag) | (iv[2].x ^ tag) | (iv[3].x ^ tag)) & 1) {
#pragma unroll
        for (int j = 0; j < 4; j++) tag_check(iv[j], g_T1 + (size_t)b * 1024 + j * 256 + (off >> 4), tag);
      }
      __syncwarp();
#pragma unroll
      for (int j = 0; j < 4; j++) { in[0][j][0] = iv[j].x; in[1][j][0] = iv[j].y; in[0][j][1] = iv[j].z; in[1][j][1] = iv[j].w; }
#pragma unroll
      for (int sg = 0; sg < 2; sg++) {
        float cr[2][4], ci[2][4], o[4][4];
        fft_s1(K, in[sg], cr, ci);
        fft_s2(K, cr, ci, o);
#pragma unroll
        for (int j = 0; j < 4; j++)
#pragma unroll
          for (int h = 0; h < 2; h++) {
            float fr = blo(fw[sg][j][h]), fi = bhi(fw[sg][j][h]), xr = o[j][2 * h], xi = o[j][2 * h + 1];
            in[sg][j][h] = pk(xr * fi + xi * fr, xr * fr - xi * fi);
          }
        fft_s1(K, in[sg], cr, ci);
        fft_s2(K, cr, ci, o);
#pragma unroll
        for (int j = 0; j < 4; j++) { in[sg][j][0] = pk(o[j][0], o[j][1]); in[sg][j][1] = pk(o[j][2], o[j][3]); }
      }
#pragma unroll
      for (int j = 0; j < 4; j++) sts128(zb + off + j * 4096, make_uint4((in[0][j][0] & ~1u) | tag, in[1][j][0], in[0][j][1], in[1][j][1]));
      STAMP(16);
      wbar();
#pragma unroll
      for (int j = 0; j < 4; j++) g_T2[(size_t)b * 1024 + j * 256 + tid] = lds128(zb + j * 4096 + tid * 16);
      wbar();
      STAMP(4);
      if (warp == 0) cnt_arrive(scr, 1, lane);
    }
    {
      uint32_t a8[2][4], a8n[2][4]; float vc[4], vs[4];
#pragma unroll
      for (int a = 0; a < 2; a++)
#pragma unroll
        for (int u = 0; u < 4; u++) {
          float c, s; cs<2048>((t + 4 * (u >> 1)) * (256 * g + 2 * b + a), c, s);
          a8[a][u] = u & 1 ? pk(-s, c) : pk(c, s);
          a8n[a][u] = pin(a8[a][u] ^ NEG);
        }
#pragma unroll
      for (int i = 0; i < 4; i++) { cs<512>(16 * warp + 4 * t + i + 128, vc[i], vs[i]); vc[i] = pinf(vc[i]); vs[i] = pinf(vs[i]); }
      if (tid == 0) cnt_wait<false>(scr, 1, rep, base + NCTA);
      wbar();
      STAMP(5);
      const uint4* tp = g_T2 + (size_t)(t * 16 + warp) * 1024 + b * 8 + (g ^ key);
      uint4 L0 = ldcg128(tp), L1 = ldcg128(tp + 64 * 1024), H0 = ldcg128(tp + 8 * 1024), H1 = ldcg128(tp + 72 * 1024);
      if (((L0.x ^ tag) | (L1.x ^ tag) | (H0.x ^ tag) | (H1.x ^ tag)) & 1) {
        tag_check(L0, tp, tag); tag_check(L1, tp + 64 * 1024, tag); tag_check(H0, tp + 8 * 1024, tag); tag_check(H1, tp + 72 * 1024, tag);
      }
      __syncwarp();
      STAMP(17);
      const uint32_t l0[4] = {L0.x, L0.y, L0.z, L0.w}, l1[4] = {L1.x, L1.y, L1.z, L1.w}, h0[4] = {H0.x, H0.y, H0.z, H0.w}, h1[4] = {H1.x, H1.y, H1.z, H1.w};
#pragma unroll
      for (int a = 0; a < 2; a++) {
        uint32_t zf[4], zm[4];
#pragma unroll
        for (int sg = 0; sg < 2; sg++) {
          float A[4], S[4], D[4];
          mma0(A, a8[a], l0[2 * a + sg], l1[2 * a + sg]);
          mmac(S, A, a8[a], h0[2 * a + sg], h1[2 * a + sg]);
          mmac(D, A, a8n[a], h0[2 * a + sg], h1[2 * a + sg]);
#pragma unroll
          for (int e = 0; e < 2; e++) {
            const int i = 2 * e + sg;
            float fr = fmaf(-D[e], vs[i], fmaf(D[2 + e], vc[i], S[2 + e])), fi = fmaf(D[2 + e], vs[i], fmaf(D[e], vc[i], S[e]));
            float mr = fmaf(2.f, S[2 + e], -fr), mi = fmaf(-2.f, S[e], fi);
            if (i == 0) {
              const bool sp = warp == 0 && t == 0;
              fr = sp ? S[2] - A[2] : fr; fi = sp ? A[2] - S[2] : fi;
              mr = sp ? 2.f * A[2] : mr; mi = sp ? -2.f * A[0] : mi;
            }
            zf[i] = pk(fi, fr); zm[i] = pk(mi, mr);
          }
        }
        const uint32_t rb = zb + (a * 8 + g) * ZROW * 4;
        const int k0 = 16 * warp + 4 * t;
        sts128(rb + zphys(k0) * 4, make_uint4(zf[0], zf[1], zf[2], zf[3]));
        sts32(rb + zphys(k0 == 0 ? 128 : 256 - k0) * 4, zm[0]);
        sts32(rb + zphys(255 - k0) * 4, zm[1]);
        sts32(rb + zphys(254 - k0) * 4, zm[2]);
        sts32(rb + zphys(253 - k0) * 4, zm[3]);
      }
      STAMP(18);
      wbar();
#pragma unroll
      for (int a = 0; a < 2; a++) {
        uint32_t in[4][2];
#pragma unroll
        for (int j = 0; j < 4; j++) { uint2 v = lds64(zb + ((a * 8 + warp) * ZROW + zphys(16 * t + 64 * j) + 2 * g) * 4); in[j][0] = v.x; in[j][1] = v.y; }
        float cr[2][4], ci[2][4], o[4][4];
        fft_s1(K, in, cr, ci);
        fft_s2(K, cr, ci, o);
        float s1 = 0.f, s2 = 0.f;
#pragma unroll
        for (int j = 0; j < 4; j++) {
          uint32_t hw[2];
#pragma unroll
          for (int h = 0; h < 2; h++) {
            asm("add.rn.bf16x2 %0, %1, %2;" : "=r"(hw[h]) : "r"(xw[a][j][h]), "r"(pk(o[j][2 * h + 1], o[j][2 * h])));
            float u0 = blo(hw[h]) - mean[a], u1 = bhi(hw[h]) - mean[a];
            o[j][2 * h] = u0; o[j][2 * h + 1] = u1;
            s1 = fmaf(u0, u0, s1); s2 = fmaf(u1, u1, s2);
          }
        }
        s2 += s1;
#pragma unroll
        for (int m = 1; m < 32; m <<= 1) s2 += __shfl_xor_sync(0xffffffffu, s2, m);
        const float var = s2 * (1.f / 512.f), r1 = rsqrtf(var + 1e-5f);
        const float r = r1 * rsqrtf(var * r1 * r1 + 1e-5f);
        if (lane == 0) g_st[256 * warp + 2 * b + a] = make_float2(1.f / r, mean[a]);
        char* np = (char*)g_Hn + (size_t)b * 4096 + (t >> 1) * 2048 + a * 1024 + warp * 128 + ((((t & 1) * 4 + (g >> 1)) ^ warp ^ (b >> 6)) << 4) + (g & 1) * 8;
#pragma unroll
        for (int j = 0; j < 4; j++)
          *(uint2*)(np + (size_t)j * 128 * 4096) = make_uint2(pk(o[j][0] * r, o[j][1] * r), pk(o[j][2] * r, o[j][3] * r));
      }
      STAMP(19);
      asm volatile("fence.proxy.async.shared::cta;" ::: "memory");
      wbar();
      STAMP(6);
      if (warp == 0) { fence_gpu(); cnt_arrive(scr, 2 + (b >> 6), lane); STAMP(25); }
      if (tid == 32) { sts32(sb + BASE_OFF, base); mbar_arrive(mb + MB_P3DONE * 8); }
    }
    const int wg = warp >> 2;
    const uint32_t peer_sb = mapa(sb, rank ^ 1);
    {
      float acc[44];
#pragma unroll
      for (int j = 0; j < 11; j++) {
        const uint32_t bw = __ldg(b1 + min(11 * ot + j, 171) * 4 + t);
        acc[4 * j] = blo(bw); acc[4 * j + 1] = bhi(bw); acc[4 * j + 2] = 0.f; acc[4 * j + 3] = 0.f;
      }
      const uint32_t da0 = desc_lo(sb + RING_OFF + wg * 2048, 0);
      uint32_t da = da0, db = desc_lo(sb, 1408), bar = mb;
      mbar_wait(mb + MB_W1 * 8, 0);
#pragma unroll 1
      for (int i = 0; i < 32; i++) {
        mbar_wait(bar + MB_FULL * 8, 0);
        if (i == 0) STAMP(7);
        asm volatile("wgmma.fence.sync.aligned;" ::: "memory");
        wgmma_n88_ss<1, 1, HI_SW128, HI_NOSW>(acc, da, db, 1);
        wgmma_n88_ss<1, 1, HI_SW128, HI_NOSW>(acc, da + 256, db + 176, 1);
        asm volatile("wgmma.commit_group.sync.aligned;" ::: "memory");
        da = da == da0 + 5 * 512 ? da0 : da + 512; db += 352;
        asm volatile("wgmma.wait_group.sync.aligned 1;" ::: "memory");
        if ((tid & 127) == 0) { if (i > 0) mbar_arrive(bar + (MB_EMPTY - 1) * 8); if (i == 4) mbar_arrive_cluster(peer_sb + BAR_OFF + MB_PEER1 * 8); }
        bar += 8;
      }
      asm volatile("wgmma.wait_group.sync.aligned 0;" ::: "memory");
#pragma unroll
      for (int i = 0; i < 44; i++) asm volatile("" : "+f"(acc[i]) :: "memory");
      if ((tid & 127) == 0) mbar_arrive(mb + (MB_EMPTY + 31) * 8);
      STAMP(8);
      mbar_wait_cluster(mb + MB_PEER1 * 8, 0);
#pragma unroll
      for (int j = 0; j < 3; j++)
        st_async4(peer_sb + j * 4096 + tid * 16, pk(acc[16 * j + 2], acc[16 * j + 3]), pk(acc[16 * j + 6], acc[16 * j + 7]), pk(acc[16 * j + 10], acc[16 * j + 11]),
                  j < 2 ? pk(acc[16 * j + 14], acc[16 * j + 15]) : 0u, peer_sb + BAR_OFF + MB_X1 * 8);
      const int uo = (4 * (warp >> 1) + (g >> 1)) * 32 + (2 * (2 * (warp & 1) + rank) + (g & 1)) * 4 + t;
      uint32_t* const ub = (uint32_t*)g_U + ((size_t)dt * 172 + 11 * ot) * 512;
      uint32_t *upa = ub + (uo ^ (ot >= 8 ? 256 : 0)), *upb = ub + (uo ^ (ot >= 7 ? 256 : 0));
      STAMP(20);
      mbar_wait_cluster(mb + MB_X1 * 8, 0);
      STAMP(21);
      uint32_t pv[12];
#pragma unroll
      for (int j = 0; j < 3; j++) { const uint4 v = lds128(sb + j * 4096 + tid * 16); pv[4 * j] = v.x; pv[4 * j + 1] = v.y; pv[4 * j + 2] = v.z; pv[4 * j + 3] = v.w; }
#pragma unroll
      for (int j = 0; j < 11; j++) {
        uint32_t v = pk(gelu(acc[4 * j] + blo(pv[j])), gelu(acc[4 * j + 1] + bhi(pv[j])));
        if (j < 7 || ot < 15) (j < 9 ? upa : upb)[j * 512] = v;
      }
      STAMP(22);
      asm volatile("fence.proxy.async.shared::cta;" ::: "memory");
      wbar();
      STAMP(9);
      if (warp == 0) { fence_gpu(); cnt_arrive(scr, 4 + dt, lane); STAMP(26); }
      if (tid == 32) mbar_arrive(mb + MB_X1DONE * 8);
    }
    {
      const int srow = 128 * ot + 16 * warp + g, oo = srow * 64 + dt * 16 + 8 * rank + t;
      float acc[64];
      const uint32_t da0 = desc_lo(sb + wg * 4096, 0), db0 = desc_lo(sb + RING_OFF, 2048);
      uint32_t da = da0 + 3 * 512, db = db0 + (32 % NST) * 512, bar = mb;
#pragma unroll
      for (int u = 0; u < 2; u++) {
        const int sr = srow + 8 * u, s1 = ot >> 1;
        const float2 st = __ldcg(g_st + sr);
        const float off = st.y + __uint_as_float((uint32_t)__ldg(b2 + sr) << 16);
#pragma unroll
        for (int jj = 0; jj < 2; jj++) {
          const uint4 v = ldcg128(g_Hn + (dt * 128 + ((sr & 255) >> 1)) * 256 + rank * 128 + (sr & 1) * 64 + s1 * 8 + ((4 * jj + t) ^ s1 ^ (ot & 1)));
          const uint32_t w[4] = {v.x, v.y, v.z, v.w};
#pragma unroll
          for (int j = 0; j < 4; j++) { acc[16 * jj + 4 * j + 2 * u] = fmaf(blo(w[j]), st.x, off); acc[16 * jj + 4 * j + 2 * u + 1] = fmaf(bhi(w[j]), st.x, off); }
        }
      }
#pragma unroll
      for (int j = 32; j < 64; j++) acc[j] = 0.f;
#pragma unroll 1
      for (int i = 0; i < 21; i++) {
        mbar_wait(bar + MB_W2 * 8, 0);
        mbar_wait(bar + (MB_FULL + 32) * 8, 0);
        if (i == 0) STAMP(10);
        asm volatile("wgmma.fence.sync.aligned;" ::: "memory");
        wgmma_n128_ss<1, 0, HI_SW128, HI_NOSW>(acc, da, db, 1);
        wgmma_n128_ss<1, 0, HI_SW128, HI_NOSW>(acc, da + 128, db + 256, 1);
        asm volatile("wgmma.commit_group.sync.aligned;" ::: "memory");
        da = i == 18 ? da0 : da + 512; db = db == db0 + 5 * 512 ? db0 : db + 512;
        asm volatile("wgmma.wait_group.sync.aligned 1;" ::: "memory");
        if ((tid & 127) == 0) { if (i > 0) mbar_arrive(bar + (MB_EMPTY + 31) * 8); if (i == 4) mbar_arrive_cluster(peer_sb + BAR_OFF + MB_PEER2 * 8); }
        bar += 8;
      }
      mbar_wait(bar + MB_W2 * 8, 0);
      mbar_wait(bar + (MB_FULL + 32) * 8, 0);
      asm volatile("wgmma.fence.sync.aligned;" ::: "memory");
      wgmma_n128_ss<1, 0, HI_SW128, HI_NOSW>(acc, da, db, 1);
      asm volatile("wgmma.commit_group.sync.aligned;" ::: "memory");
      asm volatile("wgmma.wait_group.sync.aligned 0;" ::: "memory");
#pragma unroll
      for (int i = 0; i < 64; i++) asm volatile("" : "+f"(acc[i]) :: "memory");
      STAMP(11);
      mbar_wait_cluster(mb + MB_PEER2 * 8, 0);
#pragma unroll
      for (int j = 0; j < 4; j++) {
        const int o = 32 + 16 * (j >> 1) + 2 * (j & 1);
        st_async4(peer_sb + 3 * 8192 + j * 4096 + tid * 16, pk(acc[o], acc[o + 1]), pk(acc[o + 4], acc[o + 5]), pk(acc[o + 8], acc[o + 9]), pk(acc[o + 12], acc[o + 13]),
                  peer_sb + BAR_OFF + MB_X2 * 8);
      }
      STAMP(23);
      mbar_wait_cluster(mb + MB_X2 * 8, 0);
      STAMP(24);
#pragma unroll
      for (int j = 0; j < 4; j++) {
        const int o = 16 * (j >> 1) + 2 * (j & 1);
        const uint4 v = lds128(sb + 3 * 8192 + j * 4096 + tid * 16);
        out[oo + 4 * (j >> 1) + 512 * (j & 1)] = make_uint4(pk(acc[o] + blo(v.x), acc[o + 1] + bhi(v.x)), pk(acc[o + 4] + blo(v.y), acc[o + 5] + bhi(v.y)),
                                                            pk(acc[o + 8] + blo(v.z), acc[o + 9] + bhi(v.z)), pk(acc[o + 12] + blo(v.w), acc[o + 13] + bhi(v.w)));
      }
      STAMP(12);
    }
  } else {
    const int pw = warp - 8;
    if (pw < 3 && elect()) {
#pragma unroll
      for (int i = 0; i < 57; i++) mbar_init(mb + (pw * 57 + i) * 8, pw == 2 ? 2 : 1);
      if (pw == 1) { mbar_expect(mb + MB_X1 * 8, 12288); mbar_expect(mb + MB_X2 * 8, 16384); }
      asm volatile("fence.mbarrier_init.release.cluster;" ::: "memory");
    }
    __syncwarp();
    STAMP(0);
    asm volatile("bar.sync 2, 128;" ::: "memory");
    asm volatile("barrier.cluster.arrive.relaxed.aligned;" ::: "memory");
    auto w1_issue = [&](int i) {
      if (elect()) { mbar_expect(mb + (MB_W1T + i) * 8, 5632); tma3d(sb + i * 5632, &tmW1, 88 * ot, 0, 128 * rank + 4 * i, mb + (MB_W1T + i) * 8); }
      __syncwarp();
    };
    if (!W1_LATE && pw < W1_WARPS) for (int i = 0; i < W1_DEPTH; i++) w1_issue(pw + W1_WARPS * i);
    {
      const int j1 = b >> 4, q = b & 15, slot = lane & 15, h = lane >> 4;
      const bool hi = q >= 8;
      const int k = 16 * (q & 7) + slot, col = hi ? 256 - k : (k == 0 ? 128 : k);
      const int j0 = j1 + 8 * h + 512 * pw, o0 = (hi ? 2048 - 31 * 16 - j0 : j0) * DF + col, o31 = hi && j0 == 0 ? o0 - 2048 * DF : o0;
      uint32_t vr[32], vi[32];
      if (FILT_LATE) { asm volatile("bar.sync 3, 160;" ::: "memory"); asm volatile("" : "+l"(wr), "+l"(wi)); }
#pragma unroll
      for (int n = 0; n < 32; n++) { vr[n] = __ldg(wr + (n == 31 ? o31 : o0) + n * 16 * DF); vi[n] = __ldg(wi + (n == 31 ? o31 : o0) + n * 16 * DF); }
      const uint32_t f0 = sb + FILT_OFF + pw * 4096 + (hi ? 31 * 128 : 0) + h * 8 + (slot & 1) * 4, sw = ((slot >> 1) ^ (hi ? 7 : 0)) << 4;
      const int st = hi ? -128 : 128;
#pragma unroll
      for (int n = 0; n < 32; n++)
        sts32(f0 + n * st + (sw ^ ((((n >> 3) & 3) * 2 + (n & 1)) << 4)), __byte_perm(vr[n], vi[n], 0x5410) ^ (hi ? 0x80000000u : 0u));
      asm volatile("bar.sync 2, 128;" ::: "memory");
      if (threadIdx.x == 352) mbar_arrive(mb + MB_FILT * 8);
    }
    __syncwarp();
    STAMP(1);
    {
      if (W1_LATE && pw < W1_WARPS) for (int i = 0; i < W1_DEPTH; i++) w1_issue(pw + W1_WARPS * i);
      const uint32_t rd = ((lane & 7) * 11 + (lane >> 3)) * 16, wr = lane * 16;
#pragma unroll 1
      for (int box = pw < W1_WARPS ? pw : 32; box < W1_END; box += W1_WARPS) {
        mbar_wait(mb + (MB_W1T + box) * 8, 0);
        if (box + W1_WARPS * W1_DEPTH < 32) w1_issue(box + W1_WARPS * W1_DEPTH);
        const uint32_t p = sb + box * 5632;
        uint4 v[4][3];
#pragma unroll
        for (int n = 0; n < 4; n++) { v[n][0] = lds128(p + n * 1408 + rd); v[n][1] = lds128(p + n * 1408 + rd + 64); if (lane < 24) v[n][2] = lds128(p + n * 1408 + rd + 128); }
        __syncwarp();
#pragma unroll
        for (int n = 0; n < 4; n++) { sts128(p + n * 1408 + wr, v[n][0]); sts128(p + n * 1408 + wr + 512, v[n][1]); if (lane < 24) sts128(p + n * 1408 + wr + 1024, v[n][2]); }
      }
      if (lane == 0) asm volatile("cp.async.bulk.prefetch.L2.global [%0], %1;" :: "l"(w2 + (size_t)(b * 4 + pw) * 11008), "r"(11008) : "memory");
      asm volatile("fence.proxy.async.shared::cta;" ::: "memory");
      asm volatile("bar.sync 2, 128;" ::: "memory");
      if (threadIdx.x == 352) mbar_arrive(mb + MB_W1 * 8);
    }
    STAMP(2);
    asm volatile("barrier.cluster.wait.aligned;" ::: "memory");
    if (pw == 3) {
#pragma unroll 1
      for (int n = 0; n < 22; n++) {
        if (n < W2_PRE) mbar_wait(mb + (MB_EMPTY + min(31, max(((n + 4) * 16 + 10) / 11 - 1, W2_START + n * W2_NUM / W2_DEN))) * 8, 0);
        else { mbar_wait(mb + MB_X1DONE * 8, 0); if (W2_PACE) mbar_wait(mb + (MB_FULL + 32 - W2_PRE + n) * 8, 0); }
        if (elect()) { mbar_expect(mb + (MB_W2 + n) * 8, 8192); tma3d(sb + (n < 19 ? n + 3 : n - 19) * 8192, &tmW2, 0, 688 * rank + 32 * n, 2 * ot, mb + (MB_W2 + n) * 8); }
      }
    } else {
      int i = pw;
      uint32_t dst = sb + RING_OFF + pw * 8192;
      const uint32_t dsum = 2 * dst + 3 * 8192;
      const char* src = (const char*)g_Hn + ((size_t)dt * 128 + 64 * rank) * 4096;
#pragma unroll 1
      for (int gm = 0; gm < 2; gm++) {
        if (pw == 0) {
          mbar_wait(mb + (gm ? MB_X1DONE : MB_P3DONE) * 8, 0);
          STAMP(3 + 2 * gm);
          if (lane == 0) cnt_wait<true>(scr, gm ? 4 + dt : 2 + rank, ot & (NREP - 1), ((lds32(sb + BASE_OFF) >> 1) + 64) >> gm);
        }
        asm volatile("bar.sync 2, 96;" ::: "memory");
        STAMP(4 + 2 * gm);
        asm volatile("fence.proxy.async.global;" ::: "memory");
#pragma unroll 1
        for (; i < (gm ? 54 : 32); i += 3) {
          if (i >= NST) mbar_wait(mb + (MB_EMPTY - NST + i) * 8, 0);
          if (elect()) {
            const int bytes = i < 53 ? 8192 : 4096;
            mbar_expect(mb + (MB_FULL + i) * 8, bytes); bulk_ld(dst, src + i * 8192, bytes, mb + (MB_FULL + i) * 8);
          }
          dst = dsum - dst;
        }
        src = (const char*)g_U + ((size_t)dt * 172 + 86 * rank) * 2048 - 32 * 8192;
      }
      STAMP(7);
    }
  }
}

typedef CUresult (*EncodeFn)(CUtensorMap*, CUtensorMapDataType, cuuint32_t, void*, const cuuint64_t*, const cuuint64_t*, const cuuint32_t*,
                             const cuuint32_t*, CUtensorMapInterleave, CUtensorMapSwizzle, CUtensorMapL2promotion, CUtensorMapFloatOOBfill);

extern "C" void kernel_launch(void* const* d_in, const int* in_sizes, int n_in, void* d_out, int out_size) {
  static EncodeFn enc = nullptr;
  static void* scr = nullptr;
  if (!enc) {
    void* fn = nullptr; cudaDriverEntryPointQueryResult st;
    cudaGetDriverEntryPoint("cuTensorMapEncodeTiled", &fn, cudaEnableDefault, &st);
    enc = (EncodeFn)fn;
    cudaGetSymbolAddress(&scr, g_scr);
    cudaFuncSetAttribute(fused_kernel, cudaFuncAttributeMaxDynamicSharedMemorySize, SMEM_BYTES);
  }
  CUtensorMap tm, tm1;
  {
    cuuint64_t dims[3] = {(cuuint64_t)F_, 8, 256}, strides[2] = {(cuuint64_t)256 * F_ * 2, F_ * 2};
    cuuint32_t box[3] = {88, 8, 4}, es[3] = {1, 1, 1};
    enc(&tm1, CU_TENSOR_MAP_DATA_TYPE_BFLOAT16, 3, d_in[4], dims, strides, box, es, CU_TENSOR_MAP_INTERLEAVE_NONE, CU_TENSOR_MAP_SWIZZLE_NONE,
        W1_PROMO, CU_TENSOR_MAP_FLOAT_OOB_FILL_NONE);
  }
  {
    cuuint64_t dims[3] = {64, (cuuint64_t)F_, S_ / 64}, strides[2] = {S_ * 2, 128};
    cuuint32_t box[3] = {64, 32, 2}, es[3] = {1, 1, 1};
    enc(&tm, CU_TENSOR_MAP_DATA_TYPE_BFLOAT16, 3, d_in[6], dims, strides, box, es, CU_TENSOR_MAP_INTERLEAVE_NONE, CU_TENSOR_MAP_SWIZZLE_128B,
        CU_TENSOR_MAP_L2_PROMOTION_L2_256B, CU_TENSOR_MAP_FLOAT_OOB_FILL_NONE);
  }
  fused_kernel<<<NCTA, 384, SMEM_BYTES, cudaStreamPerThread>>>((const uint2*)d_in[0], (Scratch*)scr, (const unsigned short*)d_in[1], (const unsigned short*)d_in[2],
                                          (const uint32_t*)d_in[5], (const unsigned short*)d_in[7], (uint4*)d_out, (const char*)d_in[6], tm1, tm);
}
```

```cpp
#include <cuda_runtime.h>
#include <cuda.h>
#include <cuda_bf16.h>
#include <stdint.h>
#define W1_LATE 1
#define W1_PROMO CU_TENSOR_MAP_L2_PROMOTION_NONE
#define W2_NUM 1
#define W2_DEN 1
#define PF_W1 0
#define W1_DEPTH 1
#define W1_WARPS 4
#define W2_PRE 12
#define W2_PACE 1
#define FILT_LATE 0
#define W1_END 32
template<int TA, int TB, uint32_t HA, uint32_t HB> __device__ __forceinline__ void wgmma_n88_ss(float (&d)[44], uint32_t da, uint32_t db, int sd) {
  asm volatile("{\n.reg .pred p;\n.reg .b64 da, db;\nsetp.ne.b32 p, %46, 0;\nmov.b64 da, {%44, %49};\nmov.b64 db, {%45, %50};\n"
    "wgmma.mma_async.sync.aligned.m64n88k16.f32.bf16.bf16 {%0, %1, %2, %3, %4, %5, %6, %7, %8, %9, %10, %11, %12, %13, %14, %15, %16, %17, %18, %19, %20, %21, %22, %23, %24, %25, %26, %27, %28, %29, %30, %31, %32, %33, %34, %35, %36, %37, %38, %39, %40, %41, %42, %43}, da, db, p, 1, 1, %47, %48;\n}\n"
    : "+f"(d[0]), "+f"(d[1]), "+f"(d[2]), "+f"(d[3]), "+f"(d[4]), "+f"(d[5]), "+f"(d[6]), "+f"(d[7]), "+f"(d[8]), "+f"(d[9]), "+f"(d[10]), "+f"(d[11]), "+f"(d[12]), "+f"(d[13]), "+f"(d[14]), "+f"(d[15]), "+f"(d[16]), "+f"(d[17]), "+f"(d[18]), "+f"(d[19]), "+f"(d[20]), "+f"(d[21]), "+f"(d[22]), "+f"(d[23]), "+f"(d[24]), "+f"(d[25]), "+f"(d[26]), "+f"(d[27]), "+f"(d[28]), "+f"(d[29]), "+f"(d[30]), "+f"(d[31]), "+f"(d[32]), "+f"(d[33]), "+f"(d[34]), "+f"(d[35]), "+f"(d[36]), "+f"(d[37]), "+f"(d[38]), "+f"(d[39]), "+f"(d[40]), "+f"(d[41]), "+f"(d[42]), "+f"(d[43]) : "r"(da), "r"(db), "r"(sd), "n"(TA), "n"(TB), "n"(HA), "n"(HB));
}
template<int TA, int TB, uint32_t HA, uint32_t HB> __device__ __forceinline__ void wgmma_n128_ss(float (&d)[64], uint32_t da, uint32_t db, int sd) {
  asm volatile("{\n.reg .pred p;\n.reg .b64 da, db;\nsetp.ne.b32 p, %66, 0;\nmov.b64 da, {%64, %69};\nmov.b64 db, {%65, %70};\n"
    "wgmma.mma_async.sync.aligned.m64n128k16.f32.bf16.bf16 {%0, %1, %2, %3, %4, %5, %6, %7, %8, %9, %10, %11, %12, %13, %14, %15, %16, %17, %18, %19, %20, %21, %22, %23, %24, %25, %26, %27, %28, %29, %30, %31, %32, %33, %34, %35, %36, %37, %38, %39, %40, %41, %42, %43, %44, %45, %46, %47, %48, %49, %50, %51, %52, %53, %54, %55, %56, %57, %58, %59, %60, %61, %62, %63}, da, db, p, 1, 1, %67, %68;\n}\n"
    : "+f"(d[0]), "+f"(d[1]), "+f"(d[2]), "+f"(d[3]), "+f"(d[4]), "+f"(d[5]), "+f"(d[6]), "+f"(d[7]), "+f"(d[8]), "+f"(d[9]), "+f"(d[10]), "+f"(d[11]), "+f"(d[12]), "+f"(d[13]), "+f"(d[14]), "+f"(d[15]), "+f"(d[16]), "+f"(d[17]), "+f"(d[18]), "+f"(d[19]), "+f"(d[20]), "+f"(d[21]), "+f"(d[22]), "+f"(d[23]), "+f"(d[24]), "+f"(d[25]), "+f"(d[26]), "+f"(d[27]), "+f"(d[28]), "+f"(d[29]), "+f"(d[30]), "+f"(d[31]), "+f"(d[32]), "+f"(d[33]), "+f"(d[34]), "+f"(d[35]), "+f"(d[36]), "+f"(d[37]), "+f"(d[38]), "+f"(d[39]), "+f"(d[40]), "+f"(d[41]), "+f"(d[42]), "+f"(d[43]), "+f"(d[44]), "+f"(d[45]), "+f"(d[46]), "+f"(d[47]), "+f"(d[48]), "+f"(d[49]), "+f"(d[50]), "+f"(d[51]), "+f"(d[52]), "+f"(d[53]), "+f"(d[54]), "+f"(d[55]), "+f"(d[56]), "+f"(d[57]), "+f"(d[58]), "+f"(d[59]), "+f"(d[60]), "+f"(d[61]), "+f"(d[62]), "+f"(d[63]) : "r"(da), "r"(db), "r"(sd), "n"(TA), "n"(TB), "n"(HA), "n"(HB));
}

constexpr int S_ = 2048, F_ = 1376, DF = 257;
constexpr int NCTA = 128;
constexpr int W_BYTES = 180224;
constexpr int RING_OFF = W_BYTES;
constexpr int NST = 6;
constexpr int BAR_OFF = RING_OFF + NST * 8192;
constexpr int SMEM_BYTES = BAR_OFF + 1536;
constexpr int FILT_OFF = RING_OFF;
constexpr int XCH_OFF = RING_OFF + 16384;
constexpr int ZROW = 328;
constexpr int MB_FULL = 0, MB_W2 = 54, MB_W1T = 76, MB_X1 = 108, MB_X2 = 109, MB_X1DONE = 110, MB_P3DONE = 111, MB_FILT = 112, MB_W1 = 113,
              MB_EMPTY = 114, MB_PEER1 = 168, MB_PEER2 = 169, MB_N = 171;
constexpr int BASE_OFF = BAR_OFF + MB_N * 8;
#define W2_START 24

struct Scratch {
  uint4 T1[NCTA * 1024], T2[NCTA * 1024], Hn[4 * 128 * 256], U[4 * 172 * 128];
  float2 st[S_];
  unsigned cnt[8 * 4 * 64];
};
__device__ __align__(1024) Scratch g_scr;
#define g_T1 (scr->T1)
#define g_T2 (scr->T2)
#define g_Hn (scr->Hn)
#define g_U (scr->U)
#define g_st (scr->st)
#define g_cnt (scr->cnt)
#define STAMP(i)

__device__ __forceinline__ void mbar_init(uint32_t b, int c) { asm volatile("mbarrier.init.shared::cta.b64 [%0], %1;" :: "r"(b), "r"(c) : "memory"); }
__device__ __forceinline__ void mbar_expect(uint32_t b, int bytes) { asm volatile("mbarrier.arrive.expect_tx.shared::cta.b64 _, [%0], %1;" :: "r"(b), "r"(bytes) : "memory"); }
__device__ __forceinline__ void mbar_arrive(uint32_t b) { asm volatile("mbarrier.arrive.shared::cta.b64 _, [%0];" :: "r"(b) : "memory"); }
__device__ __forceinline__ void mbar_arrive_cluster(uint32_t remote) { asm volatile("mbarrier.arrive.relaxed.cluster.shared::cluster.b64 _, [%0];" :: "r"(remote) : "memory"); }
__device__ __forceinline__ uint32_t mapa(uint32_t a, uint32_t cta) { uint32_t r; asm("mapa.shared::cluster.u32 %0, %1, %2;" : "=r"(r) : "r"(a), "r"(cta)); return r; }
__device__ __forceinline__ void mbar_wait(uint32_t b, int ph) {
  asm volatile("{\n.reg .pred p;\n.reg .u32 n;\nmov.u32 n, 0;\nL_W:\n"
               "mbarrier.try_wait.parity.shared::cta.b64 p, [%0], %1;\n@p bra L_D;\n"
               "add.u32 n, n, 1;\nsetp.lt.u32 p, n, 4000000;\n@p bra L_W;\ntrap;\nL_D:\n}" :: "r"(b), "r"(ph) : "memory");
}
__device__ __forceinline__ void mbar_wait_cluster(uint32_t b, int ph) {
  asm volatile("{\n.reg .pred p;\n.reg .u32 n;\nmov.u32 n, 0;\nL_W:\n"
               "mbarrier.try_wait.parity.acquire.cluster.shared::cta.b64 p, [%0], %1;\n@p bra L_D;\n"
               "add.u32 n, n, 1;\nsetp.lt.u32 p, n, 4000000;\n@p bra L_W;\ntrap;\nL_D:\n}" :: "r"(b), "r"(ph) : "memory");
}
__device__ __forceinline__ void bulk_ld(uint32_t dst, const void* src, int bytes, uint32_t bar) {
  asm volatile("cp.async.bulk.shared::cluster.global.mbarrier::complete_tx::bytes [%0], [%1], %2, [%3];" :: "r"(dst), "l"(src), "r"(bytes), "r"(bar) : "memory");
}
__device__ __forceinline__ void tma3d(uint32_t dst, const CUtensorMap* tm, int c0, int c1, int c2, uint32_t bar) {
  asm volatile("cp.async.bulk.tensor.3d.shared::cluster.global.mbarrier::complete_tx::bytes [%0], [%1, {%3, %4, %5}], [%2];"
               :: "r"(dst), "l"(tm), "r"(bar), "r"(c0), "r"(c1), "r"(c2) : "memory");
}
__device__ __forceinline__ bool elect() { uint32_t p; asm volatile("{.reg .pred p; elect.sync _|p, 0xffffffff; selp.b32 %0, 1, 0, p;}" : "=r"(p)); return p; }
__device__ __forceinline__ uint32_t desc_lo(uint32_t addr, uint32_t lbo) { return ((addr & 0x3FFFF) >> 4) | ((lbo >> 4) << 16); }
constexpr uint32_t HI_SW128 = (1024 >> 4) | (1u << 30), HI_NOSW = 128 >> 4;
__device__ __forceinline__ uint32_t pk(float lo, float hi) { uint32_t r; asm("cvt.rn.bf16x2.f32 %0, %1, %2;" : "=r"(r) : "f"(hi), "f"(lo)); return r; }
__device__ __forceinline__ float blo(uint32_t w) { return __uint_as_float(w << 16); }
__device__ __forceinline__ float bhi(uint32_t w) { return __uint_as_float(w & 0xffff0000u); }
__device__ __forceinline__ void mmac(float (&d)[4], const float (&c)[4], const uint32_t (&a)[4], uint32_t b0, uint32_t b1) {
  asm("mma.sync.aligned.m16n8k16.row.col.f32.bf16.bf16.f32 {%0,%1,%2,%3}, {%4,%5,%6,%7}, {%8,%9}, {%10,%11,%12,%13};"
      : "=f"(d[0]), "=f"(d[1]), "=f"(d[2]), "=f"(d[3]) : "r"(a[0]), "r"(a[1]), "r"(a[2]), "r"(a[3]), "r"(b0), "r"(b1), "f"(c[0]), "f"(c[1]), "f"(c[2]), "f"(c[3]));
}
__device__ __forceinline__ void mma0(float (&d)[4], const uint32_t (&a)[4], uint32_t b0, uint32_t b1) { const float z[4] = {0.f, 0.f, 0.f, 0.f}; mmac(d, z, a, b0, b1); }
__device__ __forceinline__ uint32_t pin(uint32_t v) { asm volatile("shfl.sync.bfly.b32 %0, %0, 0, 31, 0xffffffff;" : "+r"(v)); return v; }
__device__ __forceinline__ float pinf(float v) { asm volatile("" : "+f"(v)); return v; }
__device__ __forceinline__ void wbar() { asm volatile("bar.sync 1, 256;" ::: "memory"); }
__device__ __forceinline__ void sts32(uint32_t a, uint32_t v) { asm volatile("st.shared.b32 [%0], %1;" :: "r"(a), "r"(v) : "memory"); }
__device__ __forceinline__ void sts64(uint32_t a, uint32_t x, uint32_t y) { asm volatile("st.shared.v2.b32 [%0], {%1,%2};" :: "r"(a), "r"(x), "r"(y) : "memory"); }
__device__ __forceinline__ void sts128(uint32_t a, uint4 v) { asm volatile("st.shared.v4.b32 [%0], {%1,%2,%3,%4};" :: "r"(a), "r"(v.x), "r"(v.y), "r"(v.z), "r"(v.w) : "memory"); }
__device__ __forceinline__ uint32_t lds32(uint32_t a) { uint32_t v; asm volatile("ld.shared.b32 %0, [%1];" : "=r"(v) : "r"(a) : "memory"); return v; }
__device__ __forceinline__ uint2 lds64(uint32_t a) { uint2 v; asm volatile("ld.shared.v2.b32 {%0,%1}, [%2];" : "=r"(v.x), "=r"(v.y) : "r"(a) : "memory"); return v; }
__device__ __forceinline__ uint4 lds128(uint32_t a) { uint4 v; asm volatile("ld.shared.v4.b32 {%0,%1,%2,%3}, [%4];" : "=r"(v.x), "=r"(v.y), "=r"(v.z), "=r"(v.w) : "r"(a) : "memory"); return v; }
__device__ __forceinline__ uint4 ldcg128(const void* p) { uint4 v; asm volatile("ld.global.cg.v4.b32 {%0,%1,%2,%3}, [%4];" : "=r"(v.x), "=r"(v.y), "=r"(v.z), "=r"(v.w) : "l"(p) : "memory"); return v; }
__device__ __forceinline__ void st_async4(uint32_t a, uint32_t x, uint32_t y, uint32_t z, uint32_t w, uint32_t bar) {
  asm volatile("st.async.weak.shared::cluster.mbarrier::complete_tx::bytes.v4.b32 [%0], {%1,%2,%3,%4}, [%5];" :: "r"(a), "r"(x), "r"(y), "r"(z), "r"(w), "r"(bar) : "memory");
}
constexpr int NREP = 4;
__device__ __forceinline__ void cnt_arrive(Scratch* scr, int i, int lane) {
  if (lane < NREP) asm volatile("red.relaxed.gpu.global.add.u32 [%0], 1;" :: "l"(&g_cnt[(i * NREP + lane) * 64]) : "memory");
}
template <bool ACQ> __device__ __forceinline__ void cnt_wait(Scratch* scr, int i, int rep, unsigned target) {
  unsigned v; int n = 0;
  do {
    if (ACQ) asm volatile("ld.acquire.gpu.global.u32 %0, [%1];" : "=r"(v) : "l"(&g_cnt[(i * NREP + rep) * 64]) : "memory");
    else asm volatile("ld.relaxed.gpu.global.u32 %0, [%1];" : "=r"(v) : "l"(&g_cnt[(i * NREP + rep) * 64]) : "memory");
    if (++n > 2000000) __trap(); } while ((int)(v - target) < 0);
}
__device__ __forceinline__ void fence_gpu() { asm volatile("fence.acq_rel.gpu;" ::: "memory"); }
__device__ __forceinline__ void tag_check(uint4& v, const uint4* p, uint32_t tag) {
  int n = 0;
  while ((v.x ^ tag) & 1) {
    asm volatile("ld.relaxed.gpu.global.v4.b32 {%0,%1,%2,%3}, [%4];" : "=r"(v.x), "=r"(v.y), "=r"(v.z), "=r"(v.w) : "l"(p) : "memory");
    if (++n > 2000000) __trap();
  }
}
template <int N> __device__ __forceinline__ void cs(int n, float& c, float& s) {
  n = ((n + N / 2) & (N - 1)) - N / 2;
  float a = (float)n * (6.283185307179586f / N);
  c = __cosf(a); s = __sinf(a);
}
constexpr float ALPHA = 1.13288f;
struct FftC { uint32_t a[4][4], b[8][2]; float tc[2][4], ts[2][4]; };
constexpr uint32_t NEG = 0x80008000u;

__device__ __forceinline__ void fft_s1(const FftC& K, const uint32_t (&in)[4][2], float (&cr)[2][4], float (&ci)[2][4]) {
#pragma unroll
  for (int h = 0; h < 2; h++) { mma0(cr[h], K.a[0], in[0][h], in[1][h]); mma0(ci[h], K.a[1], in[0][h], in[1][h]); }
#pragma unroll
  for (int h = 0; h < 2; h++) { mmac(cr[h], cr[h], K.a[2], in[2][h], in[3][h]); mmac(ci[h], ci[h], K.a[3], in[2][h], in[3][h]); }
}
__device__ __forceinline__ void fft_s2(const FftC& K, const float (&cr)[2][4], const float (&ci)[2][4], float (&o)[4][4]) {
  uint32_t a[2][4];
#pragma unroll
  for (int h = 0; h < 2; h++)
#pragma unroll
    for (int i = 0; i < 4; i++) {
      float xr = cr[i & 1][2 * h + (i >> 1)], xi = ci[i & 1][2 * h + (i >> 1)];
      a[i >> 1][2 * (i & 1) + h] = pk(xr * K.tc[h][i] + xi * K.ts[h][i], xi * K.tc[h][i] - xr * K.ts[h][i]);
    }
#pragma unroll
  for (int j = 0; j < 4; j++) mma0(o[j], a[0], K.b[j][0], K.b[j][1]);
#pragma unroll
  for (int j = 0; j < 4; j++) mmac(o[j], o[j], a[1], K.b[4 + j][0], K.b[4 + j][1]);
}
__device__ __forceinline__ int zphys(int k) { return k + 8 * (k >> 5); }
__device__ __forceinline__ float gelu(float u) {
  float z = u * (0.7978845608028654f + 0.035677408136300125f * u * u), th;
  asm("tanh.approx.f32 %0, %1;" : "=f"(th) : "f"(z));
  float hu = 0.5f * u;
  return fmaf(hu, th, hu);
}

extern "C" __global__ void __cluster_dims__(2, 1, 1) __launch_bounds__(384, 1)
fused_kernel(const uint2* __restrict__ x, Scratch* scr, const unsigned short* __restrict__ wr, const unsigned short* __restrict__ wi,
             const uint32_t* __restrict__ b1, const unsigned short* __restrict__ b2, uint4* __restrict__ out, const char* __restrict__ w2,
             const __grid_constant__ CUtensorMap tmW1, const __grid_constant__ CUtensorMap tmW2) {
  extern __shared__ __align__(1024) char smem[];
  const uint32_t sb = (uint32_t)__cvta_generic_to_shared(smem);
  const uint32_t mb = sb + BAR_OFF;
  const int b = blockIdx.x, rank = b & 1, pr = b >> 1, dt = pr & 3, ot = pr >> 2;
  const int warp = __shfl_sync(0xffffffffu, threadIdx.x >> 5, 0), lane = threadIdx.x & 31;
  const int g = lane >> 2, t = lane & 3;

  if (warp < 8) {
    const int tid = threadIdx.x;
    uint32_t xw[2][4][2];
    {
      const uint2* xp = x + (size_t)(256 * warp + 2 * b) * 128 + 8 * t + g;
#pragma unroll
      for (int a = 0; a < 2; a++)
#pragma unroll
        for (int j = 0; j < 4; j++) { uint2 v = __ldg(xp + a * 128 + 32 * j); xw[a][j][0] = v.x; xw[a][j][1] = v.y; }
    }
    STAMP(0);
    asm volatile("barrier.cluster.arrive.relaxed.aligned;" ::: "memory");
    const int rep = ot & (NREP - 1);
    const unsigned base = __ldcg(&g_cnt[(1 * NREP + rep) * 64]);
    const uint32_t tag = (~base >> 7) & 1;
    FftC K;
    {
      float c, s;
#pragma unroll
      for (int h = 0; h < 2; h++)
#pragma unroll
        for (int j = 0; j < 2; j++) {
          cs<16>((2 * g + h) * (t + 4 * j), c, s);
          const uint32_t re = pk(ALPHA * c, ALPHA * s), im = pk(-ALPHA * s, ALPHA * c);
          K.a[0][2 * j + h] = re; K.a[1][2 * j + h] = im; K.a[2][2 * j + h] = pin(h ? re ^ NEG : re); K.a[3][2 * j + h] = pin(h ? im ^ NEG : im);
        }
#pragma unroll
      for (int i = 0; i < 4; i++) {
        cs<16>((4 * t + i) * (g >> 1) + 4 * (g & 1), c, s);
        const uint32_t P = pk(ALPHA * c, ALPHA * s), Q = pk(-ALPHA * s, ALPHA * c);
#pragma unroll
        for (int jj = 0; jj < 4; jj++) { const uint32_t v = ((i * jj) & 1 ? Q : P) ^ ((i * jj) & 2 ? NEG : 0u); K.b[4 * (i >> 1) + jj][i & 1] = jj ? pin(v) : v; }
      }
#pragma unroll
      for (int h = 0; h < 2; h++)
#pragma unroll
        for (int i = 0; i < 4; i++) {
          cs<256>((2 * g + h) * (4 * t + i), c, s);
          K.tc[h][i] = pinf(c * (1.f / (ALPHA * ALPHA))); K.ts[h][i] = pinf(s * (1.f / (ALPHA * ALPHA)));
        }
    }
    const int key = ((b >> 3) & 3) * 2 + (b & 1);
    const uint32_t zb = sb + XCH_OFF;
    float mean[2];
    {
      uint32_t a8[2][4], a8c[2][4], a8n[2][4]; float vc[4], vs[4];
#pragma unroll
      for (int a = 0; a < 2; a++)
#pragma unroll
        for (int u = 0; u < 4; u++) {
          float c, s; cs<2048>(g * (256 * (t + 4 * (u >> 1)) + 2 * b + a), c, s);
          a8[a][u] = u & 1 ? pk(-s, c) : pk(c, s);
          a8c[a][u] = pin(a8[a][u] ^ 0x80000000u); a8n[a][u] = pin(a8[a][u] ^ 0x00008000u);
        }
#pragma unroll
      for (int i = 0; i < 4; i++) { cs<512>(16 * warp + 8 * (i >> 1) + 2 * t + (i & 1) + 128, vc[i], vs[i]); vc[i] = pinf(vc[i]); vs[i] = pinf(vs[i]); }
      STAMP(13);
      asm volatile("{\n.reg .pred p;\n.reg .u32 n;\nmov.u32 n, %0;\nL_S:\nshr.u32 n, n, 1;\nsetp.ne.u32 p, n, 0;\n@p bra L_S;\n}" :: "r"(base & 127u) : "memory");
#pragma unroll
      for (int a = 0; a < 2; a++) {
        float cr[2][4], ci[2][4], o[4][4];
        if (a == 0) { if (xw[0][0][0] == 0x12345678u && xw[1][3][1] == 0x12345679u) STAMP(31); STAMP(14); }
        fft_s1(K, xw[a], cr, ci);
        if (FILT_LATE && a == 0 && warp == 0) asm volatile("bar.arrive 3, 160;" :: "f"(cr[0][0]) : "memory");
        float sm = ((cr[0][0] + cr[0][1]) + (cr[1][0] + cr[1][1])) + ((ci[0][0] + ci[0][1]) + (ci[1][0] + ci[1][1]));
        sm += __shfl_xor_sync(0xffffffffu, sm, 1); sm += __shfl_xor_sync(0xffffffffu, sm, 2);
        sm = g == 0 ? sm * (1.f / 32.f) : 0.f;
#pragma unroll
        for (int h = 0; h < 2; h++) { cr[h][0] -= sm; cr[h][1] -= sm; ci[h][0] -= sm; ci[h][1] -= sm; }
        mean[a] = __shfl_sync(0xffffffffu, sm, 0) * (1.f / (16.f * 1.1328125f));
        float q = 0.f, q2 = 0.f;
#pragma unroll
        for (int i = 0; i < 4; i++) { q = fmaf(cr[0][i], cr[0][i], q); q2 = fmaf(cr[1][i], cr[1][i], q2); q = fmaf(ci[0][i], ci[0][i], q); q2 = fmaf(ci[1][i], ci[1][i], q2); }
        q += q2;
#pragma unroll
        for (int m = 1; m < 32; m <<= 1) q += __shfl_xor_sync(0xffffffffu, q, m);
        float r = rsqrtf(q * (1.f / (512.f * 16.f * ALPHA * ALPHA)) + 1e-5f) * 4.76837158203125e-7f;
        fft_s2(K, cr, ci, o);
#pragma unroll
        for (int j = 0; j < 4; j++)
          sts64(zb + ((a * 8 + warp) * ZROW + zphys(16 * t + 64 * j) + 2 * g) * 4, pk(o[j][0] * r, o[j][1] * r), pk(o[j][2] * r, o[j][3] * r));
      }
      STAMP(15);
      wbar();
      uint4* tp = g_T1 + (size_t)(g * 16 + warp) * 1024 + b * 8;
#pragma unroll
      for (int nt = 0; nt < 2; nt++) {
        const int k = 16 * warp + 8 * nt + g, km = k == 0 ? 128 : 256 - k;
        uint32_t lo[4], hi[4];
#pragma unroll
        for (int a = 0; a < 2; a++) {
          const uint32_t rb = zb + (a * 8 + t) * ZROW * 4;
          float A[4], S[4], D[4];
          const uint32_t m0 = lds32(rb + zphys(km) * 4), m1 = lds32(rb + (4 * ZROW + zphys(km)) * 4);
          mma0(A, a8[a], lds32(rb + zphys(k) * 4), lds32(rb + (4 * ZROW + zphys(k)) * 4));
          mmac(S, A, a8c[a], m0, m1);
          mmac(D, A, a8n[a], m0, m1);
#pragma unroll
          for (int e = 0; e < 2; e++) {
            const float c = vc[2 * nt + e], s = vs[2 * nt + e];
            float lr = fmaf(D[2 + e], s, fmaf(D[e], c, S[e])), li = fmaf(-D[e], s, fmaf(D[2 + e], c, S[2 + e]));
            float hr = fmaf(2.f, S[e], -lr), hii = fmaf(2.f, S[2 + e], -li);
            if (nt == 0 && e == 0) {
              const bool sp = warp == 0 && t == 0;
              lr = sp ? S[0] - D[0] : lr; li = sp ? S[2] - D[2] : li;
              hr = sp ? 2.f * (A[0] - A[2]) : hr; hii = sp ? 2.f * (A[0] + A[2]) : hii;
            }
            lo[2 * a + e] = pk(lr, li); hi[2 * a + e] = pk(hr, hii);
          }
        }
        const int w = (t + 4 * nt) ^ key;
        tp[w] = make_uint4((lo[0] & ~1u) | tag, lo[1], lo[2], lo[3]);
        tp[8 * 1024 + w] = make_uint4((hi[0] & ~1u) | tag, hi[1], hi[2], hi[3]);
      }
      wbar();
      STAMP(1);
      if (warp == 0) cnt_arrive(scr, 0, lane);
    }
    {
      const uint32_t off = (8 * t + g) * 128 + ((warp ^ (2 * t + (g & 1))) << 4);
      asm volatile("barrier.cluster.wait.aligned;" ::: "memory");
      mbar_wait(mb + MB_FILT * 8, 0);
      if (tid == 0) cnt_wait<false>(scr, 0, rep, base + NCTA);
      wbar();
#pragma unroll
      for (int j = 0; j < 4; j++)
        asm volatile("cp.async.cg.shared.global [%0], [%1], 16;" :: "r"(zb + j * 4096 + tid * 16), "l"(g_T1 + (size_t)b * 1024 + j * 256 + tid) : "memory");
      STAMP(2);
      uint32_t in[2][4][2], fw[2][4][2];
#pragma unroll
      for (int j = 0; j < 4; j++) {
        uint4 v = lds128(sb + FILT_OFF + off + j * 4096);
        fw[0][j][0] = v.x; fw[1][j][0] = v.y; fw[0][j][1] = v.z; fw[1][j][1] = v.w;
      }
      asm volatile("cp.async.wait_all;" ::: "memory");
      wbar();
      STAMP(3);
      uint4 iv[4];
#pragma unroll
      for (int j = 0; j < 4; j++) iv[j] = lds128(zb + off + j * 4096);
      if (((iv[0].x ^ tag) | (iv[1].x ^ tag) | (iv[2].x ^ tag) | (iv[3].x ^ tag)) & 1) {
#pragma unroll
        for (int j = 0; j < 4; j++) tag_check(iv[j], g_T1 + (size_t)b * 1024 + j * 256 + (off >> 4), tag);
      }
      __syncwarp();
#pragma unroll
      for (int j = 0; j < 4; j++) { in[0][j][0] = iv[j].x; in[1][j][0] = iv[j].y; in[0][j][1] = iv[j].z; in[1][j][1] = iv[j].w; }
#pragma unroll
      for (int sg = 0; sg < 2; sg++) {
        float cr[2][4], ci[2][4], o[4][4];
        fft_s1(K, in[sg], cr, ci);
        fft_s2(K, cr, ci, o);
#pragma unroll
        for (int j = 0; j < 4; j++)
#pragma unroll
          for (int h = 0; h < 2; h++) {
            float fr = blo(fw[sg][j][h]), fi = bhi(fw[sg][j][h]), xr = o[j][2 * h], xi = o[j][2 * h + 1];
            in[sg][j][h] = pk(xr * fi + xi * fr, xr * fr - xi * fi);
          }
        fft_s1(K, in[sg], cr, ci);
        fft_s2(K, cr, ci, o);
#pragma unroll
        for (int j = 0; j < 4; j++) { in[sg][j][0] = pk(o[j][0], o[j][1]); in[sg][j][1] = pk(o[j][2], o[j][3]); }
      }
#pragma unroll
      for (int j = 0; j < 4; j++) sts128(zb + off + j * 4096, make_uint4((in[0][j][0] & ~1u) | tag, in[1][j][0], in[0][j][1], in[1][j][1]));
      STAMP(16);
      wbar();
#pragma unroll
      for (int j = 0; j < 4; j++) g_T2[(size_t)b * 1024 + j * 256 + tid] = lds128(zb + j * 4096 + tid * 16);
      wbar();
      STAMP(4);
      if (warp == 0) cnt_arrive(scr, 1, lane);
    }
    {
      uint32_t a8[2][4], a8n[2][4]; float vc[4], vs[4];
#pragma unroll
      for (int a = 0; a < 2; a++)
#pragma unroll
        for (int u = 0; u < 4; u++) {
          float c, s; cs<2048>((t + 4 * (u >> 1)) * (256 * g + 2 * b + a), c, s);
          a8[a][u] = u & 1 ? pk(-s, c) : pk(c, s);
          a8n[a][u] = pin(a8[a][u] ^ NEG);
        }
#pragma unroll
      for (int i = 0; i < 4; i++) { cs<512>(16 * warp + 4 * t + i + 128, vc[i], vs[i]); vc[i] = pinf(vc[i]); vs[i] = pinf(vs[i]); }
      if (tid == 0) cnt_wait<false>(scr, 1, rep, base + NCTA);
      wbar();
      STAMP(5);
      const uint4* tp = g_T2 + (size_t)(t * 16 + warp) * 1024 + b * 8 + (g ^ key);
      uint4 L0 = ldcg128(tp), L1 = ldcg128(tp + 64 * 1024), H0 = ldcg128(tp + 8 * 1024), H1 = ldcg128(tp + 72 * 1024);
      if (((L0.x ^ tag) | (L1.x ^ tag) | (H0.x ^ tag) | (H1.x ^ tag)) & 1) {
        tag_check(L0, tp, tag); tag_check(L1, tp + 64 * 1024, tag); tag_check(H0, tp + 8 * 1024, tag); tag_check(H1, tp + 72 * 1024, tag);
      }
      __syncwarp();
      STAMP(17);
      const uint32_t l0[4] = {L0.x, L0.y, L0.z, L0.w}, l1[4] = {L1.x, L1.y, L1.z, L1.w}, h0[4] = {H0.x, H0.y, H0.z, H0.w}, h1[4] = {H1.x, H1.y, H1.z, H1.w};
#pragma unroll
      for (int a = 0; a < 2; a++) {
        uint32_t zf[4], zm[4];
#pragma unroll
        for (int sg = 0; sg < 2; sg++) {
          float A[4], S[4], D[4];
          mma0(A, a8[a], l0[2 * a + sg], l1[2 * a + sg]);
          mmac(S, A, a8[a], h0[2 * a + sg], h1[2 * a + sg]);
          mmac(D, A, a8n[a], h0[2 * a + sg], h1[2 * a + sg]);
#pragma unroll
          for (int e = 0; e < 2; e++) {
            const int i = 2 * e + sg;
            float fr = fmaf(-D[e], vs[i], fmaf(D[2 + e], vc[i], S[2 + e])), fi = fmaf(D[2 + e], vs[i], fmaf(D[e], vc[i], S[e]));
            float mr = fmaf(2.f, S[2 + e], -fr), mi = fmaf(-2.f, S[e], fi);
            if (i == 0) {
              const bool sp = warp == 0 && t == 0;
              fr = sp ? S[2] - A[2] : fr; fi = sp ? A[2] - S[2] : fi;
              mr = sp ? 2.f * A[2] : mr; mi = sp ? -2.f * A[0] : mi;
            }
            zf[i] = pk(fi, fr); zm[i] = pk(mi, mr);
          }
        }
        const uint32_t rb = zb + (a * 8 + g) * ZROW * 4;
        const int k0 = 16 * warp + 4 * t;
        sts128(rb + zphys(k0) * 4, make_uint4(zf[0], zf[1], zf[2], zf[3]));
        sts32(rb + zphys(k0 == 0 ? 128 : 256 - k0) * 4, zm[0]);
        sts32(rb + zphys(255 - k0) * 4, zm[1]);
        sts32(rb + zphys(254 - k0) * 4, zm[2]);
        sts32(rb + zphys(253 - k0) * 4, zm[3]);
      }
      STAMP(18);
      wbar();
      float o[2][4][4], s2[2];
#pragma unroll
      for (int a = 0; a < 2; a++) {
        uint32_t in[4][2];
#pragma unroll
        for (int j = 0; j < 4; j++) { uint2 v = lds64(zb + ((a * 8 + warp) * ZROW + zphys(16 * t + 64 * j) + 2 * g) * 4); in[j][0] = v.x; in[j][1] = v.y; }
        float cr[2][4], ci[2][4], s1 = 0.f;
        fft_s1(K, in, cr, ci);
        fft_s2(K, cr, ci, o[a]);
        s2[a] = 0.f;
#pragma unroll
        for (int j = 0; j < 4; j++)
#pragma unroll
          for (int h = 0; h < 2; h++) {
            uint32_t hw;
            asm("add.rn.bf16x2 %0, %1, %2;" : "=r"(hw) : "r"(xw[a][j][h]), "r"(pk(o[a][j][2 * h + 1], o[a][j][2 * h])));
            const float u0 = blo(hw) - mean[a], u1 = bhi(hw) - mean[a];
            o[a][j][2 * h] = u0; o[a][j][2 * h + 1] = u1;
            s1 = fmaf(u0, u0, s1); s2[a] = fmaf(u1, u1, s2[a]);
          }
        s2[a] += s1;
      }
      float sv = (lane < 16 ? s2[0] : s2[1]) + __shfl_xor_sync(0xffffffffu, lane < 16 ? s2[1] : s2[0], 16);
#pragma unroll
      for (int m = 1; m < 16; m <<= 1) sv += __shfl_xor_sync(0xffffffffu, sv, m);
      const float var = sv * (1.f / 512.f), r1 = rsqrtf(var + 1e-5f);
      const float rr = r1 * rsqrtf(var * r1 * r1 + 1e-5f);
      const float ro = __shfl_xor_sync(0xffffffffu, rr, 16);
      char* np = (char*)g_Hn + (size_t)b * 4096 + (t >> 1) * 2048 + warp * 128 + ((((t & 1) * 4 + (g >> 1)) ^ warp ^ (b >> 6)) << 4) + (g & 1) * 8;
#pragma unroll
      for (int a = 0; a < 2; a++) {
        const float r = (lane >> 4) == a ? rr : ro;
#pragma unroll
        for (int j = 0; j < 4; j++)
          *(uint2*)(np + a * 1024 + (size_t)j * 128 * 4096) = make_uint2(pk(o[a][j][0] * r, o[a][j][1] * r), pk(o[a][j][2] * r, o[a][j][3] * r));
      }
      if ((lane & 15) == 0) g_st[256 * warp + 2 * b + (lane >> 4)] = make_float2(__fdividef(1.f, rr), lane ? mean[1] : mean[0]);
      STAMP(19);
      asm volatile("fence.proxy.async.shared::cta;" ::: "memory");
      wbar();
      STAMP(6);
      if (warp == 0) { fence_gpu(); cnt_arrive(scr, 2 + (b >> 6), lane); STAMP(25); }
      if (tid == 32) { sts32(sb + BASE_OFF, base); mbar_arrive(mb + MB_P3DONE * 8); }
    }
    const int wg = warp >> 2;
    const uint32_t peer_sb = mapa(sb, rank ^ 1);
    {
      float acc[44];
#pragma unroll
      for (int j = 0; j < 11; j++) {
        const uint32_t bw = __ldg(b1 + min(11 * ot + j, 171) * 4 + t);
        acc[4 * j] = blo(bw); acc[4 * j + 1] = bhi(bw); acc[4 * j + 2] = 0.f; acc[4 * j + 3] = 0.f;
      }
      const uint32_t da0 = desc_lo(sb + RING_OFF + wg * 2048, 0);
      uint32_t da = da0, db = desc_lo(sb, 1408), bar = mb;
      mbar_wait(mb + MB_W1 * 8, 0);
#pragma unroll 1
      for (int i = 0; i < 32; i++) {
        mbar_wait(bar + MB_FULL * 8, 0);
        if (i == 0) STAMP(7);
        asm volatile("wgmma.fence.sync.aligned;" ::: "memory");
        wgmma_n88_ss<1, 1, HI_SW128, HI_NOSW>(acc, da, db, 1);
        wgmma_n88_ss<1, 1, HI_SW128, HI_NOSW>(acc, da + 256, db + 176, 1);
        asm volatile("wgmma.commit_group.sync.aligned;" ::: "memory");
        da = da == da0 + 5 * 512 ? da0 : da + 512; db += 352;
        asm volatile("wgmma.wait_group.sync.aligned 1;" ::: "memory");
        if ((tid & 127) == 0) { if (i > 0) mbar_arrive(bar + (MB_EMPTY - 1) * 8); if (i == 4) mbar_arrive_cluster(peer_sb + BAR_OFF + MB_PEER1 * 8); }
        bar += 8;
      }
      asm volatile("wgmma.wait_group.sync.aligned 0;" ::: "memory");
#pragma unroll
      for (int i = 0; i < 44; i++) asm volatile("" : "+f"(acc[i]) :: "memory");
      if ((tid & 127) == 0) mbar_arrive(mb + (MB_EMPTY + 31) * 8);
      STAMP(8);
      mbar_wait_cluster(mb + MB_PEER1 * 8, 0);
#pragma unroll
      for (int j = 0; j < 3; j++)
        st_async4(peer_sb + j * 4096 + tid * 16, pk(acc[16 * j + 2], acc[16 * j + 3]), pk(acc[16 * j + 6], acc[16 * j + 7]), pk(acc[16 * j + 10], acc[16 * j + 11]),
                  j < 2 ? pk(acc[16 * j + 14], acc[16 * j + 15]) : 0u, peer_sb + BAR_OFF + MB_X1 * 8);
      const int uo = (4 * (warp >> 1) + (g >> 1)) * 32 + (2 * (2 * (warp & 1) + rank) + (g & 1)) * 4 + t;
      uint32_t* const ub = (uint32_t*)g_U + ((size_t)dt * 172 + 11 * ot) * 512;
      uint32_t *upa = ub + (uo ^ (ot >= 8 ? 256 : 0)), *upb = ub + (uo ^ (ot >= 7 ? 256 : 0));
      STAMP(20);
      mbar_wait_cluster(mb + MB_X1 * 8, 0);
      STAMP(21);
      uint32_t pv[12];
#pragma unroll
      for (int j = 0; j < 3; j++) { const uint4 v = lds128(sb + j * 4096 + tid * 16); pv[4 * j] = v.x; pv[4 * j + 1] = v.y; pv[4 * j + 2] = v.z; pv[4 * j + 3] = v.w; }
#pragma unroll
      for (int j = 0; j < 11; j++) {
        uint32_t v = pk(gelu(acc[4 * j] + blo(pv[j])), gelu(acc[4 * j + 1] + bhi(pv[j])));
        if (j < 7 || ot < 15) (j < 9 ? upa : upb)[j * 512] = v;
      }
      STAMP(22);
      asm volatile("fence.proxy.async.shared::cta;" ::: "memory");
      wbar();
      STAMP(9);
      if (warp == 0) { fence_gpu(); cnt_arrive(scr, 4 + dt, lane); STAMP(26); }
      if (tid == 32) mbar_arrive(mb + MB_X1DONE * 8);
    }
    {
      const int srow = 128 * ot + 16 * warp + g, oo = srow * 64 + dt * 16 + 8 * rank + t;
      float acc[64];
      const uint32_t da0 = desc_lo(sb + wg * 4096, 0), db0 = desc_lo(sb + RING_OFF, 2048);
      uint32_t da = da0 + 3 * 512, db = db0 + (32 % NST) * 512, bar = mb;
#pragma unroll
      for (int u = 0; u < 2; u++) {
        const int sr = srow + 8 * u, s1 = ot >> 1;
        const float2 st = __ldcg(g_st + sr);
        const float off = st.y + __uint_as_float((uint32_t)__ldg(b2 + sr) << 16);
#pragma unroll
        for (int jj = 0; jj < 2; jj++) {
          const uint4 v = ldcg128(g_Hn + (dt * 128 + ((sr & 255) >> 1)) * 256 + rank * 128 + (sr & 1) * 64 + s1 * 8 + ((4 * jj + t) ^ s1 ^ (ot & 1)));
          const uint32_t w[4] = {v.x, v.y, v.z, v.w};
#pragma unroll
          for (int j = 0; j < 4; j++) { acc[16 * jj + 4 * j + 2 * u] = fmaf(blo(w[j]), st.x, off); acc[16 * jj + 4 * j + 2 * u + 1] = fmaf(bhi(w[j]), st.x, off); }
        }
      }
#pragma unroll
      for (int j = 32; j < 64; j++) acc[j] = 0.f;
#pragma unroll 1
      for (int i = 0; i < 21; i++) {
        mbar_wait(bar + MB_W2 * 8, 0);
        mbar_wait(bar + (MB_FULL + 32) * 8, 0);
        if (i == 0) STAMP(10);
        asm volatile("wgmma.fence.sync.aligned;" ::: "memory");
        wgmma_n128_ss<1, 0, HI_SW128, HI_NOSW>(acc, da, db, 1);
        wgmma_n128_ss<1, 0, HI_SW128, HI_NOSW>(acc, da + 128, db + 256, 1);
        asm volatile("wgmma.commit_group.sync.aligned;" ::: "memory");
        da = i == 18 ? da0 : da + 512; db = db == db0 + 5 * 512 ? db0 : db + 512;
        asm volatile("wgmma.wait_group.sync.aligned 1;" ::: "memory");
        if ((tid & 127) == 0) { if (i > 0) mbar_arrive(bar + (MB_EMPTY + 31) * 8); if (i == 4) mbar_arrive_cluster(peer_sb + BAR_OFF + MB_PEER2 * 8); }
        bar += 8;
      }
      mbar_wait(bar + MB_W2 * 8, 0);
      mbar_wait(bar + (MB_FULL + 32) * 8, 0);
      asm volatile("wgmma.fence.sync.aligned;" ::: "memory");
      wgmma_n128_ss<1, 0, HI_SW128, HI_NOSW>(acc, da, db, 1);
      asm volatile("wgmma.commit_group.sync.aligned;" ::: "memory");
      asm volatile("wgmma.wait_group.sync.aligned 0;" ::: "memory");
#pragma unroll
      for (int i = 0; i < 64; i++) asm volatile("" : "+f"(acc[i]) :: "memory");
      STAMP(11);
      mbar_wait_cluster(mb + MB_PEER2 * 8, 0);
#pragma unroll
      for (int j = 0; j < 4; j++) {
        const int o = 32 + 16 * (j >> 1) + 2 * (j & 1);
        st_async4(peer_sb + 3 * 8192 + j * 4096 + tid * 16, pk(acc[o], acc[o + 1]), pk(acc[o + 4], acc[o + 5]), pk(acc[o + 8], acc[o + 9]), pk(acc[o + 12], acc[o + 13]),
                  peer_sb + BAR_OFF + MB_X2 * 8);
      }
      STAMP(23);
      mbar_wait_cluster(mb + MB_X2 * 8, 0);
      STAMP(24);
#pragma unroll
      for (int j = 0; j < 4; j++) {
        const int o = 16 * (j >> 1) + 2 * (j & 1);
        const uint4 v = lds128(sb + 3 * 8192 + j * 4096 + tid * 16);
        out[oo + 4 * (j >> 1) + 512 * (j & 1)] = make_uint4(pk(acc[o] + blo(v.x), acc[o + 1] + bhi(v.x)), pk(acc[o + 4] + blo(v.y), acc[o + 5] + bhi(v.y)),
                                                            pk(acc[o + 8] + blo(v.z), acc[o + 9] + bhi(v.z)), pk(acc[o + 12] + blo(v.w), acc[o + 13] + bhi(v.w)));
      }
      STAMP(12);
    }
  } else {
    const int pw = warp - 8;
    if (pw < 3 && elect()) {
#pragma unroll
      for (int i = 0; i < 57; i++) mbar_init(mb + (pw * 57 + i) * 8, pw == 2 ? 2 : 1);
      if (pw == 1) { mbar_expect(mb + MB_X1 * 8, 12288); mbar_expect(mb + MB_X2 * 8, 16384); }
      asm volatile("fence.mbarrier_init.release.cluster;" ::: "memory");
    }
    __syncwarp();
    STAMP(0);
    asm volatile("bar.sync 2, 128;" ::: "memory");
    asm volatile("barrier.cluster.arrive.relaxed.aligned;" ::: "memory");
    auto w1_issue = [&](int i) {
      if (elect()) { mbar_expect(mb + (MB_W1T + i) * 8, 5632); tma3d(sb + i * 5632, &tmW1, 88 * ot, 0, 128 * rank + 4 * i, mb + (MB_W1T + i) * 8); }
      __syncwarp();
    };
    if (!W1_LATE && pw < W1_WARPS) for (int i = 0; i < W1_DEPTH; i++) w1_issue(pw + W1_WARPS * i);
    {
      const int j1 = b >> 4, q = b & 15, slot = lane & 15, h = lane >> 4;
      const bool hi = q >= 8;
      const int k = 16 * (q & 7) + slot, col = hi ? 256 - k : (k == 0 ? 128 : k);
      const int j0 = j1 + 8 * h + 512 * pw, o0 = (hi ? 2048 - 31 * 16 - j0 : j0) * DF + col, o31 = hi && j0 == 0 ? o0 - 2048 * DF : o0;
      uint32_t vr[32], vi[32];
      if (FILT_LATE) { asm volatile("bar.sync 3, 160;" ::: "memory"); asm volatile("" : "+l"(wr), "+l"(wi)); }
#pragma unroll
      for (int n = 0; n < 32; n++) { vr[n] = __ldg(wr + (n == 31 ? o31 : o0) + n * 16 * DF); vi[n] = __ldg(wi + (n == 31 ? o31 : o0) + n * 16 * DF); }
      const uint32_t f0 = sb + FILT_OFF + pw * 4096 + (hi ? 31 * 128 : 0) + h * 8 + (slot & 1) * 4, sw = ((slot >> 1) ^ (hi ? 7 : 0)) << 4;
      const int st = hi ? -128 : 128;
#pragma unroll
      for (int n = 0; n < 32; n++)
        sts32(f0 + n * st + (sw ^ ((((n >> 3) & 3) * 2 + (n & 1)) << 4)), __byte_perm(vr[n], vi[n], 0x5410) ^ (hi ? 0x80000000u : 0u));
      asm volatile("bar.sync 2, 128;" ::: "memory");
      if (threadIdx.x == 352) mbar_arrive(mb + MB_FILT * 8);
    }
    __syncwarp();
    STAMP(1);
    {
      if (W1_LATE && pw < W1_WARPS) for (int i = 0; i < W1_DEPTH; i++) w1_issue(pw + W1_WARPS * i);
      const uint32_t rd = ((lane & 7) * 11 + (lane >> 3)) * 16, wr = lane * 16;
#pragma unroll 1
      for (int box = pw < W1_WARPS ? pw : 32; box < W1_END; box += W1_WARPS) {
        mbar_wait(mb + (MB_W1T + box) * 8, 0);
        if (box + W1_WARPS * W1_DEPTH < 32) w1_issue(box + W1_WARPS * W1_DEPTH);
        const uint32_t p = sb + box * 5632;
        uint4 v[4][3];
#pragma unroll
        for (int n = 0; n < 4; n++) { v[n][0] = lds128(p + n * 1408 + rd); v[n][1] = lds128(p + n * 1408 + rd + 64); if (lane < 24) v[n][2] = lds128(p + n * 1408 + rd + 128); }
        __syncwarp();
#pragma unroll
        for (int n = 0; n < 4; n++) { sts128(p + n * 1408 + wr, v[n][0]); sts128(p + n * 1408 + wr + 512, v[n][1]); if (lane < 24) sts128(p + n * 1408 + wr + 1024, v[n][2]); }
      }
      if (lane == 0) asm volatile("cp.async.bulk.prefetch.L2.global [%0], %1;" :: "l"(w2 + (size_t)(b * 4 + pw) * 11008), "r"(11008) : "memory");
      asm volatile("fence.proxy.async.shared::cta;" ::: "memory");
      asm volatile("bar.sync 2, 128;" ::: "memory");
      if (threadIdx.x == 352) mbar_arrive(mb + MB_W1 * 8);
    }
    STAMP(2);
    asm volatile("barrier.cluster.wait.aligned;" ::: "memory");
    if (pw == 3) {
#pragma unroll 1
      for (int n = 0; n < 22; n++) {
        if (n < W2_PRE) mbar_wait(mb + (MB_EMPTY + min(31, max(((n + 4) * 16 + 10) / 11 - 1, W2_START + n * W2_NUM / W2_DEN))) * 8, 0);
        else { mbar_wait(mb + MB_X1DONE * 8, 0); if (W2_PACE) mbar_wait(mb + (MB_FULL + 32 - W2_PRE + n) * 8, 0); }
        if (elect()) { mbar_expect(mb + (MB_W2 + n) * 8, 8192); tma3d(sb + (n < 19 ? n + 3 : n - 19) * 8192, &tmW2, 0, 688 * rank + 32 * n, 2 * ot, mb + (MB_W2 + n) * 8); }
      }
    } else {
      int i = pw;
      uint32_t dst = sb + RING_OFF + pw * 8192;
      const uint32_t dsum = 2 * dst + 3 * 8192;
      const char* src = (const char*)g_Hn + ((size_t)dt * 128 + 64 * rank) * 4096;
#pragma unroll 1
      for (int gm = 0; gm < 2; gm++) {
        if (pw == 0) {
          mbar_wait(mb + (gm ? MB_X1DONE : MB_P3DONE) * 8, 0);
          STAMP(3 + 2 * gm);
          if (lane == 0) cnt_wait<true>(scr, gm ? 4 + dt : 2 + rank, ot & (NREP - 1), ((lds32(sb + BASE_OFF) >> 1) + 64) >> gm);
        }
        asm volatile("bar.sync 2, 96;" ::: "memory");
        STAMP(4 + 2 * gm);
        asm volatile("fence.proxy.async.global;" ::: "memory");
#pragma unroll 1
        for (; i < (gm ? 54 : 32); i += 3) {
          if (i >= NST) mbar_wait(mb + (MB_EMPTY - NST + i) * 8, 0);
          if (elect()) {
            const int bytes = i < 53 ? 8192 : 4096;
            mbar_expect(mb + (MB_FULL + i) * 8, bytes); bulk_ld(dst, src + i * 8192, bytes, mb + (MB_FULL + i) * 8);
          }
          dst = dsum - dst;
        }
        src = (const char*)g_U + ((size_t)dt * 172 + 86 * rank) * 2048 - 32 * 8192;
      }
      STAMP(7);
    }
  }
}

typedef CUresult (*EncodeFn)(CUtensorMap*, CUtensorMapDataType, cuuint32_t, void*, const cuuint64_t*, const cuuint64_t*, const cuuint32_t*,
                             const cuuint32_t*, CUtensorMapInterleave, CUtensorMapSwizzle, CUtensorMapL2promotion, CUtensorMapFloatOOBfill);

extern "C" void kernel_launch(void* const* d_in, const int* in_sizes, int n_in, void* d_out, int out_size) {
  static EncodeFn enc = nullptr;
  static void* scr = nullptr;
  if (!enc) {
    void* fn = nullptr; cudaDriverEntryPointQueryResult st;
    cudaGetDriverEntryPoint("cuTensorMapEncodeTiled", &fn, cudaEnableDefault, &st);
    enc = (EncodeFn)fn;
    cudaGetSymbolAddress(&scr, g_scr);
    cudaFuncSetAttribute(fused_kernel, cudaFuncAttributeMaxDynamicSharedMemorySize, SMEM_BYTES);
  }
  CUtensorMap tm, tm1;
  {
    cuuint64_t dims[3] = {(cuuint64_t)F_, 8, 256}, strides[2] = {(cuuint64_t)256 * F_ * 2, F_ * 2};
    cuuint32_t box[3] = {88, 8, 4}, es[3] = {1, 1, 1};
    enc(&tm1, CU_TENSOR_MAP_DATA_TYPE_BFLOAT16, 3, d_in[4], dims, strides, box, es, CU_TENSOR_MAP_INTERLEAVE_NONE, CU_TENSOR_MAP_SWIZZLE_NONE,
        W1_PROMO, CU_TENSOR_MAP_FLOAT_OOB_FILL_NONE);
  }
  {
    cuuint64_t dims[3] = {64, (cuuint64_t)F_, S_ / 64}, strides[2] = {S_ * 2, 128};
    cuuint32_t box[3] = {64, 32, 2}, es[3] = {1, 1, 1};
    enc(&tm, CU_TENSOR_MAP_DATA_TYPE_BFLOAT16, 3, d_in[6], dims, strides, box, es, CU_TENSOR_MAP_INTERLEAVE_NONE, CU_TENSOR_MAP_SWIZZLE_128B,
        CU_TENSOR_MAP_L2_PROMOTION_L2_256B, CU_TENSOR_MAP_FLOAT_OOB_FILL_NONE);
  }
  fused_kernel<<<NCTA, 384, SMEM_BYTES, cudaStreamPerThread>>>((const uint2*)d_in[0], (Scratch*)scr, (const unsigned short*)d_in[1], (const unsigned short*)d_in[2],
                                          (const uint32_t*)d_in[5], (const unsigned short*)d_in[7], (uint4*)d_out, (const char*)d_in[6], tm1, tm);
}
```

```cpp
#include <cuda_runtime.h>
#include <cuda.h>
#include <cuda_bf16.h>
#include <stdint.h>
#define W1_LATE 1
#define W1_PROMO CU_TENSOR_MAP_L2_PROMOTION_NONE
#define W2_NUM 1
#define W2_DEN 1
#define PF_W1 0
#define W1_DEPTH 1
#define W1_WARPS 4
#define W2_PRE 12
#define W2_PACE 1
#define FILT_LATE 0
#define W1_END 32
template<int TA, int TB, uint32_t HA, uint32_t HB> __device__ __forceinline__ void wgmma_n88_ss(float (&d)[44], uint32_t da, uint32_t db, int sd) {
  asm volatile("{\n.reg .pred p;\n.reg .b64 da, db;\nsetp.ne.b32 p, %46, 0;\nmov.b64 da, {%44, %49};\nmov.b64 db, {%45, %50};\n"
    "wgmma.mma_async.sync.aligned.m64n88k16.f32.bf16.bf16 {%0, %1, %2, %3, %4, %5, %6, %7, %8, %9, %10, %11, %12, %13, %14, %15, %16, %17, %18, %19, %20, %21, %22, %23, %24, %25, %26, %27, %28, %29, %30, %31, %32, %33, %34, %35, %36, %37, %38, %39, %40, %41, %42, %43}, da, db, p, 1, 1, %47, %48;\n}\n"
    : "+f"(d[0]), "+f"(d[1]), "+f"(d[2]), "+f"(d[3]), "+f"(d[4]), "+f"(d[5]), "+f"(d[6]), "+f"(d[7]), "+f"(d[8]), "+f"(d[9]), "+f"(d[10]), "+f"(d[11]), "+f"(d[12]), "+f"(d[13]), "+f"(d[14]), "+f"(d[15]), "+f"(d[16]), "+f"(d[17]), "+f"(d[18]), "+f"(d[19]), "+f"(d[20]), "+f"(d[21]), "+f"(d[22]), "+f"(d[23]), "+f"(d[24]), "+f"(d[25]), "+f"(d[26]), "+f"(d[27]), "+f"(d[28]), "+f"(d[29]), "+f"(d[30]), "+f"(d[31]), "+f"(d[32]), "+f"(d[33]), "+f"(d[34]), "+f"(d[35]), "+f"(d[36]), "+f"(d[37]), "+f"(d[38]), "+f"(d[39]), "+f"(d[40]), "+f"(d[41]), "+f"(d[42]), "+f"(d[43]) : "r"(da), "r"(db), "r"(sd), "n"(TA), "n"(TB), "n"(HA), "n"(HB));
}
template<int TA, int TB, uint32_t HA, uint32_t HB> __device__ __forceinline__ void wgmma_n128_ss(float (&d)[64], uint32_t da, uint32_t db, int sd) {
  asm volatile("{\n.reg .pred p;\n.reg .b64 da, db;\nsetp.ne.b32 p, %66, 0;\nmov.b64 da, {%64, %69};\nmov.b64 db, {%65, %70};\n"
    "wgmma.mma_async.sync.aligned.m64n128k16.f32.bf16.bf16 {%0, %1, %2, %3, %4, %5, %6, %7, %8, %9, %10, %11, %12, %13, %14, %15, %16, %17, %18, %19, %20, %21, %22, %23, %24, %25, %26, %27, %28, %29, %30, %31, %32, %33, %34, %35, %36, %37, %38, %39, %40, %41, %42, %43, %44, %45, %46, %47, %48, %49, %50, %51, %52, %53, %54, %55, %56, %57, %58, %59, %60, %61, %62, %63}, da, db, p, 1, 1, %67, %68;\n}\n"
    : "+f"(d[0]), "+f"(d[1]), "+f"(d[2]), "+f"(d[3]), "+f"(d[4]), "+f"(d[5]), "+f"(d[6]), "+f"(d[7]), "+f"(d[8]), "+f"(d[9]), "+f"(d[10]), "+f"(d[11]), "+f"(d[12]), "+f"(d[13]), "+f"(d[14]), "+f"(d[15]), "+f"(d[16]), "+f"(d[17]), "+f"(d[18]), "+f"(d[19]), "+f"(d[20]), "+f"(d[21]), "+f"(d[22]), "+f"(d[23]), "+f"(d[24]), "+f"(d[25]), "+f"(d[26]), "+f"(d[27]), "+f"(d[28]), "+f"(d[29]), "+f"(d[30]), "+f"(d[31]), "+f"(d[32]), "+f"(d[33]), "+f"(d[34]), "+f"(d[35]), "+f"(d[36]), "+f"(d[37]), "+f"(d[38]), "+f"(d[39]), "+f"(d[40]), "+f"(d[41]), "+f"(d[42]), "+f"(d[43]), "+f"(d[44]), "+f"(d[45]), "+f"(d[46]), "+f"(d[47]), "+f"(d[48]), "+f"(d[49]), "+f"(d[50]), "+f"(d[51]), "+f"(d[52]), "+f"(d[53]), "+f"(d[54]), "+f"(d[55]), "+f"(d[56]), "+f"(d[57]), "+f"(d[58]), "+f"(d[59]), "+f"(d[60]), "+f"(d[61]), "+f"(d[62]), "+f"(d[63]) : "r"(da), "r"(db), "r"(sd), "n"(TA), "n"(TB), "n"(HA), "n"(HB));
}

constexpr int S_ = 2048, F_ = 1376, DF = 257;
constexpr int NCTA = 128;
constexpr int W_BYTES = 180224;
constexpr int RING_OFF = W_BYTES;
constexpr int NST = 6;
constexpr int BAR_OFF = RING_OFF + NST * 8192;
constexpr int SMEM_BYTES = BAR_OFF + 1536;
constexpr int FILT_OFF = RING_OFF;
constexpr int XCH_OFF = RING_OFF + 16384;
constexpr int ZROW = 328;
constexpr int MB_FULL = 0, MB_W2 = 54, MB_W1T = 76, MB_X1 = 108, MB_X2 = 109, MB_X1DONE = 110, MB_P3DONE = 111, MB_FILT = 112, MB_W1 = 113,
              MB_EMPTY = 114, MB_PEER1 = 168, MB_PEER2 = 169, MB_N = 171;
constexpr int BASE_OFF = BAR_OFF + MB_N * 8;
#define W2_START 24

struct Scratch {
  uint4 T1[NCTA * 1024], T2[NCTA * 1024], Hn[4 * 128 * 256], U[4 * 172 * 128];
  float2 st[S_];
  unsigned cnt[8 * 4 * 64];
};
__device__ __align__(1024) Scratch g_scr;
#define g_T1 (scr->T1)
#define g_T2 (scr->T2)
#define g_Hn (scr->Hn)
#define g_U (scr->U)
#define g_st (scr->st)
#define g_cnt (scr->cnt)
#define STAMP(i)

__device__ __forceinline__ void mbar_init(uint32_t b, int c) { asm volatile("mbarrier.init.shared::cta.b64 [%0], %1;" :: "r"(b), "r"(c) : "memory"); }
__device__ __forceinline__ void mbar_expect(uint32_t b, int bytes) { asm volatile("mbarrier.arrive.expect_tx.shared::cta.b64 _, [%0], %1;" :: "r"(b), "r"(bytes) : "memory"); }
__device__ __forceinline__ void mbar_arrive(uint32_t b) { asm volatile("mbarrier.arrive.shared::cta.b64 _, [%0];" :: "r"(b) : "memory"); }
__device__ __forceinline__ void mbar_arrive_cluster(uint32_t remote) { asm volatile("mbarrier.arrive.relaxed.cluster.shared::cluster.b64 _, [%0];" :: "r"(remote) : "memory"); }
__device__ __forceinline__ uint32_t mapa(uint32_t a, uint32_t cta) { uint32_t r; asm("mapa.shared::cluster.u32 %0, %1, %2;" : "=r"(r) : "r"(a), "r"(cta)); return r; }
__device__ __forceinline__ void mbar_wait(uint32_t b, int ph) {
  asm volatile("{\n.reg .pred p;\n.reg .u32 n;\nmov.u32 n, 0;\nL_W:\n"
               "mbarrier.try_wait.parity.shared::cta.b64 p, [%0], %1;\n@p bra L_D;\n"
               "add.u32 n, n, 1;\nsetp.lt.u32 p, n, 4000000;\n@p bra L_W;\ntrap;\nL_D:\n}" :: "r"(b), "r"(ph) : "memory");
}
__device__ __forceinline__ void mbar_wait_cluster(uint32_t b, int ph) {
  asm volatile("{\n.reg .pred p;\n.reg .u32 n;\nmov.u32 n, 0;\nL_W:\n"
               "mbarrier.try_wait.parity.acquire.cluster.shared::cta.b64 p, [%0], %1;\n@p bra L_D;\n"
               "add.u32 n, n, 1;\nsetp.lt.u32 p, n, 4000000;\n@p bra L_W;\ntrap;\nL_D:\n}" :: "r"(b), "r"(ph) : "memory");
}
__device__ __forceinline__ void bulk_ld(uint32_t dst, const void* src, int bytes, uint32_t bar) {
  asm volatile("cp.async.bulk.shared::cluster.global.mbarrier::complete_tx::bytes [%0], [%1], %2, [%3];" :: "r"(dst), "l"(src), "r"(bytes), "r"(bar) : "memory");
}
__device__ __forceinline__ void tma3d(uint32_t dst, const CUtensorMap* tm, int c0, int c1, int c2, uint32_t bar) {
  asm volatile("cp.async.bulk.tensor.3d.shared::cluster.global.mbarrier::complete_tx::bytes [%0], [%1, {%3, %4, %5}], [%2];"
               :: "r"(dst), "l"(tm), "r"(bar), "r"(c0), "r"(c1), "r"(c2) : "memory");
}
__device__ __forceinline__ bool elect() { uint32_t p; asm volatile("{.reg .pred p; elect.sync _|p, 0xffffffff; selp.b32 %0, 1, 0, p;}" : "=r"(p)); return p; }
__device__ __forceinline__ uint32_t desc_lo(uint32_t addr, uint32_t lbo) { return ((addr & 0x3FFFF) >> 4) | ((lbo >> 4) << 16); }
constexpr uint32_t HI_SW128 = (1024 >> 4) | (1u << 30), HI_NOSW = 128 >> 4;
__device__ __forceinline__ uint32_t pk(float lo, float hi) { uint32_t r; asm("cvt.rn.bf16x2.f32 %0, %1, %2;" : "=r"(r) : "f"(hi), "f"(lo)); return r; }
__device__ __forceinline__ float blo(uint32_t w) { return __uint_as_float(w << 16); }
__device__ __forceinline__ float bhi(uint32_t w) { return __uint_as_float(w & 0xffff0000u); }
__device__ __forceinline__ void mmac(float (&d)[4], const float (&c)[4], const uint32_t (&a)[4], uint32_t b0, uint32_t b1) {
  asm("mma.sync.aligned.m16n8k16.row.col.f32.bf16.bf16.f32 {%0,%1,%2,%3}, {%4,%5,%6,%7}, {%8,%9}, {%10,%11,%12,%13};"
      : "=f"(d[0]), "=f"(d[1]), "=f"(d[2]), "=f"(d[3]) : "r"(a[0]), "r"(a[1]), "r"(a[2]), "r"(a[3]), "r"(b0), "r"(b1), "f"(c[0]), "f"(c[1]), "f"(c[2]), "f"(c[3]));
}
__device__ __forceinline__ void mma0(float (&d)[4], const uint32_t (&a)[4], uint32_t b0, uint32_t b1) { const float z[4] = {0.f, 0.f, 0.f, 0.f}; mmac(d, z, a, b0, b1); }
__device__ __forceinline__ uint32_t pin(uint32_t v) { asm volatile("shfl.sync.bfly.b32 %0, %0, 0, 31, 0xffffffff;" : "+r"(v)); return v; }
__device__ __forceinline__ float pinf(float v) { return __uint_as_float(pin(__float_as_uint(v))); }
__device__ __forceinline__ void wbar() { asm volatile("bar.sync 1, 256;" ::: "memory"); }
__device__ __forceinline__ void sts32(uint32_t a, uint32_t v) { asm volatile("st.shared.b32 [%0], %1;" :: "r"(a), "r"(v) : "memory"); }
__device__ __forceinline__ void sts64(uint32_t a, uint32_t x, uint32_t y) { asm volatile("st.shared.v2.b32 [%0], {%1,%2};" :: "r"(a), "r"(x), "r"(y) : "memory"); }
__device__ __forceinline__ void sts128(uint32_t a, uint4 v) { asm volatile("st.shared.v4.b32 [%0], {%1,%2,%3,%4};" :: "r"(a), "r"(v.x), "r"(v.y), "r"(v.z), "r"(v.w) : "memory"); }
__device__ __forceinline__ uint32_t lds32(uint32_t a) { uint32_t v; asm volatile("ld.shared.b32 %0, [%1];" : "=r"(v) : "r"(a) : "memory"); return v; }
__device__ __forceinline__ uint2 lds64(uint32_t a) { uint2 v; asm volatile("ld.shared.v2.b32 {%0,%1}, [%2];" : "=r"(v.x), "=r"(v.y) : "r"(a) : "memory"); return v; }
__device__ __forceinline__ uint4 lds128(uint32_t a) { uint4 v; asm volatile("ld.shared.v4.b32 {%0,%1,%2,%3}, [%4];" : "=r"(v.x), "=r"(v.y), "=r"(v.z), "=r"(v.w) : "r"(a) : "memory"); return v; }
__device__ __forceinline__ uint4 ldcg128(const void* p) { uint4 v; asm volatile("ld.global.cg.v4.b32 {%0,%1,%2,%3}, [%4];" : "=r"(v.x), "=r"(v.y), "=r"(v.z), "=r"(v.w) : "l"(p) : "memory"); return v; }
__device__ __forceinline__ void st_async4(uint32_t a, uint32_t x, uint32_t y, uint32_t z, uint32_t w, uint32_t bar) {
  asm volatile("st.async.weak.shared::cluster.mbarrier::complete_tx::bytes.v4.b32 [%0], {%1,%2,%3,%4}, [%5];" :: "r"(a), "r"(x), "r"(y), "r"(z), "r"(w), "r"(bar) : "memory");
}
constexpr int NREP = 4;
__device__ __forceinline__ void cnt_arrive(Scratch* scr, int i, int lane) {
  if (lane < NREP) asm volatile("red.relaxed.gpu.global.add.u32 [%0], 1;" :: "l"(&g_cnt[(i * NREP + lane) * 64]) : "memory");
}
template <bool ACQ> __device__ __forceinline__ void cnt_wait(Scratch* scr, int i, int rep, unsigned target) {
  unsigned v; int n = 0;
  do {
    if (ACQ) asm volatile("ld.acquire.gpu.global.u32 %0, [%1];" : "=r"(v) : "l"(&g_cnt[(i * NREP + rep) * 64]) : "memory");
    else asm volatile("ld.relaxed.gpu.global.u32 %0, [%1];" : "=r"(v) : "l"(&g_cnt[(i * NREP + rep) * 64]) : "memory");
    if (++n > 2000000) __trap(); } while ((int)(v - target) < 0);
}
__device__ __forceinline__ void fence_gpu() { asm volatile("fence.acq_rel.gpu;" ::: "memory"); }
__device__ __forceinline__ void tag_check(uint4& v, const uint4* p, uint32_t tag) {
  int n = 0;
  while ((v.x ^ tag) & 1) {
    asm volatile("ld.relaxed.gpu.global.v4.b32 {%0,%1,%2,%3}, [%4];" : "=r"(v.x), "=r"(v.y), "=r"(v.z), "=r"(v.w) : "l"(p) : "memory");
    if (++n > 2000000) __trap();
  }
}
template <int N> __device__ __forceinline__ void cs(int n, float& c, float& s) {
  n = ((n + N / 2) & (N - 1)) - N / 2;
  float a = (float)n * (6.283185307179586f / N);
  c = __cosf(a); s = __sinf(a);
}
constexpr float ALPHA = 1.13288f;
struct FftC { uint32_t a[4][4], b[8][2]; float tc[2][4], ts[2][4]; };
constexpr uint32_t NEG = 0x80008000u;

__device__ __forceinline__ void fft_s1(const FftC& K, const uint32_t (&in)[4][2], float (&cr)[2][4], float (&ci)[2][4]) {
#pragma unroll
  for (int h = 0; h < 2; h++) { mma0(cr[h], K.a[0], in[0][h], in[1][h]); mma0(ci[h], K.a[1], in[0][h], in[1][h]); }
#pragma unroll
  for (int h = 0; h < 2; h++) { mmac(cr[h], cr[h], K.a[2], in[2][h], in[3][h]); mmac(ci[h], ci[h], K.a[3], in[2][h], in[3][h]); }
}
__device__ __forceinline__ void fft_s2(const FftC& K, const float (&cr)[2][4], const float (&ci)[2][4], float (&o)[4][4]) {
  uint32_t a[2][4];
#pragma unroll
  for (int h = 0; h < 2; h++)
#pragma unroll
    for (int i = 0; i < 4; i++) {
      float xr = cr[i & 1][2 * h + (i >> 1)], xi = ci[i & 1][2 * h + (i >> 1)];
      a[i >> 1][2 * (i & 1) + h] = pk(xr * K.tc[h][i] + xi * K.ts[h][i], xi * K.tc[h][i] - xr * K.ts[h][i]);
    }
#pragma unroll
  for (int j = 0; j < 4; j++) mma0(o[j], a[0], K.b[j][0], K.b[j][1]);
#pragma unroll
  for (int j = 0; j < 4; j++) mmac(o[j], o[j], a[1], K.b[4 + j][0], K.b[4 + j][1]);
}
__device__ __forceinline__ int zphys(int k) { return k + 8 * (k >> 5); }
__device__ __forceinline__ float gelu(float u) {
  float z = u * (0.7978845608028654f + 0.035677408136300125f * u * u), th;
  asm("tanh.approx.f32 %0, %1;" : "=f"(th) : "f"(z));
  float hu = 0.5f * u;
  return fmaf(hu, th, hu);
}

extern "C" __global__ void __cluster_dims__(2, 1, 1) __launch_bounds__(384, 1)
fused_kernel(const uint2* __restrict__ x, Scratch* scr, const unsigned short* __restrict__ wr, const unsigned short* __restrict__ wi,
             const uint32_t* __restrict__ b1, const unsigned short* __restrict__ b2, uint4* __restrict__ out, const char* __restrict__ w2,
             const __grid_constant__ CUtensorMap tmW1, const __grid_constant__ CUtensorMap tmW2) {
  extern __shared__ __align__(1024) char smem[];
  const uint32_t sb = (uint32_t)__cvta_generic_to_shared(smem);
  const uint32_t mb = sb + BAR_OFF;
  const int b = blockIdx.x, rank = b & 1, pr = b >> 1, dt = pr & 3, ot = pr >> 2;
  const int warp = __shfl_sync(0xffffffffu, threadIdx.x >> 5, 0), lane = threadIdx.x & 31;
  const int g = lane >> 2, t = lane & 3;

  if (warp < 8) {
    const int tid = threadIdx.x;
    uint32_t xw[2][4][2];
    {
      const uint2* xp = x + (size_t)(256 * warp + 2 * b) * 128 + 8 * t + g;
#pragma unroll
      for (int a = 0; a < 2; a++)
#pragma unroll
        for (int j = 0; j < 4; j++) { uint2 v = __ldg(xp + a * 128 + 32 * j); xw[a][j][0] = v.x; xw[a][j][1] = v.y; }
    }
    STAMP(0);
    asm volatile("barrier.cluster.arrive.relaxed.aligned;" ::: "memory");
    const int rep = ot & (NREP - 1);
    unsigned base;
    asm volatile("ld.relaxed.gpu.global.u32 %0, [%1];" : "=r"(base) : "l"(&g_cnt[(1 * NREP + rep) * 64]) : "memory");
    FftC K;
    {
      float c, s;
#pragma unroll
      for (int h = 0; h < 2; h++)
#pragma unroll
        for (int j = 0; j < 2; j++) {
          cs<16>((2 * g + h) * (t + 4 * j), c, s);
          const uint32_t re = pk(ALPHA * c, ALPHA * s), im = pk(-ALPHA * s, ALPHA * c);
          K.a[0][2 * j + h] = re; K.a[1][2 * j + h] = im; K.a[2][2 * j + h] = pin(h ? re ^ NEG : re); K.a[3][2 * j + h] = pin(h ? im ^ NEG : im);
        }
#pragma unroll
      for (int i = 0; i < 4; i++) {
        cs<16>((4 * t + i) * (g >> 1) + 4 * (g & 1), c, s);
        const uint32_t P = pk(ALPHA * c, ALPHA * s), Q = pk(-ALPHA * s, ALPHA * c);
#pragma unroll
        for (int jj = 0; jj < 4; jj++) { const uint32_t v = ((i * jj) & 1 ? Q : P) ^ ((i * jj) & 2 ? NEG : 0u); K.b[4 * (i >> 1) + jj][i & 1] = jj ? pin(v) : v; }
      }
#pragma unroll
      for (int h = 0; h < 2; h++)
#pragma unroll
        for (int i = 0; i < 4; i++) {
          cs<256>((2 * g + h) * (4 * t + i), c, s);
          K.tc[h][i] = pinf(c * (1.f / (ALPHA * ALPHA))); K.ts[h][i] = pinf(s * (1.f / (ALPHA * ALPHA)));
        }
    }
    const int key = ((b >> 3) & 3) * 2 + (b & 1);
    const uint32_t zb = sb + XCH_OFF;
    float mean[2];
    uint32_t tag;
    {
      uint32_t a8[2][4], a8c[2][4], a8n[2][4]; float vc[4], vs[4];
#pragma unroll
      for (int a = 0; a < 2; a++)
#pragma unroll
        for (int u = 0; u < 4; u++) {
          float c, s; cs<2048>(g * (256 * (t + 4 * (u >> 1)) + 2 * b + a), c, s);
          a8[a][u] = u & 1 ? pk(-s, c) : pk(c, s);
          a8c[a][u] = pin(a8[a][u] ^ 0x80000000u); a8n[a][u] = pin(a8[a][u] ^ 0x00008000u);
        }
#pragma unroll
      for (int i = 0; i < 4; i++) { cs<512>(16 * warp + 8 * (i >> 1) + 2 * t + (i & 1) + 128, vc[i], vs[i]); vc[i] = pinf(vc[i]); vs[i] = pinf(vs[i]); }
      STAMP(13);
      for (int n = 0; (base & 127u) && n < 1000; n++) asm volatile("ld.relaxed.gpu.global.u32 %0, [%1];" : "=r"(base) : "l"(&g_cnt[(1 * NREP + rep) * 64]) : "memory");
      __syncwarp();
      tag = (~base >> 7) & 1;
#pragma unroll
      for (int a = 0; a < 2; a++) {
        float cr[2][4], ci[2][4], o[4][4];
        if (a == 0) { if (xw[0][0][0] == 0x12345678u && xw[1][3][1] == 0x12345679u) STAMP(31); STAMP(14); }
        fft_s1(K, xw[a], cr, ci);
        if (FILT_LATE && a == 0 && warp == 0) asm volatile("bar.arrive 3, 160;" :: "f"(cr[0][0]) : "memory");
        float sm = ((cr[0][0] + cr[0][1]) + (cr[1][0] + cr[1][1])) + ((ci[0][0] + ci[0][1]) + (ci[1][0] + ci[1][1]));
        sm += __shfl_xor_sync(0xffffffffu, sm, 1); sm += __shfl_xor_sync(0xffffffffu, sm, 2);
        sm = g == 0 ? sm * (1.f / 32.f) : 0.f;
#pragma unroll
        for (int h = 0; h < 2; h++) { cr[h][0] -= sm; cr[h][1] -= sm; ci[h][0] -= sm; ci[h][1] -= sm; }
        mean[a] = __shfl_sync(0xffffffffu, sm, 0) * (1.f / (16.f * 1.1328125f));
        float q = 0.f, q2 = 0.f;
#pragma unroll
        for (int i = 0; i < 4; i++) { q = fmaf(cr[0][i], cr[0][i], q); q2 = fmaf(cr[1][i], cr[1][i], q2); q = fmaf(ci[0][i], ci[0][i], q); q2 = fmaf(ci[1][i], ci[1][i], q2); }
        q += q2;
#pragma unroll
        for (int m = 1; m < 32; m <<= 1) q += __shfl_xor_sync(0xffffffffu, q, m);
        float r = rsqrtf(q * (1.f / (512.f * 16.f * ALPHA * ALPHA)) + 1e-5f) * 4.76837158203125e-7f;
        fft_s2(K, cr, ci, o);
#pragma unroll
        for (int j = 0; j < 4; j++)
          sts64(zb + ((a * 8 + warp) * ZROW + zphys(16 * t + 64 * j) + 2 * g) * 4, pk(o[j][0] * r, o[j][1] * r), pk(o[j][2] * r, o[j][3] * r));
      }
      STAMP(15);
      wbar();
      uint4* tp = g_T1 + (size_t)(g * 16 + warp) * 1024 + b * 8;
#pragma unroll
      for (int nt = 0; nt < 2; nt++) {
        const int k = 16 * warp + 8 * nt + g, km = k == 0 ? 128 : 256 - k;
        uint32_t lo[4], hi[4];
#pragma unroll
        for (int a = 0; a < 2; a++) {
          const uint32_t rb = zb + (a * 8 + t) * ZROW * 4;
          float A[4], S[4], D[4];
          const uint32_t m0 = lds32(rb + zphys(km) * 4), m1 = lds32(rb + (4 * ZROW + zphys(km)) * 4);
          mma0(A, a8[a], lds32(rb + zphys(k) * 4), lds32(rb + (4 * ZROW + zphys(k)) * 4));
          mmac(S, A, a8c[a], m0, m1);
          mmac(D, A, a8n[a], m0, m1);
#pragma unroll
          for (int e = 0; e < 2; e++) {
            const float c = vc[2 * nt + e], s = vs[2 * nt + e];
            float lr = fmaf(D[2 + e], s, fmaf(D[e], c, S[e])), li = fmaf(-D[e], s, fmaf(D[2 + e], c, S[2 + e]));
            float hr = fmaf(2.f, S[e], -lr), hii = fmaf(2.f, S[2 + e], -li);
            if (nt == 0 && e == 0) {
              const bool sp = warp == 0 && t == 0;
              lr = sp ? S[0] - D[0] : lr; li = sp ? S[2] - D[2] : li;
              hr = sp ? 2.f * (A[0] - A[2]) : hr; hii = sp ? 2.f * (A[0] + A[2]) : hii;
            }
            lo[2 * a + e] = pk(lr, li); hi[2 * a + e] = pk(hr, hii);
          }
        }
        const int w = (t + 4 * nt) ^ key;
        tp[w] = make_uint4((lo[0] & ~1u) | tag, lo[1], lo[2], lo[3]);
        tp[8 * 1024 + w] = make_uint4((hi[0] & ~1u) | tag, hi[1], hi[2], hi[3]);
      }
      wbar();
      STAMP(1);
      if (warp == 0) cnt_arrive(scr, 0, lane);
    }
    {
      const uint32_t off = (8 * t + g) * 128 + ((warp ^ (2 * t + (g & 1))) << 4);
      asm volatile("barrier.cluster.wait.aligned;" ::: "memory");
      mbar_wait(mb + MB_FILT * 8, 0);
      if (tid == 0) cnt_wait<false>(scr, 0, rep, base + NCTA);
      wbar();
#pragma unroll
      for (int j = 0; j < 4; j++)
        asm volatile("cp.async.cg.shared.global [%0], [%1], 16;" :: "r"(zb + j * 4096 + tid * 16), "l"(g_T1 + (size_t)b * 1024 + j * 256 + tid) : "memory");
      STAMP(2);
      uint32_t in[2][4][2], fw[2][4][2];
#pragma unroll
      for (int j = 0; j < 4; j++) {
        uint4 v = lds128(sb + FILT_OFF + off + j * 4096);
        fw[0][j][0] = v.x; fw[1][j][0] = v.y; fw[0][j][1] = v.z; fw[1][j][1] = v.w;
      }
      asm volatile("cp.async.wait_all;" ::: "memory");
      wbar();
      STAMP(3);
      uint4 iv[4];
#pragma unroll
      for (int j = 0; j < 4; j++) iv[j] = lds128(zb + off + j * 4096);
      if (((iv[0].x ^ tag) | (iv[1].x ^ tag) | (iv[2].x ^ tag) | (iv[3].x ^ tag)) & 1) {
#pragma unroll
        for (int j = 0; j < 4; j++) tag_check(iv[j], g_T1 + (size_t)b * 1024 + j * 256 + (off >> 4), tag);
      }
      __syncwarp();
#pragma unroll
      for (int j = 0; j < 4; j++) { in[0][j][0] = iv[j].x; in[1][j][0] = iv[j].y; in[0][j][1] = iv[j].z; in[1][j][1] = iv[j].w; }
#pragma unroll
      for (int sg = 0; sg < 2; sg++) {
        float cr[2][4], ci[2][4], o[4][4];
        fft_s1(K, in[sg], cr, ci);
        fft_s2(K, cr, ci, o);
#pragma unroll
        for (int j = 0; j < 4; j++)
#pragma unroll
          for (int h = 0; h < 2; h++) {
            float fr = blo(fw[sg][j][h]), fi = bhi(fw[sg][j][h]), xr = o[j][2 * h], xi = o[j][2 * h + 1];
            in[sg][j][h] = pk(xr * fi + xi * fr, xr * fr - xi * fi);
          }
        fft_s1(K, in[sg], cr, ci);
        fft_s2(K, cr, ci, o);
#pragma unroll
        for (int j = 0; j < 4; j++) { in[sg][j][0] = pk(o[j][0], o[j][1]); in[sg][j][1] = pk(o[j][2], o[j][3]); }
      }
#pragma unroll
      for (int j = 0; j < 4; j++) sts128(zb + off + j * 4096, make_uint4((in[0][j][0] & ~1u) | tag, in[1][j][0], in[0][j][1], in[1][j][1]));
      STAMP(16);
      wbar();
#pragma unroll
      for (int j = 0; j < 4; j++) g_T2[(size_t)b * 1024 + j * 256 + tid] = lds128(zb + j * 4096 + tid * 16);
      wbar();
      STAMP(4);
      if (warp == 0) cnt_arrive(scr, 1, lane);
    }
    {
      uint32_t a8[2][4], a8n[2][4]; float vc[4], vs[4];
#pragma unroll
      for (int a = 0; a < 2; a++)
#pragma unroll
        for (int u = 0; u < 4; u++) {
          float c, s; cs<2048>((t + 4 * (u >> 1)) * (256 * g + 2 * b + a), c, s);
          a8[a][u] = u & 1 ? pk(-s, c) : pk(c, s);
          a8n[a][u] = pin(a8[a][u] ^ NEG);
        }
#pragma unroll
      for (int i = 0; i < 4; i++) { cs<512>(16 * warp + 4 * t + i + 128, vc[i], vs[i]); vc[i] = pinf(vc[i]); vs[i] = pinf(vs[i]); }
      if (tid == 0) cnt_wait<false>(scr, 1, rep, base + NCTA);
      wbar();
      STAMP(5);
      const uint4* tp = g_T2 + (size_t)(t * 16 + warp) * 1024 + b * 8 + (g ^ key);
      uint4 L0 = ldcg128(tp), L1 = ldcg128(tp + 64 * 1024), H0 = ldcg128(tp + 8 * 1024), H1 = ldcg128(tp + 72 * 1024);
      if (((L0.x ^ tag) | (L1.x ^ tag) | (H0.x ^ tag) | (H1.x ^ tag)) & 1) {
        tag_check(L0, tp, tag); tag_check(L1, tp + 64 * 1024, tag); tag_check(H0, tp + 8 * 1024, tag); tag_check(H1, tp + 72 * 1024, tag);
      }
      __syncwarp();
      STAMP(17);
      const uint32_t l0[4] = {L0.x, L0.y, L0.z, L0.w}, l1[4] = {L1.x, L1.y, L1.z, L1.w}, h0[4] = {H0.x, H0.y, H0.z, H0.w}, h1[4] = {H1.x, H1.y, H1.z, H1.w};
#pragma unroll
      for (int a = 0; a < 2; a++) {
        uint32_t zf[4], zm[4];
#pragma unroll
        for (int sg = 0; sg < 2; sg++) {
          float A[4], S[4], D[4];
          mma0(A, a8[a], l0[2 * a + sg], l1[2 * a + sg]);
          mmac(S, A, a8[a], h0[2 * a + sg], h1[2 * a + sg]);
          mmac(D, A, a8n[a], h0[2 * a + sg], h1[2 * a + sg]);
#pragma unroll
          for (int e = 0; e < 2; e++) {
            const int i = 2 * e + sg;
            float fr = fmaf(-D[e], vs[i], fmaf(D[2 + e], vc[i], S[2 + e])), fi = fmaf(D[2 + e], vs[i], fmaf(D[e], vc[i], S[e]));
            float mr = fmaf(2.f, S[2 + e], -fr), mi = fmaf(-2.f, S[e], fi);
            if (i == 0) {
              const bool sp = warp == 0 && t == 0;
              fr = sp ? S[2] - A[2] : fr; fi = sp ? A[2] - S[2] : fi;
              mr = sp ? 2.f * A[2] : mr; mi = sp ? -2.f * A[0] : mi;
            }
            zf[i] = pk(fi, fr); zm[i] = pk(mi, mr);
          }
        }
        const uint32_t rb = zb + (a * 8 + g) * ZROW * 4;
        const int k0 = 16 * warp + 4 * t;
        sts128(rb + zphys(k0) * 4, make_uint4(zf[0], zf[1], zf[2], zf[3]));
        sts32(rb + zphys(k0 == 0 ? 128 : 256 - k0) * 4, zm[0]);
        sts32(rb + zphys(255 - k0) * 4, zm[1]);
        sts32(rb + zphys(254 - k0) * 4, zm[2]);
        sts32(rb + zphys(253 - k0) * 4, zm[3]);
      }
      STAMP(18);
      wbar();
      float o[2][4][4], s2[2];
#pragma unroll
      for (int a = 0; a < 2; a++) {
        uint32_t in[4][2];
#pragma unroll
        for (int j = 0; j < 4; j++) { uint2 v = lds64(zb + ((a * 8 + warp) * ZROW + zphys(16 * t + 64 * j) + 2 * g) * 4); in[j][0] = v.x; in[j][1] = v.y; }
        float cr[2][4], ci[2][4], s1 = 0.f;
        fft_s1(K, in, cr, ci);
        fft_s2(K, cr, ci, o[a]);
        s2[a] = 0.f;
#pragma unroll
        for (int j = 0; j < 4; j++)
#pragma unroll
          for (int h = 0; h < 2; h++) {
            uint32_t hw;
            asm("add.rn.bf16x2 %0, %1, %2;" : "=r"(hw) : "r"(xw[a][j][h]), "r"(pk(o[a][j][2 * h + 1], o[a][j][2 * h])));
            const float u0 = blo(hw) - mean[a], u1 = bhi(hw) - mean[a];
            o[a][j][2 * h] = u0; o[a][j][2 * h + 1] = u1;
            s1 = fmaf(u0, u0, s1); s2[a] = fmaf(u1, u1, s2[a]);
          }
        s2[a] += s1;
      }
      float sv = (lane < 16 ? s2[0] : s2[1]) + __shfl_xor_sync(0xffffffffu, lane < 16 ? s2[1] : s2[0], 16);
#pragma unroll
      for (int m = 1; m < 16; m <<= 1) sv += __shfl_xor_sync(0xffffffffu, sv, m);
      const float var = sv * (1.f / 512.f), r1 = rsqrtf(var + 1e-5f);
      const float rr = r1 * rsqrtf(var * r1 * r1 + 1e-5f);
      const float ro = __shfl_xor_sync(0xffffffffu, rr, 16);
      char* np = (char*)g_Hn + (size_t)b * 4096 + (t >> 1) * 2048 + warp * 128 + ((((t & 1) * 4 + (g >> 1)) ^ warp ^ (b >> 6)) << 4) + (g & 1) * 8;
#pragma unroll
      for (int a = 0; a < 2; a++) {
        const float r = (lane >> 4) == a ? rr : ro;
#pragma unroll
        for (int j = 0; j < 4; j++)
          *(uint2*)(np + a * 1024 + (size_t)j * 128 * 4096) = make_uint2(pk(o[a][j][0] * r, o[a][j][1] * r), pk(o[a][j][2] * r, o[a][j][3] * r));
      }
      if ((lane & 15) == 0) g_st[256 * warp + 2 * b + (lane >> 4)] = make_float2(__fdividef(1.f, rr), lane ? mean[1] : mean[0]);
      STAMP(19);
      asm volatile("fence.proxy.async.shared::cta;" ::: "memory");
      wbar();
      STAMP(6);
      if (warp == 0) { fence_gpu(); cnt_arrive(scr, 2 + (b >> 6), lane); STAMP(25); }
      if (tid == 32) { sts32(sb + BASE_OFF, base); mbar_arrive(mb + MB_P3DONE * 8); }
    }
    const int wg = warp >> 2;
    const uint32_t peer_sb = mapa(sb, rank ^ 1);
    {
      float acc[44];
#pragma unroll
      for (int j = 0; j < 11; j++) {
        const uint32_t bw = __ldg(b1 + min(11 * ot + j, 171) * 4 + t);
        acc[4 * j] = blo(bw); acc[4 * j + 1] = bhi(bw); acc[4 * j + 2] = 0.f; acc[4 * j + 3] = 0.f;
      }
      const uint32_t da0 = desc_lo(sb + RING_OFF + wg * 2048, 0);
      uint32_t da = da0, db = desc_lo(sb, 1408), bar = mb;
      mbar_wait(mb + MB_W1 * 8, 0);
#pragma unroll 1
      for (int i = 0; i < 32; i++) {
        mbar_wait(bar + MB_FULL * 8, 0);
        if (i == 0) STAMP(7);
        asm volatile("wgmma.fence.sync.aligned;" ::: "memory");
        wgmma_n88_ss<1, 1, HI_SW128, HI_NOSW>(acc, da, db, 1);
        wgmma_n88_ss<1, 1, HI_SW128, HI_NOSW>(acc, da + 256, db + 176, 1);
        asm volatile("wgmma.commit_group.sync.aligned;" ::: "memory");
        da = da == da0 + 5 * 512 ? da0 : da + 512; db += 352;
        asm volatile("wgmma.wait_group.sync.aligned 1;" ::: "memory");
        if ((tid & 127) == 0) { if (i > 0) mbar_arrive(bar + (MB_EMPTY - 1) * 8); if (i == 4) mbar_arrive_cluster(peer_sb + BAR_OFF + MB_PEER1 * 8); }
        bar += 8;
      }
      asm volatile("wgmma.wait_group.sync.aligned 0;" ::: "memory");
#pragma unroll
      for (int i = 0; i < 44; i++) asm volatile("" : "+f"(acc[i]) :: "memory");
      if ((tid & 127) == 0) mbar_arrive(mb + (MB_EMPTY + 31) * 8);
      STAMP(8);
      mbar_wait_cluster(mb + MB_PEER1 * 8, 0);
#pragma unroll
      for (int j = 0; j < 3; j++)
        st_async4(peer_sb + j * 4096 + tid * 16, pk(acc[16 * j + 2], acc[16 * j + 3]), pk(acc[16 * j + 6], acc[16 * j + 7]), pk(acc[16 * j + 10], acc[16 * j + 11]),
                  j < 2 ? pk(acc[16 * j + 14], acc[16 * j + 15]) : 0u, peer_sb + BAR_OFF + MB_X1 * 8);
      const int uo = (4 * (warp >> 1) + (g >> 1)) * 32 + (2 * (2 * (warp & 1) + rank) + (g & 1)) * 4 + t;
      uint32_t* const ub = (uint32_t*)g_U + ((size_t)dt * 172 + 11 * ot) * 512;
      uint32_t *upa = ub + (uo ^ (ot >= 8 ? 256 : 0)), *upb = ub + (uo ^ (ot >= 7 ? 256 : 0));
      STAMP(20);
      mbar_wait_cluster(mb + MB_X1 * 8, 0);
      STAMP(21);
      uint32_t pv[12];
#pragma unroll
      for (int j = 0; j < 3; j++) { const uint4 v = lds128(sb + j * 4096 + tid * 16); pv[4 * j] = v.x; pv[4 * j + 1] = v.y; pv[4 * j + 2] = v.z; pv[4 * j + 3] = v.w; }
#pragma unroll
      for (int j = 0; j < 11; j++) {
        uint32_t v = pk(gelu(acc[4 * j] + blo(pv[j])), gelu(acc[4 * j + 1] + bhi(pv[j])));
        if (j < 7 || ot < 15) (j < 9 ? upa : upb)[j * 512] = v;
      }
      STAMP(22);
      asm volatile("fence.proxy.async.shared::cta;" ::: "memory");
      wbar();
      STAMP(9);
      if (warp == 0) { fence_gpu(); cnt_arrive(scr, 4 + dt, lane); STAMP(26); }
      if (tid == 32) mbar_arrive(mb + MB_X1DONE * 8);
    }
    {
      const int srow = 128 * ot + 16 * warp + g, oo = srow * 64 + dt * 16 + 8 * rank + t;
      float acc[64];
      const uint32_t da0 = desc_lo(sb + wg * 4096, 0), db0 = desc_lo(sb + RING_OFF, 2048);
      uint32_t da = da0 + 3 * 512, db = db0 + (32 % NST) * 512, bar = mb;
#pragma unroll
      for (int u = 0; u < 2; u++) {
        const int sr = srow + 8 * u, s1 = ot >> 1;
        const float2 st = __ldcg(g_st + sr);
        const float off = st.y + __uint_as_float((uint32_t)__ldg(b2 + sr) << 16);
#pragma unroll
        for (int jj = 0; jj < 2; jj++) {
          const uint4 v = ldcg128(g_Hn + (dt * 128 + ((sr & 255) >> 1)) * 256 + rank * 128 + (sr & 1) * 64 + s1 * 8 + ((4 * jj + t) ^ s1 ^ (ot & 1)));
          const uint32_t w[4] = {v.x, v.y, v.z, v.w};
#pragma unroll
          for (int j = 0; j < 4; j++) { acc[16 * jj + 4 * j + 2 * u] = fmaf(blo(w[j]), st.x, off); acc[16 * jj + 4 * j + 2 * u + 1] = fmaf(bhi(w[j]), st.x, off); }
        }
      }
#pragma unroll
      for (int j = 32; j < 64; j++) acc[j] = 0.f;
#pragma unroll 1
      for (int i = 0; i < 21; i++) {
        mbar_wait(bar + MB_W2 * 8, 0);
        mbar_wait(bar + (MB_FULL + 32) * 8, 0);
        if (i == 0) STAMP(10);
        asm volatile("wgmma.fence.sync.aligned;" ::: "memory");
        wgmma_n128_ss<1, 0, HI_SW128, HI_NOSW>(acc, da, db, 1);
        wgmma_n128_ss<1, 0, HI_SW128, HI_NOSW>(acc, da + 128, db + 256, 1);
        asm volatile("wgmma.commit_group.sync.aligned;" ::: "memory");
        da = i == 18 ? da0 : da + 512; db = db == db0 + 5 * 512 ? db0 : db + 512;
        asm volatile("wgmma.wait_group.sync.aligned 1;" ::: "memory");
        if ((tid & 127) == 0) { if (i > 0) mbar_arrive(bar + (MB_EMPTY + 31) * 8); if (i == 4) mbar_arrive_cluster(peer_sb + BAR_OFF + MB_PEER2 * 8); }
        bar += 8;
      }
      mbar_wait(bar + MB_W2 * 8, 0);
      mbar_wait(bar + (MB_FULL + 32) * 8, 0);
      asm volatile("wgmma.fence.sync.aligned;" ::: "memory");
      wgmma_n128_ss<1, 0, HI_SW128, HI_NOSW>(acc, da, db, 1);
      asm volatile("wgmma.commit_group.sync.aligned;" ::: "memory");
      asm volatile("wgmma.wait_group.sync.aligned 0;" ::: "memory");
#pragma unroll
      for (int i = 0; i < 64; i++) asm volatile("" : "+f"(acc[i]) :: "memory");
      STAMP(11);
      mbar_wait_cluster(mb + MB_PEER2 * 8, 0);
#pragma unroll
      for (int j = 0; j < 4; j++) {
        const int o = 32 + 16 * (j >> 1) + 2 * (j & 1);
        st_async4(peer_sb + 3 * 8192 + j * 4096 + tid * 16, pk(acc[o], acc[o + 1]), pk(acc[o + 4], acc[o + 5]), pk(acc[o + 8], acc[o + 9]), pk(acc[o + 12], acc[o + 13]),
                  peer_sb + BAR_OFF + MB_X2 * 8);
      }
      STAMP(23);
      mbar_wait_cluster(mb + MB_X2 * 8, 0);
      STAMP(24);
#pragma unroll
      for (int j = 0; j < 4; j++) {
        const int o = 16 * (j >> 1) + 2 * (j & 1);
        const uint4 v = lds128(sb + 3 * 8192 + j * 4096 + tid * 16);
        out[oo + 4 * (j >> 1) + 512 * (j & 1)] = make_uint4(pk(acc[o] + blo(v.x), acc[o + 1] + bhi(v.x)), pk(acc[o + 4] + blo(v.y), acc[o + 5] + bhi(v.y)),
                                                            pk(acc[o + 8] + blo(v.z), acc[o + 9] + bhi(v.z)), pk(acc[o + 12] + blo(v.w), acc[o + 13] + bhi(v.w)));
      }
      STAMP(12);
    }
  } else {
    const int pw = warp - 8;
    if (pw < 3 && elect()) {
#pragma unroll
      for (int i = 0; i < 57; i++) mbar_init(mb + (pw * 57 + i) * 8, pw == 2 ? 2 : 1);
      if (pw == 1) { mbar_expect(mb + MB_X1 * 8, 12288); mbar_expect(mb + MB_X2 * 8, 16384); }
      asm volatile("fence.mbarrier_init.release.cluster;" ::: "memory");
    }
    __syncwarp();
    STAMP(0);
    asm volatile("bar.sync 2, 128;" ::: "memory");
    asm volatile("barrier.cluster.arrive.relaxed.aligned;" ::: "memory");
    auto w1_issue = [&](int i) {
      if (elect()) { mbar_expect(mb + (MB_W1T + i) * 8, 5632); tma3d(sb + i * 5632, &tmW1, 88 * ot, 0, 128 * rank + 4 * i, mb + (MB_W1T + i) * 8); }
      __syncwarp();
    };
    if (!W1_LATE && pw < W1_WARPS) for (int i = 0; i < W1_DEPTH; i++) w1_issue(pw + W1_WARPS * i);
    {
      const int j1 = b >> 4, q = b & 15, slot = lane & 15, h = lane >> 4;
      const bool hi = q >= 8;
      const int k = 16 * (q & 7) + slot, col = hi ? 256 - k : (k == 0 ? 128 : k);
      const int j0 = j1 + 8 * h + 512 * pw, o0 = (hi ? 2048 - 31 * 16 - j0 : j0) * DF + col, o31 = hi && j0 == 0 ? o0 - 2048 * DF : o0;
      uint32_t vr[32], vi[32];
      if (FILT_LATE) { asm volatile("bar.sync 3, 160;" ::: "memory"); asm volatile("" : "+l"(wr), "+l"(wi)); }
#pragma unroll
      for (int n = 0; n < 32; n++) { vr[n] = __ldg(wr + (n == 31 ? o31 : o0) + n * 16 * DF); vi[n] = __ldg(wi + (n == 31 ? o31 : o0) + n * 16 * DF); }
      const uint32_t f0 = sb + FILT_OFF + pw * 4096 + (hi ? 31 * 128 : 0) + h * 8 + (slot & 1) * 4, sw = ((slot >> 1) ^ (hi ? 7 : 0)) << 4;
      const int st = hi ? -128 : 128;
#pragma unroll
      for (int n = 0; n < 32; n++)
        sts32(f0 + n * st + (sw ^ ((((n >> 3) & 3) * 2 + (n & 1)) << 4)), __byte_perm(vr[n], vi[n], 0x5410) ^ (hi ? 0x80000000u : 0u));
      asm volatile("bar.sync 2, 128;" ::: "memory");
      if (threadIdx.x == 352) mbar_arrive(mb + MB_FILT * 8);
    }
    __syncwarp();
    STAMP(1);
    {
      if (W1_LATE && pw < W1_WARPS) for (int i = 0; i < W1_DEPTH; i++) w1_issue(pw + W1_WARPS * i);
      const uint32_t rd = ((lane & 7) * 11 + (lane >> 3)) * 16, wr = lane * 16;
#pragma unroll 1
      for (int box = pw < W1_WARPS ? pw : 32; box < W1_END; box += W1_WARPS) {
        mbar_wait(mb + (MB_W1T + box) * 8, 0);
        if (box + W1_WARPS * W1_DEPTH < 32) w1_issue(box + W1_WARPS * W1_DEPTH);
        const uint32_t p = sb + box * 5632;
        uint4 v[4][3];
#pragma unroll
        for (int n = 0; n < 4; n++) { v[n][0] = lds128(p + n * 1408 + rd); v[n][1] = lds128(p + n * 1408 + rd + 64); if (lane < 24) v[n][2] = lds128(p + n * 1408 + rd + 128); }
        __syncwarp();
#pragma unroll
        for (int n = 0; n < 4; n++) { sts128(p + n * 1408 + wr, v[n][0]); sts128(p + n * 1408 + wr + 512, v[n][1]); if (lane < 24) sts128(p + n * 1408 + wr + 1024, v[n][2]); }
      }
      if (lane == 0) asm volatile("cp.async.bulk.prefetch.L2.global [%0], %1;" :: "l"(w2 + (size_t)(b * 4 + pw) * 11008), "r"(11008) : "memory");
      asm volatile("fence.proxy.async.shared::cta;" ::: "memory");
      asm volatile("bar.sync 2, 128;" ::: "memory");
      if (threadIdx.x == 352) mbar_arrive(mb + MB_W1 * 8);
    }
    STAMP(2);
    asm volatile("barrier.cluster.wait.aligned;" ::: "memory");
    if (pw == 3) {
#pragma unroll 1
      for (int n = 0; n < 22; n++) {
        if (n < W2_PRE) mbar_wait(mb + (MB_EMPTY + min(31, max(((n + 4) * 16 + 10) / 11 - 1, W2_START + n * W2_NUM / W2_DEN))) * 8, 0);
        else { mbar_wait(mb + MB_X1DONE * 8, 0); if (W2_PACE) mbar_wait(mb + (MB_FULL + 32 - W2_PRE + n) * 8, 0); }
        if (elect()) { mbar_expect(mb + (MB_W2 + n) * 8, 8192); tma3d(sb + (n < 19 ? n + 3 : n - 19) * 8192, &tmW2, 0, 688 * rank + 32 * n, 2 * ot, mb + (MB_W2 + n) * 8); }
      }
    } else {
      int i = pw;
      uint32_t dst = sb + RING_OFF + pw * 8192;
      const uint32_t dsum = 2 * dst + 3 * 8192;
      const char* src = (const char*)g_Hn + ((size_t)dt * 128 + 64 * rank) * 4096;
#pragma unroll 1
      for (int gm = 0; gm < 2; gm++) {
        if (pw == 0) {
          mbar_wait(mb + (gm ? MB_X1DONE : MB_P3DONE) * 8, 0);
          STAMP(3 + 2 * gm);
          if (lane == 0) cnt_wait<true>(scr, gm ? 4 + dt : 2 + rank, ot & (NREP - 1), ((lds32(sb + BASE_OFF) >> 1) + 64) >> gm);
        }
        asm volatile("bar.sync 2, 96;" ::: "memory");
        STAMP(4 + 2 * gm);
        asm volatile("fence.proxy.async.global;" ::: "memory");
#pragma unroll 1
        for (; i < (gm ? 54 : 32); i += 3) {
          if (i >= NST) mbar_wait(mb + (MB_EMPTY - NST + i) * 8, 0);
          if (elect()) {
            const int bytes = i < 53 ? 8192 : 4096;
            mbar_expect(mb + (MB_FULL + i) * 8, bytes); bulk_ld(dst, src + i * 8192, bytes, mb + (MB_FULL + i) * 8);
          }
          dst = dsum - dst;
        }
        src = (const char*)g_U + ((size_t)dt * 172 + 86 * rank) * 2048 - 32 * 8192;
      }
      STAMP(7);
    }
  }
}

typedef CUresult (*EncodeFn)(CUtensorMap*, CUtensorMapDataType, cuuint32_t, void*, const cuuint64_t*, const cuuint64_t*, const cuuint32_t*,
                             const cuuint32_t*, CUtensorMapInterleave, CUtensorMapSwizzle, CUtensorMapL2promotion, CUtensorMapFloatOOBfill);

extern "C" void kernel_launch(void* const* d_in, const int* in_sizes, int n_in, void* d_out, int out_size) {
  static EncodeFn enc = nullptr;
  static void* scr = nullptr;
  if (!enc) {
    void* fn = nullptr; cudaDriverEntryPointQueryResult st;
    cudaGetDriverEntryPoint("cuTensorMapEncodeTiled", &fn, cudaEnableDefault, &st);
    enc = (EncodeFn)fn;
    cudaGetSymbolAddress(&scr, g_scr);
    cudaFuncSetAttribute(fused_kernel, cudaFuncAttributeMaxDynamicSharedMemorySize, SMEM_BYTES);
  }
  CUtensorMap tm, tm1;
  {
    cuuint64_t dims[3] = {(cuuint64_t)F_, 8, 256}, strides[2] = {(cuuint64_t)256 * F_ * 2, F_ * 2};
    cuuint32_t box[3] = {88, 8, 4}, es[3] = {1, 1, 1};
    enc(&tm1, CU_TENSOR_MAP_DATA_TYPE_BFLOAT16, 3, d_in[4], dims, strides, box, es, CU_TENSOR_MAP_INTERLEAVE_NONE, CU_TENSOR_MAP_SWIZZLE_NONE,
        W1_PROMO, CU_TENSOR_MAP_FLOAT_OOB_FILL_NONE);
  }
  {
    cuuint64_t dims[3] = {64, (cuuint64_t)F_, S_ / 64}, strides[2] = {S_ * 2, 128};
    cuuint32_t box[3] = {64, 32, 2}, es[3] = {1, 1, 1};
    enc(&tm, CU_TENSOR_MAP_DATA_TYPE_BFLOAT16, 3, d_in[6], dims, strides, box, es, CU_TENSOR_MAP_INTERLEAVE_NONE, CU_TENSOR_MAP_SWIZZLE_128B,
        CU_TENSOR_MAP_L2_PROMOTION_L2_256B, CU_TENSOR_MAP_FLOAT_OOB_FILL_NONE);
  }
  fused_kernel<<<NCTA, 384, SMEM_BYTES, cudaStreamPerThread>>>((const uint2*)d_in[0], (Scratch*)scr, (const unsigned short*)d_in[1], (const unsigned short*)d_in[2],
                                          (const uint32_t*)d_in[5], (const unsigned short*)d_in[7], (uint4*)d_out, (const char*)d_in[6], tm1, tm);
}
```

```cpp
#include <cuda_runtime.h>
#include <cuda.h>
#include <cuda_bf16.h>
#include <stdint.h>
#define W1_LATE 1
#define W1_PROMO CU_TENSOR_MAP_L2_PROMOTION_NONE
#define W2_NUM 1
#define W2_DEN 1
#define PF_W1 0
#define W1_DEPTH 1
#define W1_WARPS 4
#define W2_PRE 12
#define W2_PACE 1
#define FILT_LATE 0
#define W1_END 32
#define TLB_WARM 0
template<int TA, int TB, uint32_t HA, uint32_t HB> __device__ __forceinline__ void wgmma_n88_ss(float (&d)[44], uint32_t da, uint32_t db, int sd) {
  asm volatile("{\n.reg .pred p;\n.reg .b64 da, db;\nsetp.ne.b32 p, %46, 0;\nmov.b64 da, {%44, %49};\nmov.b64 db, {%45, %50};\n"
    "wgmma.mma_async.sync.aligned.m64n88k16.f32.bf16.bf16 {%0, %1, %2, %3, %4, %5, %6, %7, %8, %9, %10, %11, %12, %13, %14, %15, %16, %17, %18, %19, %20, %21, %22, %23, %24, %25, %26, %27, %28, %29, %30, %31, %32, %33, %34, %35, %36, %37, %38, %39, %40, %41, %42, %43}, da, db, p, 1, 1, %47, %48;\n}\n"
    : "+f"(d[0]), "+f"(d[1]), "+f"(d[2]), "+f"(d[3]), "+f"(d[4]), "+f"(d[5]), "+f"(d[6]), "+f"(d[7]), "+f"(d[8]), "+f"(d[9]), "+f"(d[10]), "+f"(d[11]), "+f"(d[12]), "+f"(d[13]), "+f"(d[14]), "+f"(d[15]), "+f"(d[16]), "+f"(d[17]), "+f"(d[18]), "+f"(d[19]), "+f"(d[20]), "+f"(d[21]), "+f"(d[22]), "+f"(d[23]), "+f"(d[24]), "+f"(d[25]), "+f"(d[26]), "+f"(d[27]), "+f"(d[28]), "+f"(d[29]), "+f"(d[30]), "+f"(d[31]), "+f"(d[32]), "+f"(d[33]), "+f"(d[34]), "+f"(d[35]), "+f"(d[36]), "+f"(d[37]), "+f"(d[38]), "+f"(d[39]), "+f"(d[40]), "+f"(d[41]), "+f"(d[42]), "+f"(d[43]) : "r"(da), "r"(db), "r"(sd), "n"(TA), "n"(TB), "n"(HA), "n"(HB));
}
template<int TA, int TB, uint32_t HA, uint32_t HB> __device__ __forceinline__ void wgmma_n128_ss(float (&d)[64], uint32_t da, uint32_t db, int sd) {
  asm volatile("{\n.reg .pred p;\n.reg .b64 da, db;\nsetp.ne.b32 p, %66, 0;\nmov.b64 da, {%64, %69};\nmov.b64 db, {%65, %70};\n"
    "wgmma.mma_async.sync.aligned.m64n128k16.f32.bf16.bf16 {%0, %1, %2, %3, %4, %5, %6, %7, %8, %9, %10, %11, %12, %13, %14, %15, %16, %17, %18, %19, %20, %21, %22, %23, %24, %25, %26, %27, %28, %29, %30, %31, %32, %33, %34, %35, %36, %37, %38, %39, %40, %41, %42, %43, %44, %45, %46, %47, %48, %49, %50, %51, %52, %53, %54, %55, %56, %57, %58, %59, %60, %61, %62, %63}, da, db, p, 1, 1, %67, %68;\n}\n"
    : "+f"(d[0]), "+f"(d[1]), "+f"(d[2]), "+f"(d[3]), "+f"(d[4]), "+f"(d[5]), "+f"(d[6]), "+f"(d[7]), "+f"(d[8]), "+f"(d[9]), "+f"(d[10]), "+f"(d[11]), "+f"(d[12]), "+f"(d[13]), "+f"(d[14]), "+f"(d[15]), "+f"(d[16]), "+f"(d[17]), "+f"(d[18]), "+f"(d[19]), "+f"(d[20]), "+f"(d[21]), "+f"(d[22]), "+f"(d[23]), "+f"(d[24]), "+f"(d[25]), "+f"(d[26]), "+f"(d[27]), "+f"(d[28]), "+f"(d[29]), "+f"(d[30]), "+f"(d[31]), "+f"(d[32]), "+f"(d[33]), "+f"(d[34]), "+f"(d[35]), "+f"(d[36]), "+f"(d[37]), "+f"(d[38]), "+f"(d[39]), "+f"(d[40]), "+f"(d[41]), "+f"(d[42]), "+f"(d[43]), "+f"(d[44]), "+f"(d[45]), "+f"(d[46]), "+f"(d[47]), "+f"(d[48]), "+f"(d[49]), "+f"(d[50]), "+f"(d[51]), "+f"(d[52]), "+f"(d[53]), "+f"(d[54]), "+f"(d[55]), "+f"(d[56]), "+f"(d[57]), "+f"(d[58]), "+f"(d[59]), "+f"(d[60]), "+f"(d[61]), "+f"(d[62]), "+f"(d[63]) : "r"(da), "r"(db), "r"(sd), "n"(TA), "n"(TB), "n"(HA), "n"(HB));
}

constexpr int S_ = 2048, F_ = 1376, DF = 257;
constexpr int NCTA = 128;
constexpr int W_BYTES = 180224;
constexpr int RING_OFF = W_BYTES;
constexpr int NST = 6;
constexpr int BAR_OFF = RING_OFF + NST * 8192;
constexpr int SMEM_BYTES = BAR_OFF + 1536;
constexpr int FILT_OFF = RING_OFF;
constexpr int XCH_OFF = RING_OFF + 16384;
constexpr int ZROW = 328;
constexpr int MB_FULL = 0, MB_W2 = 54, MB_W1T = 76, MB_X1 = 108, MB_X2 = 109, MB_X1DONE = 110, MB_P3DONE = 111, MB_FILT = 112, MB_W1 = 113,
              MB_EMPTY = 114, MB_PEER1 = 168, MB_PEER2 = 169, MB_N = 171;
constexpr int BASE_OFF = BAR_OFF + MB_N * 8;
#define W2_START 24

struct Scratch {
  uint4 T1[NCTA * 1024], T2[NCTA * 1024], Hn[4 * 128 * 256], U[4 * 172 * 128];
  float2 st[S_];
  unsigned cnt[8 * 4 * 64];
};
__device__ __align__(1024) Scratch g_scr;
#define g_T1 (scr->T1)
#define g_T2 (scr->T2)
#define g_Hn (scr->Hn)
#define g_U (scr->U)
#define g_st (scr->st)
#define g_cnt (scr->cnt)
#define STAMP(i)

__device__ __forceinline__ void mbar_init(uint32_t b, int c) { asm volatile("mbarrier.init.shared::cta.b64 [%0], %1;" :: "r"(b), "r"(c) : "memory"); }
__device__ __forceinline__ void mbar_expect(uint32_t b, int bytes) { asm volatile("mbarrier.arrive.expect_tx.shared::cta.b64 _, [%0], %1;" :: "r"(b), "r"(bytes) : "memory"); }
__device__ __forceinline__ void mbar_arrive(uint32_t b) { asm volatile("mbarrier.arrive.shared::cta.b64 _, [%0];" :: "r"(b) : "memory"); }
__device__ __forceinline__ void mbar_arrive_cluster(uint32_t remote) { asm volatile("mbarrier.arrive.relaxed.cluster.shared::cluster.b64 _, [%0];" :: "r"(remote) : "memory"); }
__device__ __forceinline__ uint32_t mapa(uint32_t a, uint32_t cta) { uint32_t r; asm("mapa.shared::cluster.u32 %0, %1, %2;" : "=r"(r) : "r"(a), "r"(cta)); return r; }
__device__ __forceinline__ void mbar_wait(uint32_t b, int ph) {
  asm volatile("{\n.reg .pred p;\n.reg .u32 n;\nmov.u32 n, 0;\nL_W:\n"
               "mbarrier.try_wait.parity.shared::cta.b64 p, [%0], %1;\n@p bra L_D;\n"
               "add.u32 n, n, 1;\nsetp.lt.u32 p, n, 4000000;\n@p bra L_W;\ntrap;\nL_D:\n}" :: "r"(b), "r"(ph) : "memory");
}
__device__ __forceinline__ void mbar_wait_cluster(uint32_t b, int ph) {
  asm volatile("{\n.reg .pred p;\n.reg .u32 n;\nmov.u32 n, 0;\nL_W:\n"
               "mbarrier.try_wait.parity.acquire.cluster.shared::cta.b64 p, [%0], %1;\n@p bra L_D;\n"
               "add.u32 n, n, 1;\nsetp.lt.u32 p, n, 4000000;\n@p bra L_W;\ntrap;\nL_D:\n}" :: "r"(b), "r"(ph) : "memory");
}
__device__ __forceinline__ void bulk_ld(uint32_t dst, const void* src, int bytes, uint32_t bar) {
  asm volatile("cp.async.bulk.shared::cluster.global.mbarrier::complete_tx::bytes [%0], [%1], %2, [%3];" :: "r"(dst), "l"(src), "r"(bytes), "r"(bar) : "memory");
}
__device__ __forceinline__ void tma3d(uint32_t dst, const CUtensorMap* tm, int c0, int c1, int c2, uint32_t bar) {
  asm volatile("cp.async.bulk.tensor.3d.shared::cluster.global.mbarrier::complete_tx::bytes [%0], [%1, {%3, %4, %5}], [%2];"
               :: "r"(dst), "l"(tm), "r"(bar), "r"(c0), "r"(c1), "r"(c2) : "memory");
}
__device__ __forceinline__ bool elect() { uint32_t p; asm volatile("{.reg .pred p; elect.sync _|p, 0xffffffff; selp.b32 %0, 1, 0, p;}" : "=r"(p)); return p; }
__device__ __forceinline__ uint32_t desc_lo(uint32_t addr, uint32_t lbo) { return ((addr & 0x3FFFF) >> 4) | ((lbo >> 4) << 16); }
constexpr uint32_t HI_SW128 = (1024 >> 4) | (1u << 30), HI_NOSW = 128 >> 4;
__device__ __forceinline__ uint32_t pk(float lo, float hi) { uint32_t r; asm("cvt.rn.bf16x2.f32 %0, %1, %2;" : "=r"(r) : "f"(hi), "f"(lo)); return r; }
__device__ __forceinline__ float blo(uint32_t w) { return __uint_as_float(w << 16); }
__device__ __forceinline__ float bhi(uint32_t w) { return __uint_as_float(w & 0xffff0000u); }
__device__ __forceinline__ void mmac(float (&d)[4], const float (&c)[4], const uint32_t (&a)[4], uint32_t b0, uint32_t b1) {
  asm("mma.sync.aligned.m16n8k16.row.col.f32.bf16.bf16.f32 {%0,%1,%2,%3}, {%4,%5,%6,%7}, {%8,%9}, {%10,%11,%12,%13};"
      : "=f"(d[0]), "=f"(d[1]), "=f"(d[2]), "=f"(d[3]) : "r"(a[0]), "r"(a[1]), "r"(a[2]), "r"(a[3]), "r"(b0), "r"(b1), "f"(c[0]), "f"(c[1]), "f"(c[2]), "f"(c[3]));
}
__device__ __forceinline__ void mma0(float (&d)[4], const uint32_t (&a)[4], uint32_t b0, uint32_t b1) { const float z[4] = {0.f, 0.f, 0.f, 0.f}; mmac(d, z, a, b0, b1); }
__device__ __forceinline__ uint32_t pin(uint32_t v) { asm volatile("shfl.sync.bfly.b32 %0, %0, 0, 31, 0xffffffff;" : "+r"(v)); return v; }
__device__ __forceinline__ float pinf(float v) { return __uint_as_float(pin(__float_as_uint(v))); }
__device__ __forceinline__ void wbar() { asm volatile("bar.sync 1, 256;" ::: "memory"); }
__device__ __forceinline__ void sts32(uint32_t a, uint32_t v) { asm volatile("st.shared.b32 [%0], %1;" :: "r"(a), "r"(v) : "memory"); }
__device__ __forceinline__ void sts64(uint32_t a, uint32_t x, uint32_t y) { asm volatile("st.shared.v2.b32 [%0], {%1,%2};" :: "r"(a), "r"(x), "r"(y) : "memory"); }
__device__ __forceinline__ void sts128(uint32_t a, uint4 v) { asm volatile("st.shared.v4.b32 [%0], {%1,%2,%3,%4};" :: "r"(a), "r"(v.x), "r"(v.y), "r"(v.z), "r"(v.w) : "memory"); }
__device__ __forceinline__ uint32_t lds32(uint32_t a) { uint32_t v; asm volatile("ld.shared.b32 %0, [%1];" : "=r"(v) : "r"(a) : "memory"); return v; }
__device__ __forceinline__ uint2 lds64(uint32_t a) { uint2 v; asm volatile("ld.shared.v2.b32 {%0,%1}, [%2];" : "=r"(v.x), "=r"(v.y) : "r"(a) : "memory"); return v; }
__device__ __forceinline__ uint4 lds128(uint32_t a) { uint4 v; asm volatile("ld.shared.v4.b32 {%0,%1,%2,%3}, [%4];" : "=r"(v.x), "=r"(v.y), "=r"(v.z), "=r"(v.w) : "r"(a) : "memory"); return v; }
__device__ __forceinline__ uint4 ldcg128(const void* p) { uint4 v; asm volatile("ld.global.cg.v4.b32 {%0,%1,%2,%3}, [%4];" : "=r"(v.x), "=r"(v.y), "=r"(v.z), "=r"(v.w) : "l"(p) : "memory"); return v; }
__device__ __forceinline__ void st_async4(uint32_t a, uint32_t x, uint32_t y, uint32_t z, uint32_t w, uint32_t bar) {
  asm volatile("st.async.weak.shared::cluster.mbarrier::complete_tx::bytes.v4.b32 [%0], {%1,%2,%3,%4}, [%5];" :: "r"(a), "r"(x), "r"(y), "r"(z), "r"(w), "r"(bar) : "memory");
}
constexpr int NREP = 4;
__device__ __forceinline__ void cnt_arrive(Scratch* scr, int i, int lane) {
  if (lane < NREP) asm volatile("red.relaxed.gpu.global.add.u32 [%0], 1;" :: "l"(&g_cnt[(i * NREP + lane) * 64]) : "memory");
}
template <bool ACQ> __device__ __forceinline__ void cnt_wait(Scratch* scr, int i, int rep, unsigned target) {
  unsigned v; int n = 0;
  do {
    if (ACQ) asm volatile("ld.acquire.gpu.global.u32 %0, [%1];" : "=r"(v) : "l"(&g_cnt[(i * NREP + rep) * 64]) : "memory");
    else asm volatile("ld.relaxed.gpu.global.u32 %0, [%1];" : "=r"(v) : "l"(&g_cnt[(i * NREP + rep) * 64]) : "memory");
    if (++n > 2000000) __trap(); } while ((int)(v - target) < 0);
}
__device__ __forceinline__ void fence_gpu() { asm volatile("fence.acq_rel.gpu;" ::: "memory"); }
__device__ __forceinline__ void tag_check(uint4& v, const uint4* p, uint32_t tag) {
  int n = 0;
  while ((v.x ^ tag) & 1) {
    asm volatile("ld.relaxed.gpu.global.v4.b32 {%0,%1,%2,%3}, [%4];" : "=r"(v.x), "=r"(v.y), "=r"(v.z), "=r"(v.w) : "l"(p) : "memory");
    if (++n > 2000000) __trap();
  }
}
template <int N> __device__ __forceinline__ void cs(int n, float& c, float& s) {
  n = ((n + N / 2) & (N - 1)) - N / 2;
  float a = (float)n * (6.283185307179586f / N);
  c = __cosf(a); s = __sinf(a);
}
constexpr float ALPHA = 1.13288f;
struct FftC { uint32_t a[4][4], b[8][2]; float tc[2][4], ts[2][4]; };
constexpr uint32_t NEG = 0x80008000u;

__device__ __forceinline__ void fft_s1(const FftC& K, const uint32_t (&in)[4][2], float (&cr)[2][4], float (&ci)[2][4]) {
#pragma unroll
  for (int h = 0; h < 2; h++) { mma0(cr[h], K.a[0], in[0][h], in[1][h]); mma0(ci[h], K.a[1], in[0][h], in[1][h]); }
#pragma unroll
  for (int h = 0; h < 2; h++) { mmac(cr[h], cr[h], K.a[2], in[2][h], in[3][h]); mmac(ci[h], ci[h], K.a[3], in[2][h], in[3][h]); }
}
__device__ __forceinline__ void fft_s2(const FftC& K, const float (&cr)[2][4], const float (&ci)[2][4], float (&o)[4][4]) {
  uint32_t a[2][4];
#pragma unroll
  for (int h = 0; h < 2; h++)
#pragma unroll
    for (int i = 0; i < 4; i++) {
      float xr = cr[i & 1][2 * h + (i >> 1)], xi = ci[i & 1][2 * h + (i >> 1)];
      a[i >> 1][2 * (i & 1) + h] = pk(xr * K.tc[h][i] + xi * K.ts[h][i], xi * K.tc[h][i] - xr * K.ts[h][i]);
    }
#pragma unroll
  for (int j = 0; j < 4; j++) mma0(o[j], a[0], K.b[j][0], K.b[j][1]);
#pragma unroll
  for (int j = 0; j < 4; j++) mmac(o[j], o[j], a[1], K.b[4 + j][0], K.b[4 + j][1]);
}
__device__ __forceinline__ int zphys(int k) { return k + 8 * (k >> 5); }
__device__ __forceinline__ float gelu(float u) {
  float z = u * (0.7978845608028654f + 0.035677408136300125f * u * u), th;
  asm("tanh.approx.f32 %0, %1;" : "=f"(th) : "f"(z));
  float hu = 0.5f * u;
  return fmaf(hu, th, hu);
}

extern "C" __global__ void __cluster_dims__(2, 1, 1) __launch_bounds__(384, 1)
fused_kernel(const uint2* __restrict__ x, Scratch* scr, const unsigned short* __restrict__ wr, const unsigned short* __restrict__ wi,
             const uint32_t* __restrict__ b1, const unsigned short* __restrict__ b2, uint4* __restrict__ out, const char* __restrict__ w2,
             const __grid_constant__ CUtensorMap tmW1, const __grid_constant__ CUtensorMap tmW2) {
  extern __shared__ __align__(1024) char smem[];
  const uint32_t sb = (uint32_t)__cvta_generic_to_shared(smem);
  const uint32_t mb = sb + BAR_OFF;
  const int b = blockIdx.x, rank = b & 1, pr = b >> 1, dt = pr & 3, ot = pr >> 2;
  const int warp = __shfl_sync(0xffffffffu, threadIdx.x >> 5, 0), lane = threadIdx.x & 31;
  const int g = lane >> 2, t = lane & 3;

  if (warp >= 8) {
    const int pw = warp - 8;
    if (pw < 3 && elect()) {
#pragma unroll
      for (int i = 0; i < 57; i++) mbar_init(mb + (pw * 57 + i) * 8, pw == 2 ? 2 : 1);
      if (pw == 1) { mbar_expect(mb + MB_X1 * 8, 12288); mbar_expect(mb + MB_X2 * 8, 16384); }
      asm volatile("fence.mbarrier_init.release.cluster;" ::: "memory");
    }
    __syncwarp();
    STAMP(0);
    asm volatile("bar.sync 2, 128;" ::: "memory");
    asm volatile("barrier.cluster.arrive.relaxed.aligned;" ::: "memory");
    auto w1_issue = [&](int i) {
      if (elect()) { mbar_expect(mb + (MB_W1T + i) * 8, 5632); tma3d(sb + i * 5632, &tmW1, 88 * ot, 0, 128 * rank + 4 * i, mb + (MB_W1T + i) * 8); }
      __syncwarp();
    };
    if (!W1_LATE && pw < W1_WARPS) for (int i = 0; i < W1_DEPTH; i++) w1_issue(pw + W1_WARPS * i);
    {
      const int j1 = b >> 4, q = b & 15, slot = lane & 15, h = lane >> 4;
      const bool hi = q >= 8;
      const int k = 16 * (q & 7) + slot, col = hi ? 256 - k : (k == 0 ? 128 : k);
      const int j0 = j1 + 8 * h + 512 * pw, o0 = (hi ? 2048 - 31 * 16 - j0 : j0) * DF + col, o31 = hi && j0 == 0 ? o0 - 2048 * DF : o0;
      uint32_t vr[32], vi[32];
      if (FILT_LATE) { asm volatile("bar.sync 3, 160;" ::: "memory"); asm volatile("" : "+l"(wr), "+l"(wi)); }
#pragma unroll
      for (int n = 0; n < 32; n++) { vr[n] = __ldg(wr + (n == 31 ? o31 : o0) + n * 16 * DF); vi[n] = __ldg(wi + (n == 31 ? o31 : o0) + n * 16 * DF); }
      const uint32_t f0 = sb + FILT_OFF + pw * 4096 + (hi ? 31 * 128 : 0) + h * 8 + (slot & 1) * 4, sw = ((slot >> 1) ^ (hi ? 7 : 0)) << 4;
      const int st = hi ? -128 : 128;
#pragma unroll
      for (int n = 0; n < 32; n++)
        sts32(f0 + n * st + (sw ^ ((((n >> 3) & 3) * 2 + (n & 1)) << 4)), __byte_perm(vr[n], vi[n], 0x5410) ^ (hi ? 0x80000000u : 0u));
      asm volatile("bar.sync 2, 128;" ::: "memory");
      if (threadIdx.x == 352) mbar_arrive(mb + MB_FILT * 8);
    }
    __syncwarp();
    STAMP(1);
    {
      if (W1_LATE && pw < W1_WARPS) for (int i = 0; i < W1_DEPTH; i++) w1_issue(pw + W1_WARPS * i);
      const uint32_t rd = ((lane & 7) * 11 + (lane >> 3)) * 16, wr = lane * 16;
#pragma unroll 1
      for (int box = pw < W1_WARPS ? pw : 32; box < W1_END; box += W1_WARPS) {
        mbar_wait(mb + (MB_W1T + box) * 8, 0);
        if (box + W1_WARPS * W1_DEPTH < 32) w1_issue(box + W1_WARPS * W1_DEPTH);
        const uint32_t p = sb + box * 5632;
        uint4 v[4][3];
#pragma unroll
        for (int n = 0; n < 4; n++) { v[n][0] = lds128(p + n * 1408 + rd); v[n][1] = lds128(p + n * 1408 + rd + 64); if (lane < 24) v[n][2] = lds128(p + n * 1408 + rd + 128); }
        __syncwarp();
#pragma unroll
        for (int n = 0; n < 4; n++) { sts128(p + n * 1408 + wr, v[n][0]); sts128(p + n * 1408 + wr + 512, v[n][1]); if (lane < 24) sts128(p + n * 1408 + wr + 1024, v[n][2]); }
      }
      if (lane == 0) asm volatile("cp.async.bulk.prefetch.L2.global [%0], %1;" :: "l"(w2 + (size_t)(b * 4 + pw) * 11008), "r"(11008) : "memory");
      asm volatile("fence.proxy.async.shared::cta;" ::: "memory");
      asm volatile("bar.sync 2, 128;" ::: "memory");
      if (threadIdx.x == 352) mbar_arrive(mb + MB_W1 * 8);
    }
    STAMP(2);
    asm volatile("barrier.cluster.wait.aligned;" ::: "memory");
    if (pw == 3) {
#pragma unroll 1
      for (int n = 0; n < 22; n++) {
        if (n < W2_PRE) mbar_wait(mb + (MB_EMPTY + min(31, max(((n + 4) * 16 + 10) / 11 - 1, W2_START + n * W2_NUM / W2_DEN))) * 8, 0);
        else { mbar_wait(mb + MB_X1DONE * 8, 0); if (W2_PACE) mbar_wait(mb + (MB_FULL + 32 - W2_PRE + n) * 8, 0); }
        if (elect()) { mbar_expect(mb + (MB_W2 + n) * 8, 8192); tma3d(sb + (n < 19 ? n + 3 : n - 19) * 8192, &tmW2, 0, 688 * rank + 32 * n, 2 * ot, mb + (MB_W2 + n) * 8); }
      }
    } else {
      int i = pw;
      uint32_t dst = sb + RING_OFF + pw * 8192;
      const uint32_t dsum = 2 * dst + 3 * 8192;
      const char* src = (const char*)g_Hn + ((size_t)dt * 128 + 64 * rank) * 4096;
#pragma unroll 1
      for (int gm = 0; gm < 2; gm++) {
        if (pw == 0) {
          mbar_wait(mb + (gm ? MB_X1DONE : MB_P3DONE) * 8, 0);
          STAMP(3 + 2 * gm);
          if (lane == 0) cnt_wait<true>(scr, gm ? 4 + dt : 2 + rank, ot & (NREP - 1), ((lds32(sb + BASE_OFF) >> 1) + 64) >> gm);
        }
        asm volatile("bar.sync 2, 96;" ::: "memory");
        STAMP(4 + 2 * gm);
        asm volatile("fence.proxy.async.global;" ::: "memory");
#pragma unroll 1
        for (; i < (gm ? 54 : 32); i += 3) {
          if (i >= NST) mbar_wait(mb + (MB_EMPTY - NST + i) * 8, 0);
          if (elect()) {
            const int bytes = i < 53 ? 8192 : 4096;
            mbar_expect(mb + (MB_FULL + i) * 8, bytes); bulk_ld(dst, src + i * 8192, bytes, mb + (MB_FULL + i) * 8);
          }
          dst = dsum - dst;
        }
        src = (const char*)g_U + ((size_t)dt * 172 + 86 * rank) * 2048 - 32 * 8192;
      }
      STAMP(7);
    }
  } else {
    const int tid = threadIdx.x;
    uint32_t xw[2][4][2];
    const uint32_t zb = sb + XCH_OFF, zw = zb + warp * ZROW * 4;
    const int rep = ot & (NREP - 1);
#pragma unroll
    for (int j = 0; j < 4; j++)
      asm volatile("cp.async.cg.shared.global [%0], [%1], 16;" :: "r"(zw + (j >> 1) * 8 * ZROW * 4 + (j & 1) * 512 + lane * 16),
                   "l"(x + (size_t)(256 * warp + 2 * b) * 128 + j * 64 + lane * 2) : "memory");
    if (lane == 0) asm volatile("cp.async.cg.shared.global [%0], [%1], 16;" :: "r"(zw + 1280), "l"(&g_cnt[(1 * NREP + rep) * 64]) : "memory");
    STAMP(0);
    asm volatile("barrier.cluster.arrive.relaxed.aligned;" ::: "memory");
    STAMP(30);
    FftC K;
    {
      float c, s;
#pragma unroll
      for (int h = 0; h < 2; h++)
#pragma unroll
        for (int j = 0; j < 2; j++) {
          cs<16>((2 * g + h) * (t + 4 * j), c, s);
          const uint32_t re = pk(ALPHA * c, ALPHA * s), im = pk(-ALPHA * s, ALPHA * c);
          K.a[0][2 * j + h] = re; K.a[1][2 * j + h] = im; K.a[2][2 * j + h] = pin(h ? re ^ NEG : re); K.a[3][2 * j + h] = pin(h ? im ^ NEG : im);
        }
      STAMP(27);
#pragma unroll
      for (int i = 0; i < 4; i++) {
        cs<16>((4 * t + i) * (g >> 1) + 4 * (g & 1), c, s);
        const uint32_t P = pk(ALPHA * c, ALPHA * s), Q = pk(-ALPHA * s, ALPHA * c);
#pragma unroll
        for (int jj = 0; jj < 4; jj++) { const uint32_t v = ((i * jj) & 1 ? Q : P) ^ ((i * jj) & 2 ? NEG : 0u); K.b[4 * (i >> 1) + jj][i & 1] = jj ? pin(v) : v; }
      }
      STAMP(28);
#pragma unroll
      for (int h = 0; h < 2; h++)
#pragma unroll
        for (int i = 0; i < 4; i++) {
          cs<256>((2 * g + h) * (4 * t + i), c, s);
          K.tc[h][i] = pinf(c * (1.f / (ALPHA * ALPHA))); K.ts[h][i] = pinf(s * (1.f / (ALPHA * ALPHA)));
        }
    }
    STAMP(29);
    const int key = ((b >> 3) & 3) * 2 + (b & 1);
    float mean[2];
    uint32_t tag, base;
    {
      uint32_t a8[2][4], a8c[2][4], a8n[2][4]; float vc[4], vs[4];
#pragma unroll
      for (int a = 0; a < 2; a++)
#pragma unroll
        for (int u = 0; u < 4; u++) {
          float c, s; cs<2048>(g * (256 * (t + 4 * (u >> 1)) + 2 * b + a), c, s);
          a8[a][u] = u & 1 ? pk(-s, c) : pk(c, s);
          a8c[a][u] = pin(a8[a][u] ^ 0x80000000u); a8n[a][u] = pin(a8[a][u] ^ 0x00008000u);
        }
#pragma unroll
      for (int i = 0; i < 4; i++) { cs<512>(16 * warp + 8 * (i >> 1) + 2 * t + (i & 1) + 128, vc[i], vs[i]); vc[i] = pinf(vc[i]); vs[i] = pinf(vs[i]); }
      STAMP(13);
      asm volatile("cp.async.wait_all;" ::: "memory");
      __syncwarp();
#pragma unroll
      for (int a = 0; a < 2; a++)
#pragma unroll
        for (int j = 0; j < 4; j++) { const uint2 v = lds64(zw + a * 8 * ZROW * 4 + j * 256 + (8 * t + g) * 8); xw[a][j][0] = v.x; xw[a][j][1] = v.y; }
      base = lds32(zw + 1280);
      __syncwarp();
      tag = (~base >> 7) & 1;
#pragma unroll
      for (int a = 0; a < 2; a++) {
        float cr[2][4], ci[2][4], o[4][4];
        if (a == 0) { if (xw[0][0][0] == 0x12345678u && xw[1][3][1] == 0x12345679u) STAMP(31); STAMP(14); }
        fft_s1(K, xw[a], cr, ci);
        if (FILT_LATE && a == 0 && warp == 0) asm volatile("bar.arrive 3, 160;" :: "f"(cr[0][0]) : "memory");
        float sm = ((cr[0][0] + cr[0][1]) + (cr[1][0] + cr[1][1])) + ((ci[0][0] + ci[0][1]) + (ci[1][0] + ci[1][1]));
        sm += __shfl_xor_sync(0xffffffffu, sm, 1); sm += __shfl_xor_sync(0xffffffffu, sm, 2);
        sm = g == 0 ? sm * (1.f / 32.f) : 0.f;
#pragma unroll
        for (int h = 0; h < 2; h++) { cr[h][0] -= sm; cr[h][1] -= sm; ci[h][0] -= sm; ci[h][1] -= sm; }
        mean[a] = __shfl_sync(0xffffffffu, sm, 0) * (1.f / (16.f * 1.1328125f));
        float q = 0.f, q2 = 0.f;
#pragma unroll
        for (int i = 0; i < 4; i++) { q = fmaf(cr[0][i], cr[0][i], q); q2 = fmaf(cr[1][i], cr[1][i], q2); q = fmaf(ci[0][i], ci[0][i], q); q2 = fmaf(ci[1][i], ci[1][i], q2); }
        q += q2;
#pragma unroll
        for (int m = 1; m < 32; m <<= 1) q += __shfl_xor_sync(0xffffffffu, q, m);
        float r = rsqrtf(q * (1.f / (512.f * 16.f * ALPHA * ALPHA)) + 1e-5f) * 4.76837158203125e-7f;
        fft_s2(K, cr, ci, o);
#pragma unroll
        for (int j = 0; j < 4; j++)
          sts64(zb + ((a * 8 + warp) * ZROW + zphys(16 * t + 64 * j) + 2 * g) * 4, pk(o[j][0] * r, o[j][1] * r), pk(o[j][2] * r, o[j][3] * r));
      }
      STAMP(15);
      wbar();
      uint4* tp = g_T1 + (size_t)(g * 16 + warp) * 1024 + b * 8;
#pragma unroll
      for (int nt = 0; nt < 2; nt++) {
        const int k = 16 * warp + 8 * nt + g, km = k == 0 ? 128 : 256 - k;
        uint32_t lo[4], hi[4];
#pragma unroll
        for (int a = 0; a < 2; a++) {
          const uint32_t rb = zb + (a * 8 + t) * ZROW * 4;
          float A[4], S[4], D[4];
          const uint32_t m0 = lds32(rb + zphys(km) * 4), m1 = lds32(rb + (4 * ZROW + zphys(km)) * 4);
          mma0(A, a8[a], lds32(rb + zphys(k) * 4), lds32(rb + (4 * ZROW + zphys(k)) * 4));
          mmac(S, A, a8c[a], m0, m1);
          mmac(D, A, a8n[a], m0, m1);
#pragma unroll
          for (int e = 0; e < 2; e++) {
            const float c = vc[2 * nt + e], s = vs[2 * nt + e];
            float lr = fmaf(D[2 + e], s, fmaf(D[e], c, S[e])), li = fmaf(-D[e], s, fmaf(D[2 + e], c, S[2 + e]));
            float hr = fmaf(2.f, S[e], -lr), hii = fmaf(2.f, S[2 + e], -li);
            if (nt == 0 && e == 0) {
              const bool sp = warp == 0 && t == 0;
              lr = sp ? S[0] - D[0] : lr; li = sp ? S[2] - D[2] : li;
              hr = sp ? 2.f * (A[0] - A[2]) : hr; hii = sp ? 2.f * (A[0] + A[2]) : hii;
            }
            lo[2 * a + e] = pk(lr, li); hi[2 * a + e] = pk(hr, hii);
          }
        }
        const int w = (t + 4 * nt) ^ key;
        tp[w] = make_uint4((lo[0] & ~1u) | tag, lo[1], lo[2], lo[3]);
        tp[8 * 1024 + w] = make_uint4((hi[0] & ~1u) | tag, hi[1], hi[2], hi[3]);
      }
      wbar();
      STAMP(1);
      if (warp == 0) cnt_arrive(scr, 0, lane);
    }
    {
      const uint32_t off = (8 * t + g) * 128 + ((warp ^ (2 * t + (g & 1))) << 4);
      asm volatile("barrier.cluster.wait.aligned;" ::: "memory");
      mbar_wait(mb + MB_FILT * 8, 0);
      if (tid == 0) cnt_wait<false>(scr, 0, rep, base + NCTA);
      wbar();
#pragma unroll
      for (int j = 0; j < 4; j++)
        asm volatile("cp.async.cg.shared.global [%0], [%1], 16;" :: "r"(zb + j * 4096 + tid * 16), "l"(g_T1 + (size_t)b * 1024 + j * 256 + tid) : "memory");
      STAMP(2);
      uint32_t in[2][4][2], fw[2][4][2];
#pragma unroll
      for (int j = 0; j < 4; j++) {
        uint4 v = lds128(sb + FILT_OFF + off + j * 4096);
        fw[0][j][0] = v.x; fw[1][j][0] = v.y; fw[0][j][1] = v.z; fw[1][j][1] = v.w;
      }
      asm volatile("cp.async.wait_all;" ::: "memory");
      wbar();
      STAMP(3);
      uint4 iv[4];
#pragma unroll
      for (int j = 0; j < 4; j++) iv[j] = lds128(zb + off + j * 4096);
      if (((iv[0].x ^ tag) | (iv[1].x ^ tag) | (iv[2].x ^ tag) | (iv[3].x ^ tag)) & 1) {
#pragma unroll
        for (int j = 0; j < 4; j++) tag_check(iv[j], g_T1 + (size_t)b * 1024 + j * 256 + (off >> 4), tag);
      }
      __syncwarp();
#pragma unroll
      for (int j = 0; j < 4; j++) { in[0][j][0] = iv[j].x; in[1][j][0] = iv[j].y; in[0][j][1] = iv[j].z; in[1][j][1] = iv[j].w; }
#pragma unroll
      for (int sg = 0; sg < 2; sg++) {
        float cr[2][4], ci[2][4], o[4][4];
        fft_s1(K, in[sg], cr, ci);
        fft_s2(K, cr, ci, o);
#pragma unroll
        for (int j = 0; j < 4; j++)
#pragma unroll
          for (int h = 0; h < 2; h++) {
            float fr = blo(fw[sg][j][h]), fi = bhi(fw[sg][j][h]), xr = o[j][2 * h], xi = o[j][2 * h + 1];
            in[sg][j][h] = pk(xr * fi + xi * fr, xr * fr - xi * fi);
          }
        fft_s1(K, in[sg], cr, ci);
        fft_s2(K, cr, ci, o);
#pragma unroll
        for (int j = 0; j < 4; j++) { in[sg][j][0] = pk(o[j][0], o[j][1]); in[sg][j][1] = pk(o[j][2], o[j][3]); }
      }
#pragma unroll
      for (int j = 0; j < 4; j++) sts128(zb + off + j * 4096, make_uint4((in[0][j][0] & ~1u) | tag, in[1][j][0], in[0][j][1], in[1][j][1]));
      STAMP(16);
      wbar();
#pragma unroll
      for (int j = 0; j < 4; j++) g_T2[(size_t)b * 1024 + j * 256 + tid] = lds128(zb + j * 4096 + tid * 16);
      wbar();
      STAMP(4);
      if (warp == 0) cnt_arrive(scr, 1, lane);
    }
    {
      uint32_t a8[2][4], a8n[2][4]; float vc[4], vs[4];
#pragma unroll
      for (int a = 0; a < 2; a++)
#pragma unroll
        for (int u = 0; u < 4; u++) {
          float c, s; cs<2048>((t + 4 * (u >> 1)) * (256 * g + 2 * b + a), c, s);
          a8[a][u] = u & 1 ? pk(-s, c) : pk(c, s);
          a8n[a][u] = pin(a8[a][u] ^ NEG);
        }
#pragma unroll
      for (int i = 0; i < 4; i++) { cs<512>(16 * warp + 4 * t + i + 128, vc[i], vs[i]); vc[i] = pinf(vc[i]); vs[i] = pinf(vs[i]); }
      if (tid == 0) cnt_wait<false>(scr, 1, rep, base + NCTA);
      wbar();
      STAMP(5);
      const uint4* tp = g_T2 + (size_t)(t * 16 + warp) * 1024 + b * 8 + (g ^ key);
      uint4 L0 = ldcg128(tp), L1 = ldcg128(tp + 64 * 1024), H0 = ldcg128(tp + 8 * 1024), H1 = ldcg128(tp + 72 * 1024);
      if (((L0.x ^ tag) | (L1.x ^ tag) | (H0.x ^ tag) | (H1.x ^ tag)) & 1) {
        tag_check(L0, tp, tag); tag_check(L1, tp + 64 * 1024, tag); tag_check(H0, tp + 8 * 1024, tag); tag_check(H1, tp + 72 * 1024, tag);
      }
      __syncwarp();
      STAMP(17);
      const uint32_t l0[4] = {L0.x, L0.y, L0.z, L0.w}, l1[4] = {L1.x, L1.y, L1.z, L1.w}, h0[4] = {H0.x, H0.y, H0.z, H0.w}, h1[4] = {H1.x, H1.y, H1.z, H1.w};
#pragma unroll
      for (int a = 0; a < 2; a++) {
        uint32_t zf[4], zm[4];
#pragma unroll
        for (int sg = 0; sg < 2; sg++) {
          float A[4], S[4], D[4];
          mma0(A, a8[a], l0[2 * a + sg], l1[2 * a + sg]);
          mmac(S, A, a8[a], h0[2 * a + sg], h1[2 * a + sg]);
          mmac(D, A, a8n[a], h0[2 * a + sg], h1[2 * a + sg]);
#pragma unroll
          for (int e = 0; e < 2; e++) {
            const int i = 2 * e + sg;
            float fr = fmaf(-D[e], vs[i], fmaf(D[2 + e], vc[i], S[2 + e])), fi = fmaf(D[2 + e], vs[i], fmaf(D[e], vc[i], S[e]));
            float mr = fmaf(2.f, S[2 + e], -fr), mi = fmaf(-2.f, S[e], fi);
            if (i == 0) {
              const bool sp = warp == 0 && t == 0;
              fr = sp ? S[2] - A[2] : fr; fi = sp ? A[2] - S[2] : fi;
              mr = sp ? 2.f * A[2] : mr; mi = sp ? -2.f * A[0] : mi;
            }
            zf[i] = pk(fi, fr); zm[i] = pk(mi, mr);
          }
        }
        const uint32_t rb = zb + (a * 8 + g) * ZROW * 4;
        const int k0 = 16 * warp + 4 * t;
        sts128(rb + zphys(k0) * 4, make_uint4(zf[0], zf[1], zf[2], zf[3]));
        sts32(rb + zphys(k0 == 0 ? 128 : 256 - k0) * 4, zm[0]);
        sts32(rb + zphys(255 - k0) * 4, zm[1]);
        sts32(rb + zphys(254 - k0) * 4, zm[2]);
        sts32(rb + zphys(253 - k0) * 4, zm[3]);
      }
      STAMP(18);
      wbar();
      float o[2][4][4], s2[2];
#pragma unroll
      for (int a = 0; a < 2; a++) {
        uint32_t in[4][2];
#pragma unroll
        for (int j = 0; j < 4; j++) { uint2 v = lds64(zb + ((a * 8 + warp) * ZROW + zphys(16 * t + 64 * j) + 2 * g) * 4); in[j][0] = v.x; in[j][1] = v.y; }
        float cr[2][4], ci[2][4], s1 = 0.f;
        fft_s1(K, in, cr, ci);
        fft_s2(K, cr, ci, o[a]);
        s2[a] = 0.f;
#pragma unroll
        for (int j = 0; j < 4; j++)
#pragma unroll
          for (int h = 0; h < 2; h++) {
            uint32_t hw;
            asm("add.rn.bf16x2 %0, %1, %2;" : "=r"(hw) : "r"(xw[a][j][h]), "r"(pk(o[a][j][2 * h + 1], o[a][j][2 * h])));
            const float u0 = blo(hw) - mean[a], u1 = bhi(hw) - mean[a];
            o[a][j][2 * h] = u0; o[a][j][2 * h + 1] = u1;
            s1 = fmaf(u0, u0, s1); s2[a] = fmaf(u1, u1, s2[a]);
          }
        s2[a] += s1;
      }
      float sv = (lane < 16 ? s2[0] : s2[1]) + __shfl_xor_sync(0xffffffffu, lane < 16 ? s2[1] : s2[0], 16);
#pragma unroll
      for (int m = 1; m < 16; m <<= 1) sv += __shfl_xor_sync(0xffffffffu, sv, m);
      const float var = sv * (1.f / 512.f), r1 = rsqrtf(var + 1e-5f);
      const float rr = r1 * rsqrtf(var * r1 * r1 + 1e-5f);
      const float ro = __shfl_xor_sync(0xffffffffu, rr, 16);
      char* np = (char*)g_Hn + (size_t)b * 4096 + (t >> 1) * 2048 + warp * 128 + ((((t & 1) * 4 + (g >> 1)) ^ warp ^ (b >> 6)) << 4) + (g & 1) * 8;
#pragma unroll
      for (int a = 0; a < 2; a++) {
        const float r = (lane >> 4) == a ? rr : ro;
#pragma unroll
        for (int j = 0; j < 4; j++)
          *(uint2*)(np + a * 1024 + (size_t)j * 128 * 4096) = make_uint2(pk(o[a][j][0] * r, o[a][j][1] * r), pk(o[a][j][2] * r, o[a][j][3] * r));
      }
      if ((lane & 15) == 0) g_st[256 * warp + 2 * b + (lane >> 4)] = make_float2(__fdividef(1.f, rr), lane ? mean[1] : mean[0]);
      STAMP(19);
      asm volatile("fence.proxy.async.shared::cta;" ::: "memory");
      wbar();
      STAMP(6);
      if (warp == 0) { fence_gpu(); cnt_arrive(scr, 2 + (b >> 6), lane); STAMP(25); }
      if (tid == 32) { sts32(sb + BASE_OFF, base); mbar_arrive(mb + MB_P3DONE * 8); }
    }
    const int wg = warp >> 2;
    const uint32_t peer_sb = mapa(sb, rank ^ 1);
    {
      float acc[44];
#pragma unroll
      for (int j = 0; j < 11; j++) {
        const uint32_t bw = __ldg(b1 + min(11 * ot + j, 171) * 4 + t);
        acc[4 * j] = blo(bw); acc[4 * j + 1] = bhi(bw); acc[4 * j + 2] = 0.f; acc[4 * j + 3] = 0.f;
      }
      const uint32_t da0 = desc_lo(sb + RING_OFF + wg * 2048, 0);
      uint32_t da = da0, db = desc_lo(sb, 1408), bar = mb;
      mbar_wait(mb + MB_W1 * 8, 0);
#pragma unroll 1
      for (int i = 0; i < 32; i++) {
        mbar_wait(bar + MB_FULL * 8, 0);
        if (i == 0) STAMP(7);
        asm volatile("wgmma.fence.sync.aligned;" ::: "memory");
        wgmma_n88_ss<1, 1, HI_SW128, HI_NOSW>(acc, da, db, 1);
        wgmma_n88_ss<1, 1, HI_SW128, HI_NOSW>(acc, da + 256, db + 176, 1);
        asm volatile("wgmma.commit_group.sync.aligned;" ::: "memory");
        da = da == da0 + 5 * 512 ? da0 : da + 512; db += 352;
        asm volatile("wgmma.wait_group.sync.aligned 1;" ::: "memory");
        if ((tid & 127) == 0) { if (i > 0) mbar_arrive(bar + (MB_EMPTY - 1) * 8); if (i == 4) mbar_arrive_cluster(peer_sb + BAR_OFF + MB_PEER1 * 8); }
        bar += 8;
      }
      asm volatile("wgmma.wait_group.sync.aligned 0;" ::: "memory");
#pragma unroll
      for (int i = 0; i < 44; i++) asm volatile("" : "+f"(acc[i]) :: "memory");
      if ((tid & 127) == 0) mbar_arrive(mb + (MB_EMPTY + 31) * 8);
      STAMP(8);
      mbar_wait_cluster(mb + MB_PEER1 * 8, 0);
#pragma unroll
      for (int j = 0; j < 3; j++)
        st_async4(peer_sb + j * 4096 + tid * 16, pk(acc[16 * j + 2], acc[16 * j + 3]), pk(acc[16 * j + 6], acc[16 * j + 7]), pk(acc[16 * j + 10], acc[16 * j + 11]),
                  j < 2 ? pk(acc[16 * j + 14], acc[16 * j + 15]) : 0u, peer_sb + BAR_OFF + MB_X1 * 8);
      const int uo = (4 * (warp >> 1) + (g >> 1)) * 32 + (2 * (2 * (warp & 1) + rank) + (g & 1)) * 4 + t;
      uint32_t* const ub = (uint32_t*)g_U + ((size_t)dt * 172 + 11 * ot) * 512;
      uint32_t *upa = ub + (uo ^ (ot >= 8 ? 256 : 0)), *upb = ub + (uo ^ (ot >= 7 ? 256 : 0));
      STAMP(20);
      mbar_wait_cluster(mb + MB_X1 * 8, 0);
      STAMP(21);
      uint32_t pv[12];
#pragma unroll
      for (int j = 0; j < 3; j++) { const uint4 v = lds128(sb + j * 4096 + tid * 16); pv[4 * j] = v.x; pv[4 * j + 1] = v.y; pv[4 * j + 2] = v.z; pv[4 * j + 3] = v.w; }
#pragma unroll
      for (int j = 0; j < 11; j++) {
        uint32_t v = pk(gelu(acc[4 * j] + blo(pv[j])), gelu(acc[4 * j + 1] + bhi(pv[j])));
        if (j < 7 || ot < 15) (j < 9 ? upa : upb)[j * 512] = v;
      }
      STAMP(22);
      asm volatile("fence.proxy.async.shared::cta;" ::: "memory");
      wbar();
      STAMP(9);
      if (warp == 0) { fence_gpu(); cnt_arrive(scr, 4 + dt, lane); STAMP(26); }
      if (tid == 32) mbar_arrive(mb + MB_X1DONE * 8);
    }
    {
      const int srow = 128 * ot + 16 * warp + g, oo = srow * 64 + dt * 16 + 8 * rank + t;
      float acc[64];
      const uint32_t da0 = desc_lo(sb + wg * 4096, 0), db0 = desc_lo(sb + RING_OFF, 2048);
      uint32_t da = da0 + 3 * 512, db = db0 + (32 % NST) * 512, bar = mb;
#pragma unroll
      for (int u = 0; u < 2; u++) {
        const int sr = srow + 8 * u, s1 = ot >> 1;
        const float2 st = __ldcg(g_st + sr);
        const float off = st.y + __uint_as_float((uint32_t)__ldg(b2 + sr) << 16);
#pragma unroll
        for (int jj = 0; jj < 2; jj++) {
          const uint4 v = ldcg128(g_Hn + (dt * 128 + ((sr & 255) >> 1)) * 256 + rank * 128 + (sr & 1) * 64 + s1 * 8 + ((4 * jj + t) ^ s1 ^ (ot & 1)));
          const uint32_t w[4] = {v.x, v.y, v.z, v.w};
#pragma unroll
          for (int j = 0; j < 4; j++) { acc[16 * jj + 4 * j + 2 * u] = fmaf(blo(w[j]), st.x, off); acc[16 * jj + 4 * j + 2 * u + 1] = fmaf(bhi(w[j]), st.x, off); }
        }
      }
#pragma unroll
      for (int j = 32; j < 64; j++) acc[j] = 0.f;
#pragma unroll 1
      for (int i = 0; i < 21; i++) {
        mbar_wait(bar + MB_W2 * 8, 0);
        mbar_wait(bar + (MB_FULL + 32) * 8, 0);
        if (i == 0) STAMP(10);
        asm volatile("wgmma.fence.sync.aligned;" ::: "memory");
        wgmma_n128_ss<1, 0, HI_SW128, HI_NOSW>(acc, da, db, 1);
        wgmma_n128_ss<1, 0, HI_SW128, HI_NOSW>(acc, da + 128, db + 256, 1);
        asm volatile("wgmma.commit_group.sync.aligned;" ::: "memory");
        da = i == 18 ? da0 : da + 512; db = db == db0 + 5 * 512 ? db0 : db + 512;
        asm volatile("wgmma.wait_group.sync.aligned 1;" ::: "memory");
        if ((tid & 127) == 0) { if (i > 0) mbar_arrive(bar + (MB_EMPTY + 31) * 8); if (i == 4) mbar_arrive_cluster(peer_sb + BAR_OFF + MB_PEER2 * 8); }
        bar += 8;
      }
      mbar_wait(bar + MB_W2 * 8, 0);
      mbar_wait(bar + (MB_FULL + 32) * 8, 0);
      asm volatile("wgmma.fence.sync.aligned;" ::: "memory");
      wgmma_n128_ss<1, 0, HI_SW128, HI_NOSW>(acc, da, db, 1);
      asm volatile("wgmma.commit_group.sync.aligned;" ::: "memory");
      asm volatile("wgmma.wait_group.sync.aligned 0;" ::: "memory");
#pragma unroll
      for (int i = 0; i < 64; i++) asm volatile("" : "+f"(acc[i]) :: "memory");
      STAMP(11);
      mbar_wait_cluster(mb + MB_PEER2 * 8, 0);
#pragma unroll
      for (int j = 0; j < 4; j++) {
        const int o = 32 + 16 * (j >> 1) + 2 * (j & 1);
        st_async4(peer_sb + 3 * 8192 + j * 4096 + tid * 16, pk(acc[o], acc[o + 1]), pk(acc[o + 4], acc[o + 5]), pk(acc[o + 8], acc[o + 9]), pk(acc[o + 12], acc[o + 13]),
                  peer_sb + BAR_OFF + MB_X2 * 8);
      }
      STAMP(23);
      mbar_wait_cluster(mb + MB_X2 * 8, 0);
      STAMP(24);
#pragma unroll
      for (int j = 0; j < 4; j++) {
        const int o = 16 * (j >> 1) + 2 * (j & 1);
        const uint4 v = lds128(sb + 3 * 8192 + j * 4096 + tid * 16);
        out[oo + 4 * (j >> 1) + 512 * (j & 1)] = make_uint4(pk(acc[o] + blo(v.x), acc[o + 1] + bhi(v.x)), pk(acc[o + 4] + blo(v.y), acc[o + 5] + bhi(v.y)),
                                                            pk(acc[o + 8] + blo(v.z), acc[o + 9] + bhi(v.z)), pk(acc[o + 12] + blo(v.w), acc[o + 13] + bhi(v.w)));
      }
      STAMP(12);
    }
  }
}

typedef CUresult (*EncodeFn)(CUtensorMap*, CUtensorMapDataType, cuuint32_t, void*, const cuuint64_t*, const cuuint64_t*, const cuuint32_t*,
                             const cuuint32_t*, CUtensorMapInterleave, CUtensorMapSwizzle, CUtensorMapL2promotion, CUtensorMapFloatOOBfill);

extern "C" void kernel_launch(void* const* d_in, const int* in_sizes, int n_in, void* d_out, int out_size) {
  static EncodeFn enc = nullptr;
  static void* scr = nullptr;
  if (!enc) {
    void* fn = nullptr; cudaDriverEntryPointQueryResult st;
    cudaGetDriverEntryPoint("cuTensorMapEncodeTiled", &fn, cudaEnableDefault, &st);
    enc = (EncodeFn)fn;
    cudaGetSymbolAddress(&scr, g_scr);
    cudaFuncSetAttribute(fused_kernel, cudaFuncAttributeMaxDynamicSharedMemorySize, SMEM_BYTES);
  }
  CUtensorMap tm, tm1;
  {
    cuuint64_t dims[3] = {(cuuint64_t)F_, 8, 256}, strides[2] = {(cuuint64_t)256 * F_ * 2, F_ * 2};
    cuuint32_t box[3] = {88, 8, 4}, es[3] = {1, 1, 1};
    enc(&tm1, CU_TENSOR_MAP_DATA_TYPE_BFLOAT16, 3, d_in[4], dims, strides, box, es, CU_TENSOR_MAP_INTERLEAVE_NONE, CU_TENSOR_MAP_SWIZZLE_NONE,
        W1_PROMO, CU_TENSOR_MAP_FLOAT_OOB_FILL_NONE);
  }
  {
    cuuint64_t dims[3] = {64, (cuuint64_t)F_, S_ / 64}, strides[2] = {S_ * 2, 128};
    cuuint32_t box[3] = {64, 32, 2}, es[3] = {1, 1, 1};
    enc(&tm, CU_TENSOR_MAP_DATA_TYPE_BFLOAT16, 3, d_in[6], dims, strides, box, es, CU_TENSOR_MAP_INTERLEAVE_NONE, CU_TENSOR_MAP_SWIZZLE_128B,
        CU_TENSOR_MAP_L2_PROMOTION_L2_256B, CU_TENSOR_MAP_FLOAT_OOB_FILL_NONE);
  }
  fused_kernel<<<NCTA, 384, SMEM_BYTES, cudaStreamPerThread>>>((const uint2*)d_in[0], (Scratch*)scr, (const unsigned short*)d_in[1], (const unsigned short*)d_in[2],
                                          (const uint32_t*)d_in[5], (const unsigned short*)d_in[7], (uint4*)d_out, (const char*)d_in[6], tm1, tm);
}
```

```cpp
#include <cuda_runtime.h>
#include <cuda.h>
#include <cuda_bf16.h>
#include <stdint.h>
#define W1_LATE 1
#define W1_PROMO CU_TENSOR_MAP_L2_PROMOTION_NONE
#define W2_NUM 1
#define W2_DEN 1
#define PF_W1 0
#define W1_DEPTH 1
#define W1_WARPS 4
#define W2_PRE 12
#define W2_PACE 1
#define FILT_LATE 0
#define W1_END 32
#define TLB_WARM 0
template<int TA, int TB, uint32_t HA, uint32_t HB> __device__ __forceinline__ void wgmma_n88_ss(float (&d)[44], uint32_t da, uint32_t db, int sd) {
  asm volatile("{\n.reg .pred p;\n.reg .b64 da, db;\nsetp.ne.b32 p, %46, 0;\nmov.b64 da, {%44, %49};\nmov.b64 db, {%45, %50};\n"
    "wgmma.mma_async.sync.aligned.m64n88k16.f32.bf16.bf16 {%0, %1, %2, %3, %4, %5, %6, %7, %8, %9, %10, %11, %12, %13, %14, %15, %16, %17, %18, %19, %20, %21, %22, %23, %24, %25, %26, %27, %28, %29, %30, %31, %32, %33, %34, %35, %36, %37, %38, %39, %40, %41, %42, %43}, da, db, p, 1, 1, %47, %48;\n}\n"
    : "+f"(d[0]), "+f"(d[1]), "+f"(d[2]), "+f"(d[3]), "+f"(d[4]), "+f"(d[5]), "+f"(d[6]), "+f"(d[7]), "+f"(d[8]), "+f"(d[9]), "+f"(d[10]), "+f"(d[11]), "+f"(d[12]), "+f"(d[13]), "+f"(d[14]), "+f"(d[15]), "+f"(d[16]), "+f"(d[17]), "+f"(d[18]), "+f"(d[19]), "+f"(d[20]), "+f"(d[21]), "+f"(d[22]), "+f"(d[23]), "+f"(d[24]), "+f"(d[25]), "+f"(d[26]), "+f"(d[27]), "+f"(d[28]), "+f"(d[29]), "+f"(d[30]), "+f"(d[31]), "+f"(d[32]), "+f"(d[33]), "+f"(d[34]), "+f"(d[35]), "+f"(d[36]), "+f"(d[37]), "+f"(d[38]), "+f"(d[39]), "+f"(d[40]), "+f"(d[41]), "+f"(d[42]), "+f"(d[43]) : "r"(da), "r"(db), "r"(sd), "n"(TA), "n"(TB), "n"(HA), "n"(HB));
}
template<int TA, int TB, uint32_t HA, uint32_t HB> __device__ __forceinline__ void wgmma_n128_ss(float (&d)[64], uint32_t da, uint32_t db, int sd) {
  asm volatile("{\n.reg .pred p;\n.reg .b64 da, db;\nsetp.ne.b32 p, %66, 0;\nmov.b64 da, {%64, %69};\nmov.b64 db, {%65, %70};\n"
    "wgmma.mma_async.sync.aligned.m64n128k16.f32.bf16.bf16 {%0, %1, %2, %3, %4, %5, %6, %7, %8, %9, %10, %11, %12, %13, %14, %15, %16, %17, %18, %19, %20, %21, %22, %23, %24, %25, %26, %27, %28, %29, %30, %31, %32, %33, %34, %35, %36, %37, %38, %39, %40, %41, %42, %43, %44, %45, %46, %47, %48, %49, %50, %51, %52, %53, %54, %55, %56, %57, %58, %59, %60, %61, %62, %63}, da, db, p, 1, 1, %67, %68;\n}\n"
    : "+f"(d[0]), "+f"(d[1]), "+f"(d[2]), "+f"(d[3]), "+f"(d[4]), "+f"(d[5]), "+f"(d[6]), "+f"(d[7]), "+f"(d[8]), "+f"(d[9]), "+f"(d[10]), "+f"(d[11]), "+f"(d[12]), "+f"(d[13]), "+f"(d[14]), "+f"(d[15]), "+f"(d[16]), "+f"(d[17]), "+f"(d[18]), "+f"(d[19]), "+f"(d[20]), "+f"(d[21]), "+f"(d[22]), "+f"(d[23]), "+f"(d[24]), "+f"(d[25]), "+f"(d[26]), "+f"(d[27]), "+f"(d[28]), "+f"(d[29]), "+f"(d[30]), "+f"(d[31]), "+f"(d[32]), "+f"(d[33]), "+f"(d[34]), "+f"(d[35]), "+f"(d[36]), "+f"(d[37]), "+f"(d[38]), "+f"(d[39]), "+f"(d[40]), "+f"(d[41]), "+f"(d[42]), "+f"(d[43]), "+f"(d[44]), "+f"(d[45]), "+f"(d[46]), "+f"(d[47]), "+f"(d[48]), "+f"(d[49]), "+f"(d[50]), "+f"(d[51]), "+f"(d[52]), "+f"(d[53]), "+f"(d[54]), "+f"(d[55]), "+f"(d[56]), "+f"(d[57]), "+f"(d[58]), "+f"(d[59]), "+f"(d[60]), "+f"(d[61]), "+f"(d[62]), "+f"(d[63]) : "r"(da), "r"(db), "r"(sd), "n"(TA), "n"(TB), "n"(HA), "n"(HB));
}

constexpr int S_ = 2048, F_ = 1376, DF = 257;
constexpr int NCTA = 128;
constexpr int W_BYTES = 180224;
constexpr int RING_OFF = W_BYTES;
constexpr int NST = 6;
constexpr int BAR_OFF = RING_OFF + NST * 8192;
constexpr int SMEM_BYTES = BAR_OFF + 2048;
constexpr int FILT_OFF = RING_OFF;
constexpr int XCH_OFF = RING_OFF + 16384;
constexpr int ZROW = 328;
constexpr int MB_FULL = 0, MB_W2 = 54, MB_W1T = 76, MB_X1 = 108, MB_X2 = 109, MB_X1DONE = 110, MB_P3DONE = 111, MB_FILT = 112, MB_W1 = 113,
              MB_EMPTY = 114, MB_PEER1 = 168, MB_PEER2 = 169, MB_X = 171, MB_N = 179;
constexpr int BASE_OFF = BAR_OFF + MB_N * 8;
#define W2_START 24

struct Scratch {
  uint4 T1[NCTA * 1024], T2[NCTA * 1024], Hn[4 * 128 * 256], U[4 * 172 * 128];
  float2 st[S_];
  unsigned cnt[8 * 4 * 64];
};
__device__ __align__(1024) Scratch g_scr;
#define g_T1 (scr->T1)
#define g_T2 (scr->T2)
#define g_Hn (scr->Hn)
#define g_U (scr->U)
#define g_st (scr->st)
#define g_cnt (scr->cnt)
#define STAMP(i)

__device__ __forceinline__ void mbar_init(uint32_t b, int c) { asm volatile("mbarrier.init.shared::cta.b64 [%0], %1;" :: "r"(b), "r"(c) : "memory"); }
__device__ __forceinline__ void mbar_expect(uint32_t b, int bytes) { asm volatile("mbarrier.arrive.expect_tx.shared::cta.b64 _, [%0], %1;" :: "r"(b), "r"(bytes) : "memory"); }
__device__ __forceinline__ void mbar_arrive(uint32_t b) { asm volatile("mbarrier.arrive.shared::cta.b64 _, [%0];" :: "r"(b) : "memory"); }
__device__ __forceinline__ void mbar_arrive_cluster(uint32_t remote) { asm volatile("mbarrier.arrive.relaxed.cluster.shared::cluster.b64 _, [%0];" :: "r"(remote) : "memory"); }
__device__ __forceinline__ uint32_t mapa(uint32_t a, uint32_t cta) { uint32_t r; asm("mapa.shared::cluster.u32 %0, %1, %2;" : "=r"(r) : "r"(a), "r"(cta)); return r; }
__device__ __forceinline__ void mbar_wait(uint32_t b, int ph) {
  asm volatile("{\n.reg .pred p;\n.reg .u32 n;\nmov.u32 n, 0;\nL_W:\n"
               "mbarrier.try_wait.parity.shared::cta.b64 p, [%0], %1;\n@p bra L_D;\n"
               "add.u32 n, n, 1;\nsetp.lt.u32 p, n, 4000000;\n@p bra L_W;\ntrap;\nL_D:\n}" :: "r"(b), "r"(ph) : "memory");
}
__device__ __forceinline__ void mbar_wait_cluster(uint32_t b, int ph) {
  asm volatile("{\n.reg .pred p;\n.reg .u32 n;\nmov.u32 n, 0;\nL_W:\n"
               "mbarrier.try_wait.parity.acquire.cluster.shared::cta.b64 p, [%0], %1;\n@p bra L_D;\n"
               "add.u32 n, n, 1;\nsetp.lt.u32 p, n, 4000000;\n@p bra L_W;\ntrap;\nL_D:\n}" :: "r"(b), "r"(ph) : "memory");
}
__device__ __forceinline__ void bulk_ld(uint32_t dst, const void* src, int bytes, uint32_t bar) {
  asm volatile("cp.async.bulk.shared::cluster.global.mbarrier::complete_tx::bytes [%0], [%1], %2, [%3];" :: "r"(dst), "l"(src), "r"(bytes), "r"(bar) : "memory");
}
__device__ __forceinline__ void tma3d(uint32_t dst, const CUtensorMap* tm, int c0, int c1, int c2, uint32_t bar) {
  asm volatile("cp.async.bulk.tensor.3d.shared::cluster.global.mbarrier::complete_tx::bytes [%0], [%1, {%3, %4, %5}], [%2];"
               :: "r"(dst), "l"(tm), "r"(bar), "r"(c0), "r"(c1), "r"(c2) : "memory");
}
__device__ __forceinline__ bool elect() { uint32_t p; asm volatile("{.reg .pred p; elect.sync _|p, 0xffffffff; selp.b32 %0, 1, 0, p;}" : "=r"(p)); return p; }
__device__ __forceinline__ uint32_t desc_lo(uint32_t addr, uint32_t lbo) { return ((addr & 0x3FFFF) >> 4) | ((lbo >> 4) << 16); }
constexpr uint32_t HI_SW128 = (1024 >> 4) | (1u << 30), HI_NOSW = 128 >> 4;
__device__ __forceinline__ uint32_t pk(float lo, float hi) { uint32_t r; asm("cvt.rn.bf16x2.f32 %0, %1, %2;" : "=r"(r) : "f"(hi), "f"(lo)); return r; }
__device__ __forceinline__ float blo(uint32_t w) { return __uint_as_float(w << 16); }
__device__ __forceinline__ float bhi(uint32_t w) { return __uint_as_float(w & 0xffff0000u); }
__device__ __forceinline__ void mmac(float (&d)[4], const float (&c)[4], const uint32_t (&a)[4], uint32_t b0, uint32_t b1) {
  asm("mma.sync.aligned.m16n8k16.row.col.f32.bf16.bf16.f32 {%0,%1,%2,%3}, {%4,%5,%6,%7}, {%8,%9}, {%10,%11,%12,%13};"
      : "=f"(d[0]), "=f"(d[1]), "=f"(d[2]), "=f"(d[3]) : "r"(a[0]), "r"(a[1]), "r"(a[2]), "r"(a[3]), "r"(b0), "r"(b1), "f"(c[0]), "f"(c[1]), "f"(c[2]), "f"(c[3]));
}
__device__ __forceinline__ void mma0(float (&d)[4], const uint32_t (&a)[4], uint32_t b0, uint32_t b1) { const float z[4] = {0.f, 0.f, 0.f, 0.f}; mmac(d, z, a, b0, b1); }
__device__ __forceinline__ uint32_t pin(uint32_t v) { asm volatile("shfl.sync.bfly.b32 %0, %0, 0, 31, 0xffffffff;" : "+r"(v)); return v; }
__device__ __forceinline__ float pinf(float v) { return __uint_as_float(pin(__float_as_uint(v))); }
__device__ __forceinline__ void wbar() { asm volatile("bar.sync 1, 256;" ::: "memory"); }
__device__ __forceinline__ void sts32(uint32_t a, uint32_t v) { asm volatile("st.shared.b32 [%0], %1;" :: "r"(a), "r"(v) : "memory"); }
__device__ __forceinline__ void sts64(uint32_t a, uint32_t x, uint32_t y) { asm volatile("st.shared.v2.b32 [%0], {%1,%2};" :: "r"(a), "r"(x), "r"(y) : "memory"); }
__device__ __forceinline__ void sts128(uint32_t a, uint4 v) { asm volatile("st.shared.v4.b32 [%0], {%1,%2,%3,%4};" :: "r"(a), "r"(v.x), "r"(v.y), "r"(v.z), "r"(v.w) : "memory"); }
__device__ __forceinline__ uint32_t lds32(uint32_t a) { uint32_t v; asm volatile("ld.shared.b32 %0, [%1];" : "=r"(v) : "r"(a) : "memory"); return v; }
__device__ __forceinline__ uint2 lds64(uint32_t a) { uint2 v; asm volatile("ld.shared.v2.b32 {%0,%1}, [%2];" : "=r"(v.x), "=r"(v.y) : "r"(a) : "memory"); return v; }
__device__ __forceinline__ uint4 lds128(uint32_t a) { uint4 v; asm volatile("ld.shared.v4.b32 {%0,%1,%2,%3}, [%4];" : "=r"(v.x), "=r"(v.y), "=r"(v.z), "=r"(v.w) : "r"(a) : "memory"); return v; }
__device__ __forceinline__ uint4 ldcg128(const void* p) { uint4 v; asm volatile("ld.global.cg.v4.b32 {%0,%1,%2,%3}, [%4];" : "=r"(v.x), "=r"(v.y), "=r"(v.z), "=r"(v.w) : "l"(p) : "memory"); return v; }
__device__ __forceinline__ void st_async4(uint32_t a, uint32_t x, uint32_t y, uint32_t z, uint32_t w, uint32_t bar) {
  asm volatile("st.async.weak.shared::cluster.mbarrier::complete_tx::bytes.v4.b32 [%0], {%1,%2,%3,%4}, [%5];" :: "r"(a), "r"(x), "r"(y), "r"(z), "r"(w), "r"(bar) : "memory");
}
constexpr int NREP = 4;
__device__ __forceinline__ void cnt_arrive(Scratch* scr, int i, int lane) {
  if (lane < NREP) asm volatile("red.relaxed.gpu.global.add.u32 [%0], 1;" :: "l"(&g_cnt[(i * NREP + lane) * 64]) : "memory");
}
template <bool ACQ> __device__ __forceinline__ void cnt_wait(Scratch* scr, int i, int rep, unsigned target) {
  unsigned v; int n = 0;
  do {
    if (ACQ) asm volatile("ld.acquire.gpu.global.u32 %0, [%1];" : "=r"(v) : "l"(&g_cnt[(i * NREP + rep) * 64]) : "memory");
    else asm volatile("ld.relaxed.gpu.global.u32 %0, [%1];" : "=r"(v) : "l"(&g_cnt[(i * NREP + rep) * 64]) : "memory");
    if (++n > 2000000) __trap(); } while ((int)(v - target) < 0);
}
__device__ __forceinline__ void fence_gpu() { asm volatile("fence.acq_rel.gpu;" ::: "memory"); }
__device__ __forceinline__ void tag_check(uint4& v, const uint4* p, uint32_t tag) {
  int n = 0;
  while ((v.x ^ tag) & 1) {
    asm volatile("ld.relaxed.gpu.global.v4.b32 {%0,%1,%2,%3}, [%4];" : "=r"(v.x), "=r"(v.y), "=r"(v.z), "=r"(v.w) : "l"(p) : "memory");
    if (++n > 2000000) __trap();
  }
}
template <int N> __device__ __forceinline__ void cs(int n, float& c, float& s) {
  n = ((n + N / 2) & (N - 1)) - N / 2;
  float a = (float)n * (6.283185307179586f / N);
  c = __cosf(a); s = __sinf(a);
}
constexpr float ALPHA = 1.13288f;
struct FftC { uint32_t a[4][4], b[8][2]; float tc[2][4], ts[2][4]; };
constexpr uint32_t NEG = 0x80008000u;

__device__ __forceinline__ void fft_s1(const FftC& K, const uint32_t (&in)[4][2], float (&cr)[2][4], float (&ci)[2][4]) {
#pragma unroll
  for (int h = 0; h < 2; h++) { mma0(cr[h], K.a[0], in[0][h], in[1][h]); mma0(ci[h], K.a[1], in[0][h], in[1][h]); }
#pragma unroll
  for (int h = 0; h < 2; h++) { mmac(cr[h], cr[h], K.a[2], in[2][h], in[3][h]); mmac(ci[h], ci[h], K.a[3], in[2][h], in[3][h]); }
}
__device__ __forceinline__ void fft_s2(const FftC& K, const float (&cr)[2][4], const float (&ci)[2][4], float (&o)[4][4]) {
  uint32_t a[2][4];
#pragma unroll
  for (int h = 0; h < 2; h++)
#pragma unroll
    for (int i = 0; i < 4; i++) {
      float xr = cr[i & 1][2 * h + (i >> 1)], xi = ci[i & 1][2 * h + (i >> 1)];
      a[i >> 1][2 * (i & 1) + h] = pk(xr * K.tc[h][i] + xi * K.ts[h][i], xi * K.tc[h][i] - xr * K.ts[h][i]);
    }
#pragma unroll
  for (int j = 0; j < 4; j++) mma0(o[j], a[0], K.b[j][0], K.b[j][1]);
#pragma unroll
  for (int j = 0; j < 4; j++) mmac(o[j], o[j], a[1], K.b[4 + j][0], K.b[4 + j][1]);
}
__device__ __forceinline__ int zphys(int k) { return k + 8 * (k >> 5); }
__device__ __forceinline__ float gelu(float u) {
  float z = u * (0.7978845608028654f + 0.035677408136300125f * u * u), th;
  asm("tanh.approx.f32 %0, %1;" : "=f"(th) : "f"(z));
  float hu = 0.5f * u;
  return fmaf(hu, th, hu);
}

extern "C" __global__ void __cluster_dims__(2, 1, 1) __launch_bounds__(384, 1)
fused_kernel(const uint2* __restrict__ x, Scratch* scr, const unsigned short* __restrict__ wr, const unsigned short* __restrict__ wi,
             const uint32_t* __restrict__ b1, const unsigned short* __restrict__ b2, uint4* __restrict__ out, const char* __restrict__ w2,
             const __grid_constant__ CUtensorMap tmW1, const __grid_constant__ CUtensorMap tmW2) {
  extern __shared__ __align__(1024) char smem[];
  const uint32_t sb = (uint32_t)__cvta_generic_to_shared(smem);
  const uint32_t mb = sb + BAR_OFF;
  const int b = blockIdx.x, rank = b & 1, pr = b >> 1, dt = pr & 3, ot = pr >> 2;
  const int warp = __shfl_sync(0xffffffffu, threadIdx.x >> 5, 0), lane = threadIdx.x & 31;
  const int g = lane >> 2, t = lane & 3;

  if (warp >= 8) {
    const int pw = warp - 8;
    if (pw < 3 && elect()) {
#pragma unroll
      for (int i = 0; i < 57; i++) mbar_init(mb + (pw * 57 + i) * 8, pw == 2 ? 2 : 1);
      if (pw == 1) { mbar_expect(mb + MB_X1 * 8, 12288); mbar_expect(mb + MB_X2 * 8, 16384); }
      asm volatile("fence.mbarrier_init.release.cluster;" ::: "memory");
    }
    __syncwarp();
    STAMP(0);
    asm volatile("bar.sync 2, 128;" ::: "memory");
    asm volatile("barrier.cluster.arrive.relaxed.aligned;" ::: "memory");
    auto w1_issue = [&](int i) {
      if (elect()) { mbar_expect(mb + (MB_W1T + i) * 8, 5632); tma3d(sb + i * 5632, &tmW1, 88 * ot, 0, 128 * rank + 4 * i, mb + (MB_W1T + i) * 8); }
      __syncwarp();
    };
    if (!W1_LATE && pw < W1_WARPS) for (int i = 0; i < W1_DEPTH; i++) w1_issue(pw + W1_WARPS * i);
    {
      const int j1 = b >> 4, q = b & 15, slot = lane & 15, h = lane >> 4;
      const bool hi = q >= 8;
      const int k = 16 * (q & 7) + slot, col = hi ? 256 - k : (k == 0 ? 128 : k);
      const int j0 = j1 + 8 * h + 512 * pw, o0 = (hi ? 2048 - 31 * 16 - j0 : j0) * DF + col, o31 = hi && j0 == 0 ? o0 - 2048 * DF : o0;
      uint32_t vr[32], vi[32];
      if (FILT_LATE) { asm volatile("bar.sync 3, 160;" ::: "memory"); asm volatile("" : "+l"(wr), "+l"(wi)); }
#pragma unroll
      for (int n = 0; n < 32; n++) { vr[n] = __ldg(wr + (n == 31 ? o31 : o0) + n * 16 * DF); vi[n] = __ldg(wi + (n == 31 ? o31 : o0) + n * 16 * DF); }
      const uint32_t f0 = sb + FILT_OFF + pw * 4096 + (hi ? 31 * 128 : 0) + h * 8 + (slot & 1) * 4, sw = ((slot >> 1) ^ (hi ? 7 : 0)) << 4;
      const int st = hi ? -128 : 128;
#pragma unroll
      for (int n = 0; n < 32; n++)
        sts32(f0 + n * st + (sw ^ ((((n >> 3) & 3) * 2 + (n & 1)) << 4)), __byte_perm(vr[n], vi[n], 0x5410) ^ (hi ? 0x80000000u : 0u));
      asm volatile("bar.sync 2, 128;" ::: "memory");
      if (threadIdx.x == 352) mbar_arrive(mb + MB_FILT * 8);
    }
    __syncwarp();
    STAMP(1);
    {
      if (W1_LATE && pw < W1_WARPS) for (int i = 0; i < W1_DEPTH; i++) w1_issue(pw + W1_WARPS * i);
      const uint32_t rd = ((lane & 7) * 11 + (lane >> 3)) * 16, wr = lane * 16;
#pragma unroll 1
      for (int box = pw < W1_WARPS ? pw : 32; box < W1_END; box += W1_WARPS) {
        mbar_wait(mb + (MB_W1T + box) * 8, 0);
        if (box + W1_WARPS * W1_DEPTH < 32) w1_issue(box + W1_WARPS * W1_DEPTH);
        const uint32_t p = sb + box * 5632;
        uint4 v[4][3];
#pragma unroll
        for (int n = 0; n < 4; n++) { v[n][0] = lds128(p + n * 1408 + rd); v[n][1] = lds128(p + n * 1408 + rd + 64); if (lane < 24) v[n][2] = lds128(p + n * 1408 + rd + 128); }
        __syncwarp();
#pragma unroll
        for (int n = 0; n < 4; n++) { sts128(p + n * 1408 + wr, v[n][0]); sts128(p + n * 1408 + wr + 512, v[n][1]); if (lane < 24) sts128(p + n * 1408 + wr + 1024, v[n][2]); }
      }
      if (lane == 0) asm volatile("cp.async.bulk.prefetch.L2.global [%0], %1;" :: "l"(w2 + (size_t)(b * 4 + pw) * 11008), "r"(11008) : "memory");
      asm volatile("fence.proxy.async.shared::cta;" ::: "memory");
      asm volatile("bar.sync 2, 128;" ::: "memory");
      if (threadIdx.x == 352) mbar_arrive(mb + MB_W1 * 8);
    }
    STAMP(2);
    asm volatile("barrier.cluster.wait.aligned;" ::: "memory");
    if (pw == 3) {
#pragma unroll 1
      for (int n = 0; n < 22; n++) {
        if (n < W2_PRE) mbar_wait(mb + (MB_EMPTY + min(31, max(((n + 4) * 16 + 10) / 11 - 1, W2_START + n * W2_NUM / W2_DEN))) * 8, 0);
        else { mbar_wait(mb + MB_X1DONE * 8, 0); if (W2_PACE) mbar_wait(mb + (MB_FULL + 32 - W2_PRE + n) * 8, 0); }
        if (elect()) { mbar_expect(mb + (MB_W2 + n) * 8, 8192); tma3d(sb + (n < 19 ? n + 3 : n - 19) * 8192, &tmW2, 0, 688 * rank + 32 * n, 2 * ot, mb + (MB_W2 + n) * 8); }
      }
    } else {
      int i = pw;
      uint32_t dst = sb + RING_OFF + pw * 8192;
      const uint32_t dsum = 2 * dst + 3 * 8192;
      const char* src = (const char*)g_Hn + ((size_t)dt * 128 + 64 * rank) * 4096;
#pragma unroll 1
      for (int gm = 0; gm < 2; gm++) {
        if (pw == 0) {
          mbar_wait(mb + (gm ? MB_X1DONE : MB_P3DONE) * 8, 0);
          STAMP(3 + 2 * gm);
          if (lane == 0) cnt_wait<true>(scr, gm ? 4 + dt : 2 + rank, ot & (NREP - 1), ((lds32(sb + BASE_OFF) >> 1) + 64) >> gm);
        }
        asm volatile("bar.sync 2, 96;" ::: "memory");
        STAMP(4 + 2 * gm);
        asm volatile("fence.proxy.async.global;" ::: "memory");
#pragma unroll 1
        for (; i < (gm ? 54 : 32); i += 3) {
          if (i >= NST) mbar_wait(mb + (MB_EMPTY - NST + i) * 8, 0);
          if (elect()) {
            const int bytes = i < 53 ? 8192 : 4096;
            mbar_expect(mb + (MB_FULL + i) * 8, bytes); bulk_ld(dst, src + i * 8192, bytes, mb + (MB_FULL + i) * 8);
          }
          dst = dsum - dst;
        }
        src = (const char*)g_U + ((size_t)dt * 172 + 86 * rank) * 2048 - 32 * 8192;
      }
      STAMP(7);
    }
  } else {
    const int tid = threadIdx.x;
    uint32_t xw[2][4][2];
    const uint32_t zb = sb + XCH_OFF, zw = zb + warp * ZROW * 4;
    const int rep = ot & (NREP - 1);
    if (elect()) {
      const uint32_t xb = mb + (MB_X + warp) * 8;
      mbar_init(xb, 1);
      asm volatile("fence.proxy.async.shared::cta;" ::: "memory");
      mbar_expect(xb, 2064);
      bulk_ld(zw, x + (size_t)(256 * warp + 2 * b) * 128, 1024, xb);
      bulk_ld(zw + 8 * ZROW * 4, x + (size_t)(256 * warp + 2 * b + 1) * 128, 1024, xb);
      bulk_ld(zw + 1280, &g_cnt[(1 * NREP + rep) * 64], 16, xb);
    }
    __syncwarp();
    STAMP(0);
    asm volatile("barrier.cluster.arrive.relaxed.aligned;" ::: "memory");
    STAMP(30);
    FftC K;
    {
      float c, s;
#pragma unroll
      for (int h = 0; h < 2; h++)
#pragma unroll
        for (int j = 0; j < 2; j++) {
          cs<16>((2 * g + h) * (t + 4 * j), c, s);
          const uint32_t re = pk(ALPHA * c, ALPHA * s), im = pk(-ALPHA * s, ALPHA * c);
          K.a[0][2 * j + h] = re; K.a[1][2 * j + h] = im; K.a[2][2 * j + h] = pin(h ? re ^ NEG : re); K.a[3][2 * j + h] = pin(h ? im ^ NEG : im);
        }
      STAMP(27);
#pragma unroll
      for (int i = 0; i < 4; i++) {
        cs<16>((4 * t + i) * (g >> 1) + 4 * (g & 1), c, s);
        const uint32_t P = pk(ALPHA * c, ALPHA * s), Q = pk(-ALPHA * s, ALPHA * c);
#pragma unroll
        for (int jj = 0; jj < 4; jj++) { const uint32_t v = ((i * jj) & 1 ? Q : P) ^ ((i * jj) & 2 ? NEG : 0u); K.b[4 * (i >> 1) + jj][i & 1] = jj ? pin(v) : v; }
      }
      STAMP(28);
#pragma unroll
      for (int h = 0; h < 2; h++)
#pragma unroll
        for (int i = 0; i < 4; i++) {
          cs<256>((2 * g + h) * (4 * t + i), c, s);
          K.tc[h][i] = pinf(c * (1.f / (ALPHA * ALPHA))); K.ts[h][i] = pinf(s * (1.f / (ALPHA * ALPHA)));
        }
    }
    STAMP(29);
    const int key = ((b >> 3) & 3) * 2 + (b & 1);
    float mean[2];
    uint32_t tag, base;
    {
      uint32_t a8[2][4], a8c[2][4], a8n[2][4]; float vc[4], vs[4];
#pragma unroll
      for (int a = 0; a < 2; a++)
#pragma unroll
        for (int u = 0; u < 4; u++) {
          float c, s; cs<2048>(g * (256 * (t + 4 * (u >> 1)) + 2 * b + a), c, s);
          a8[a][u] = u & 1 ? pk(-s, c) : pk(c, s);
          a8c[a][u] = pin(a8[a][u] ^ 0x80000000u); a8n[a][u] = pin(a8[a][u] ^ 0x00008000u);
        }
#pragma unroll
      for (int i = 0; i < 4; i++) { cs<512>(16 * warp + 8 * (i >> 1) + 2 * t + (i & 1) + 128, vc[i], vs[i]); vc[i] = pinf(vc[i]); vs[i] = pinf(vs[i]); }
      STAMP(13);
      mbar_wait(mb + (MB_X + warp) * 8, 0);
#pragma unroll
      for (int a = 0; a < 2; a++)
#pragma unroll
        for (int j = 0; j < 4; j++) { const uint2 v = lds64(zw + a * 8 * ZROW * 4 + j * 256 + (8 * t + g) * 8); xw[a][j][0] = v.x; xw[a][j][1] = v.y; }
      base = lds32(zw + 1280);
      __syncwarp();
      tag = (~base >> 7) & 1;
#pragma unroll
      for (int a = 0; a < 2; a++) {
        float cr[2][4], ci[2][4], o[4][4];
        if (a == 0) { if (xw[0][0][0] == 0x12345678u && xw[1][3][1] == 0x12345679u) STAMP(31); STAMP(14); }
        fft_s1(K, xw[a], cr, ci);
        if (FILT_LATE && a == 0 && warp == 0) asm volatile("bar.arrive 3, 160;" :: "f"(cr[0][0]) : "memory");
        float sm = ((cr[0][0] + cr[0][1]) + (cr[1][0] + cr[1][1])) + ((ci[0][0] + ci[0][1]) + (ci[1][0] + ci[1][1]));
        sm += __shfl_xor_sync(0xffffffffu, sm, 1); sm += __shfl_xor_sync(0xffffffffu, sm, 2);
        sm = g == 0 ? sm * (1.f / 32.f) : 0.f;
#pragma unroll
        for (int h = 0; h < 2; h++) { cr[h][0] -= sm; cr[h][1] -= sm; ci[h][0] -= sm; ci[h][1] -= sm; }
        mean[a] = __shfl_sync(0xffffffffu, sm, 0) * (1.f / (16.f * 1.1328125f));
        float q = 0.f, q2 = 0.f;
#pragma unroll
        for (int i = 0; i < 4; i++) { q = fmaf(cr[0][i], cr[0][i], q); q2 = fmaf(cr[1][i], cr[1][i], q2); q = fmaf(ci[0][i], ci[0][i], q); q2 = fmaf(ci[1][i], ci[1][i], q2); }
        q += q2;
#pragma unroll
        for (int m = 1; m < 32; m <<= 1) q += __shfl_xor_sync(0xffffffffu, q, m);
        float r = rsqrtf(q * (1.f / (512.f * 16.f * ALPHA * ALPHA)) + 1e-5f) * 4.76837158203125e-7f;
        fft_s2(K, cr, ci, o);
#pragma unroll
        for (int j = 0; j < 4; j++)
          sts64(zb + ((a * 8 + warp) * ZROW + zphys(16 * t + 64 * j) + 2 * g) * 4, pk(o[j][0] * r, o[j][1] * r), pk(o[j][2] * r, o[j][3] * r));
      }
      STAMP(15);
      wbar();
      uint4* tp = g_T1 + (size_t)(g * 16 + warp) * 1024 + b * 8;
#pragma unroll
      for (int nt = 0; nt < 2; nt++) {
        const int k = 16 * warp + 8 * nt + g, km = k == 0 ? 128 : 256 - k;
        uint32_t lo[4], hi[4];
#pragma unroll
        for (int a = 0; a < 2; a++) {
          const uint32_t rb = zb + (a * 8 + t) * ZROW * 4;
          float A[4], S[4], D[4];
          const uint32_t m0 = lds32(rb + zphys(km) * 4), m1 = lds32(rb + (4 * ZROW + zphys(km)) * 4);
          mma0(A, a8[a], lds32(rb + zphys(k) * 4), lds32(rb + (4 * ZROW + zphys(k)) * 4));
          mmac(S, A, a8c[a], m0, m1);
          mmac(D, A, a8n[a], m0, m1);
#pragma unroll
          for (int e = 0; e < 2; e++) {
            const float c = vc[2 * nt + e], s = vs[2 * nt + e];
            float lr = fmaf(D[2 + e], s, fmaf(D[e], c, S[e])), li = fmaf(-D[e], s, fmaf(D[2 + e], c, S[2 + e]));
            float hr = fmaf(2.f, S[e], -lr), hii = fmaf(2.f, S[2 + e], -li);
            if (nt == 0 && e == 0) {
              const bool sp = warp == 0 && t == 0;
              lr = sp ? S[0] - D[0] : lr; li = sp ? S[2] - D[2] : li;
              hr = sp ? 2.f * (A[0] - A[2]) : hr; hii = sp ? 2.f * (A[0] + A[2]) : hii;
            }
            lo[2 * a + e] = pk(lr, li); hi[2 * a + e] = pk(hr, hii);
          }
        }
        const int w = (t + 4 * nt) ^ key;
        tp[w] = make_uint4((lo[0] & ~1u) | tag, lo[1], lo[2], lo[3]);
        tp[8 * 1024 + w] = make_uint4((hi[0] & ~1u) | tag, hi[1], hi[2], hi[3]);
      }
      wbar();
      STAMP(1);
      if (warp == 0) cnt_arrive(scr, 0, lane);
    }
    {
      const uint32_t off = (8 * t + g) * 128 + ((warp ^ (2 * t + (g & 1))) << 4);
      asm volatile("barrier.cluster.wait.aligned;" ::: "memory");
      mbar_wait(mb + MB_FILT * 8, 0);
      if (tid == 0) cnt_wait<false>(scr, 0, rep, base + NCTA);
      wbar();
#pragma unroll
      for (int j = 0; j < 4; j++)
        asm volatile("cp.async.cg.shared.global [%0], [%1], 16;" :: "r"(zb + j * 4096 + tid * 16), "l"(g_T1 + (size_t)b * 1024 + j * 256 + tid) : "memory");
      STAMP(2);
      uint32_t in[2][4][2], fw[2][4][2];
#pragma unroll
      for (int j = 0; j < 4; j++) {
        uint4 v = lds128(sb + FILT_OFF + off + j * 4096);
        fw[0][j][0] = v.x; fw[1][j][0] = v.y; fw[0][j][1] = v.z; fw[1][j][1] = v.w;
      }
      asm volatile("cp.async.wait_all;" ::: "memory");
      wbar();
      STAMP(3);
      uint4 iv[4];
#pragma unroll
      for (int j = 0; j < 4; j++) iv[j] = lds128(zb + off + j * 4096);
      if (((iv[0].x ^ tag) | (iv[1].x ^ tag) | (iv[2].x ^ tag) | (iv[3].x ^ tag)) & 1) {
#pragma unroll
        for (int j = 0; j < 4; j++) tag_check(iv[j], g_T1 + (size_t)b * 1024 + j * 256 + (off >> 4), tag);
      }
      __syncwarp();
#pragma unroll
      for (int j = 0; j < 4; j++) { in[0][j][0] = iv[j].x; in[1][j][0] = iv[j].y; in[0][j][1] = iv[j].z; in[1][j][1] = iv[j].w; }
#pragma unroll
      for (int sg = 0; sg < 2; sg++) {
        float cr[2][4], ci[2][4], o[4][4];
        fft_s1(K, in[sg], cr, ci);
        fft_s2(K, cr, ci, o);
#pragma unroll
        for (int j = 0; j < 4; j++)
#pragma unroll
          for (int h = 0; h < 2; h++) {
            float fr = blo(fw[sg][j][h]), fi = bhi(fw[sg][j][h]), xr = o[j][2 * h], xi = o[j][2 * h + 1];
            in[sg][j][h] = pk(xr * fi + xi * fr, xr * fr - xi * fi);
          }
        fft_s1(K, in[sg], cr, ci);
        fft_s2(K, cr, ci, o);
#pragma unroll
        for (int j = 0; j < 4; j++) { in[sg][j][0] = pk(o[j][0], o[j][1]); in[sg][j][1] = pk(o[j][2], o[j][3]); }
      }
#pragma unroll
      for (int j = 0; j < 4; j++) sts128(zb + off + j * 4096, make_uint4((in[0][j][0] & ~1u) | tag, in[1][j][0], in[0][j][1], in[1][j][1]));
      STAMP(16);
      wbar();
#pragma unroll
      for (int j = 0; j < 4; j++) g_T2[(size_t)b * 1024 + j * 256 + tid] = lds128(zb + j * 4096 + tid * 16);
      wbar();
      STAMP(4);
      if (warp == 0) cnt_arrive(scr, 1, lane);
    }
    {
      uint32_t a8[2][4], a8n[2][4]; float vc[4], vs[4];
#pragma unroll
      for (int a = 0; a < 2; a++)
#pragma unroll
        for (int u = 0; u < 4; u++) {
          float c, s; cs<2048>((t + 4 * (u >> 1)) * (256 * g + 2 * b + a), c, s);
          a8[a][u] = u & 1 ? pk(-s, c) : pk(c, s);
          a8n[a][u] = pin(a8[a][u] ^ NEG);
        }
#pragma unroll
      for (int i = 0; i < 4; i++) { cs<512>(16 * warp + 4 * t + i + 128, vc[i], vs[i]); vc[i] = pinf(vc[i]); vs[i] = pinf(vs[i]); }
      if (tid == 0) cnt_wait<false>(scr, 1, rep, base + NCTA);
      wbar();
      STAMP(5);
      const uint4* tp = g_T2 + (size_t)(t * 16 + warp) * 1024 + b * 8 + (g ^ key);
      uint4 L0 = ldcg128(tp), L1 = ldcg128(tp + 64 * 1024), H0 = ldcg128(tp + 8 * 1024), H1 = ldcg128(tp + 72 * 1024);
      if (((L0.x ^ tag) | (L1.x ^ tag) | (H0.x ^ tag) | (H1.x ^ tag)) & 1) {
        tag_check(L0, tp, tag); tag_check(L1, tp + 64 * 1024, tag); tag_check(H0, tp + 8 * 1024, tag); tag_check(H1, tp + 72 * 1024, tag);
      }
      __syncwarp();
      STAMP(17);
      const uint32_t l0[4] = {L0.x, L0.y, L0.z, L0.w}, l1[4] = {L1.x, L1.y, L1.z, L1.w}, h0[4] = {H0.x, H0.y, H0.z, H0.w}, h1[4] = {H1.x, H1.y, H1.z, H1.w};
#pragma unroll
      for (int a = 0; a < 2; a++) {
        uint32_t zf[4], zm[4];
#pragma unroll
        for (int sg = 0; sg < 2; sg++) {
          float A[4], S[4], D[4];
          mma0(A, a8[a], l0[2 * a + sg], l1[2 * a + sg]);
          mmac(S, A, a8[a], h0[2 * a + sg], h1[2 * a + sg]);
          mmac(D, A, a8n[a], h0[2 * a + sg], h1[2 * a + sg]);
#pragma unroll
          for (int e = 0; e < 2; e++) {
            const int i = 2 * e + sg;
            float fr = fmaf(-D[e], vs[i], fmaf(D[2 + e], vc[i], S[2 + e])), fi = fmaf(D[2 + e], vs[i], fmaf(D[e], vc[i], S[e]));
            float mr = fmaf(2.f, S[2 + e], -fr), mi = fmaf(-2.f, S[e], fi);
            if (i == 0) {
              const bool sp = warp == 0 && t == 0;
              fr = sp ? S[2] - A[2] : fr; fi = sp ? A[2] - S[2] : fi;
              mr = sp ? 2.f * A[2] : mr; mi = sp ? -2.f * A[0] : mi;
            }
            zf[i] = pk(fi, fr); zm[i] = pk(mi, mr);
          }
        }
        const uint32_t rb = zb + (a * 8 + g) * ZROW * 4;
        const int k0 = 16 * warp + 4 * t;
        sts128(rb + zphys(k0) * 4, make_uint4(zf[0], zf[1], zf[2], zf[3]));
        sts32(rb + zphys(k0 == 0 ? 128 : 256 - k0) * 4, zm[0]);
        sts32(rb + zphys(255 - k0) * 4, zm[1]);
        sts32(rb + zphys(254 - k0) * 4, zm[2]);
        sts32(rb + zphys(253 - k0) * 4, zm[3]);
      }
      STAMP(18);
      wbar();
      float o[2][4][4], s2[2];
#pragma unroll
      for (int a = 0; a < 2; a++) {
        uint32_t in[4][2];
#pragma unroll
        for (int j = 0; j < 4; j++) { uint2 v = lds64(zb + ((a * 8 + warp) * ZROW + zphys(16 * t + 64 * j) + 2 * g) * 4); in[j][0] = v.x; in[j][1] = v.y; }
        float cr[2][4], ci[2][4], s1 = 0.f;
        fft_s1(K, in, cr, ci);
        fft_s2(K, cr, ci, o[a]);
        s2[a] = 0.f;
#pragma unroll
        for (int j = 0; j < 4; j++)
#pragma unroll
          for (int h = 0; h < 2; h++) {
            uint32_t hw;
            asm("add.rn.bf16x2 %0, %1, %2;" : "=r"(hw) : "r"(xw[a][j][h]), "r"(pk(o[a][j][2 * h + 1], o[a][j][2 * h])));
            const float u0 = blo(hw) - mean[a], u1 = bhi(hw) - mean[a];
            o[a][j][2 * h] = u0; o[a][j][2 * h + 1] = u1;
            s1 = fmaf(u0, u0, s1); s2[a] = fmaf(u1, u1, s2[a]);
          }
        s2[a] += s1;
      }
      float sv = (lane < 16 ? s2[0] : s2[1]) + __shfl_xor_sync(0xffffffffu, lane < 16 ? s2[1] : s2[0], 16);
#pragma unroll
      for (int m = 1; m < 16; m <<= 1) sv += __shfl_xor_sync(0xffffffffu, sv, m);
      const float var = sv * (1.f / 512.f), r1 = rsqrtf(var + 1e-5f);
      const float rr = r1 * rsqrtf(var * r1 * r1 + 1e-5f);
      const float ro = __shfl_xor_sync(0xffffffffu, rr, 16);
      char* np = (char*)g_Hn + (size_t)b * 4096 + (t >> 1) * 2048 + warp * 128 + ((((t & 1) * 4 + (g >> 1)) ^ warp ^ (b >> 6)) << 4) + (g & 1) * 8;
#pragma unroll
      for (int a = 0; a < 2; a++) {
        const float r = (lane >> 4) == a ? rr : ro;
#pragma unroll
        for (int j = 0; j < 4; j++)
          *(uint2*)(np + a * 1024 + (size_t)j * 128 * 4096) = make_uint2(pk(o[a][j][0] * r, o[a][j][1] * r), pk(o[a][j][2] * r, o[a][j][3] * r));
      }
      if ((lane & 15) == 0) g_st[256 * warp + 2 * b + (lane >> 4)] = make_float2(__fdividef(1.f, rr), lane ? mean[1] : mean[0]);
      STAMP(19);
      asm volatile("fence.proxy.async.shared::cta;" ::: "memory");
      wbar();
      STAMP(6);
      if (warp == 0) { fence_gpu(); cnt_arrive(scr, 2 + (b >> 6), lane); STAMP(25); }
      if (tid == 32) { sts32(sb + BASE_OFF, base); mbar_arrive(mb + MB_P3DONE * 8); }
    }
    const int wg = warp >> 2;
    const uint32_t peer_sb = mapa(sb, rank ^ 1);
    {
      float acc[44];
#pragma unroll
      for (int j = 0; j < 11; j++) {
        const uint32_t bw = __ldg(b1 + min(11 * ot + j, 171) * 4 + t);
        acc[4 * j] = blo(bw); acc[4 * j + 1] = bhi(bw); acc[4 * j + 2] = 0.f; acc[4 * j + 3] = 0.f;
      }
      const uint32_t da0 = desc_lo(sb + RING_OFF + wg * 2048, 0);
      uint32_t da = da0, db = desc_lo(sb, 1408), bar = mb;
      mbar_wait(mb + MB_W1 * 8, 0);
#pragma unroll 1
      for (int i = 0; i < 32; i++) {
        mbar_wait(bar + MB_FULL * 8, 0);
        if (i == 0) STAMP(7);
        asm volatile("wgmma.fence.sync.aligned;" ::: "memory");
        wgmma_n88_ss<1, 1, HI_SW128, HI_NOSW>(acc, da, db, 1);
        wgmma_n88_ss<1, 1, HI_SW128, HI_NOSW>(acc, da + 256, db + 176, 1);
        asm volatile("wgmma.commit_group.sync.aligned;" ::: "memory");
        da = da == da0 + 5 * 512 ? da0 : da + 512; db += 352;
        asm volatile("wgmma.wait_group.sync.aligned 1;" ::: "memory");
        if ((tid & 127) == 0) { if (i > 0) mbar_arrive(bar + (MB_EMPTY - 1) * 8); if (i == 4) mbar_arrive_cluster(peer_sb + BAR_OFF + MB_PEER1 * 8); }
        bar += 8;
      }
      asm volatile("wgmma.wait_group.sync.aligned 0;" ::: "memory");
#pragma unroll
      for (int i = 0; i < 44; i++) asm volatile("" : "+f"(acc[i]) :: "memory");
      if ((tid & 127) == 0) mbar_arrive(mb + (MB_EMPTY + 31) * 8);
      STAMP(8);
      mbar_wait_cluster(mb + MB_PEER1 * 8, 0);
#pragma unroll
      for (int j = 0; j < 3; j++)
        st_async4(peer_sb + j * 4096 + tid * 16, pk(acc[16 * j + 2], acc[16 * j + 3]), pk(acc[16 * j + 6], acc[16 * j + 7]), pk(acc[16 * j + 10], acc[16 * j + 11]),
                  j < 2 ? pk(acc[16 * j + 14], acc[16 * j + 15]) : 0u, peer_sb + BAR_OFF + MB_X1 * 8);
      const int uo = (4 * (warp >> 1) + (g >> 1)) * 32 + (2 * (2 * (warp & 1) + rank) + (g & 1)) * 4 + t;
      uint32_t* const ub = (uint32_t*)g_U + ((size_t)dt * 172 + 11 * ot) * 512;
      uint32_t *upa = ub + (uo ^ (ot >= 8 ? 256 : 0)), *upb = ub + (uo ^ (ot >= 7 ? 256 : 0));
      STAMP(20);
      mbar_wait_cluster(mb + MB_X1 * 8, 0);
      STAMP(21);
      uint32_t pv[12];
#pragma unroll
      for (int j = 0; j < 3; j++) { const uint4 v = lds128(sb + j * 4096 + tid * 16); pv[4 * j] = v.x; pv[4 * j + 1] = v.y; pv[4 * j + 2] = v.z; pv[4 * j + 3] = v.w; }
#pragma unroll
      for (int j = 0; j < 11; j++) {
        uint32_t v = pk(gelu(acc[4 * j] + blo(pv[j])), gelu(acc[4 * j + 1] + bhi(pv[j])));
        if (j < 7 || ot < 15) (j < 9 ? upa : upb)[j * 512] = v;
      }
      STAMP(22);
      asm volatile("fence.proxy.async.shared::cta;" ::: "memory");
      wbar();
      STAMP(9);
      if (warp == 0) { fence_gpu(); cnt_arrive(scr, 4 + dt, lane); STAMP(26); }
      if (tid == 32) mbar_arrive(mb + MB_X1DONE * 8);
    }
    {
      const int srow = 128 * ot + 16 * warp + g, oo = srow * 64 + dt * 16 + 8 * rank + t;
      float acc[64];
      const uint32_t da0 = desc_lo(sb + wg * 4096, 0), db0 = desc_lo(sb + RING_OFF, 2048);
      uint32_t da = da0 + 3 * 512, db = db0 + (32 % NST) * 512, bar = mb;
#pragma unroll
      for (int u = 0; u < 2; u++) {
        const int sr = srow + 8 * u, s1 = ot >> 1;
        const float2 st = __ldcg(g_st + sr);
        const float off = st.y + __uint_as_float((uint32_t)__ldg(b2 + sr) << 16);
#pragma unroll
        for (int jj = 0; jj < 2; jj++) {
          const uint4 v = ldcg128(g_Hn + (dt * 128 + ((sr & 255) >> 1)) * 256 + rank * 128 + (sr & 1) * 64 + s1 * 8 + ((4 * jj + t) ^ s1 ^ (ot & 1)));
          const uint32_t w[4] = {v.x, v.y, v.z, v.w};
#pragma unroll
          for (int j = 0; j < 4; j++) { acc[16 * jj + 4 * j + 2 * u] = fmaf(blo(w[j]), st.x, off); acc[16 * jj + 4 * j + 2 * u + 1] = fmaf(bhi(w[j]), st.x, off); }
        }
      }
#pragma unroll
      for (int j = 32; j < 64; j++) acc[j] = 0.f;
#pragma unroll 1
      for (int i = 0; i < 21; i++) {
        mbar_wait(bar + MB_W2 * 8, 0);
        mbar_wait(bar + (MB_FULL + 32) * 8, 0);
        if (i == 0) STAMP(10);
        asm volatile("wgmma.fence.sync.aligned;" ::: "memory");
        wgmma_n128_ss<1, 0, HI_SW128, HI_NOSW>(acc, da, db, 1);
        wgmma_n128_ss<1, 0, HI_SW128, HI_NOSW>(acc, da + 128, db + 256, 1);
        asm volatile("wgmma.commit_group.sync.aligned;" ::: "memory");
        da = i == 18 ? da0 : da + 512; db = db == db0 + 5 * 512 ? db0 : db + 512;
        asm volatile("wgmma.wait_group.sync.aligned 1;" ::: "memory");
        if ((tid & 127) == 0) { if (i > 0) mbar_arrive(bar + (MB_EMPTY + 31) * 8); if (i == 4) mbar_arrive_cluster(peer_sb + BAR_OFF + MB_PEER2 * 8); }
        bar += 8;
      }
      mbar_wait(bar + MB_W2 * 8, 0);
      mbar_wait(bar + (MB_FULL + 32) * 8, 0);
      asm volatile("wgmma.fence.sync.aligned;" ::: "memory");
      wgmma_n128_ss<1, 0, HI_SW128, HI_NOSW>(acc, da, db, 1);
      asm volatile("wgmma.commit_group.sync.aligned;" ::: "memory");
      asm volatile("wgmma.wait_group.sync.aligned 0;" ::: "memory");
#pragma unroll
      for (int i = 0; i < 64; i++) asm volatile("" : "+f"(acc[i]) :: "memory");
      STAMP(11);
      mbar_wait_cluster(mb + MB_PEER2 * 8, 0);
#pragma unroll
      for (int j = 0; j < 4; j++) {
        const int o = 32 + 16 * (j >> 1) + 2 * (j & 1);
        st_async4(peer_sb + 3 * 8192 + j * 4096 + tid * 16, pk(acc[o], acc[o + 1]), pk(acc[o + 4], acc[o + 5]), pk(acc[o + 8], acc[o + 9]), pk(acc[o + 12], acc[o + 13]),
                  peer_sb + BAR_OFF + MB_X2 * 8);
      }
      STAMP(23);
      mbar_wait_cluster(mb + MB_X2 * 8, 0);
      STAMP(24);
#pragma unroll
      for (int j = 0; j < 4; j++) {
        const int o = 16 * (j >> 1) + 2 * (j & 1);
        const uint4 v = lds128(sb + 3 * 8192 + j * 4096 + tid * 16);
        out[oo + 4 * (j >> 1) + 512 * (j & 1)] = make_uint4(pk(acc[o] + blo(v.x), acc[o + 1] + bhi(v.x)), pk(acc[o + 4] + blo(v.y), acc[o + 5] + bhi(v.y)),
                                                            pk(acc[o + 8] + blo(v.z), acc[o + 9] + bhi(v.z)), pk(acc[o + 12] + blo(v.w), acc[o + 13] + bhi(v.w)));
      }
      STAMP(12);
    }
  }
}

typedef CUresult (*EncodeFn)(CUtensorMap*, CUtensorMapDataType, cuuint32_t, void*, const cuuint64_t*, const cuuint64_t*, const cuuint32_t*,
                             const cuuint32_t*, CUtensorMapInterleave, CUtensorMapSwizzle, CUtensorMapL2promotion, CUtensorMapFloatOOBfill);

extern "C" void kernel_launch(void* const* d_in, const int* in_sizes, int n_in, void* d_out, int out_size) {
  static EncodeFn enc = nullptr;
  static void* scr = nullptr;
  if (!enc) {
    void* fn = nullptr; cudaDriverEntryPointQueryResult st;
    cudaGetDriverEntryPoint("cuTensorMapEncodeTiled", &fn, cudaEnableDefault, &st);
    enc = (EncodeFn)fn;
    cudaGetSymbolAddress(&scr, g_scr);
    cudaFuncSetAttribute(fused_kernel, cudaFuncAttributeMaxDynamicSharedMemorySize, SMEM_BYTES);
  }
  CUtensorMap tm, tm1;
  {
    cuuint64_t dims[3] = {(cuuint64_t)F_, 8, 256}, strides[2] = {(cuuint64_t)256 * F_ * 2, F_ * 2};
    cuuint32_t box[3] = {88, 8, 4}, es[3] = {1, 1, 1};
    enc(&tm1, CU_TENSOR_MAP_DATA_TYPE_BFLOAT16, 3, d_in[4], dims, strides, box, es, CU_TENSOR_MAP_INTERLEAVE_NONE, CU_TENSOR_MAP_SWIZZLE_NONE,
        W1_PROMO, CU_TENSOR_MAP_FLOAT_OOB_FILL_NONE);
  }
  {
    cuuint64_t dims[3] = {64, (cuuint64_t)F_, S_ / 64}, strides[2] = {S_ * 2, 128};
    cuuint32_t box[3] = {64, 32, 2}, es[3] = {1, 1, 1};
    enc(&tm, CU_TENSOR_MAP_DATA_TYPE_BFLOAT16, 3, d_in[6], dims, strides, box, es, CU_TENSOR_MAP_INTERLEAVE_NONE, CU_TENSOR_MAP_SWIZZLE_128B,
        CU_TENSOR_MAP_L2_PROMOTION_L2_256B, CU_TENSOR_MAP_FLOAT_OOB_FILL_NONE);
  }
  fused_kernel<<<NCTA, 384, SMEM_BYTES, cudaStreamPerThread>>>((const uint2*)d_in[0], (Scratch*)scr, (const unsigned short*)d_in[1], (const unsigned short*)d_in[2],
                                          (const uint32_t*)d_in[5], (const unsigned short*)d_in[7], (uint4*)d_out, (const char*)d_in[6], tm1, tm);
}
```

```cpp
#include <cuda_runtime.h>
#include <cuda.h>
#include <cuda_bf16.h>
#include <stdint.h>
#define W1_LATE 1
#define W1_PROMO CU_TENSOR_MAP_L2_PROMOTION_NONE
#define W2_NUM 1
#define W2_DEN 1
#define PF_W1 0
#define W1_DEPTH 1
#define W1_WARPS 4
#define W2_PRE 12
#define W2_PACE 1
#define FILT_LATE 0
#define W1_END 32
#define TLB_WARM 0
template<int TA, int TB, uint32_t HA, uint32_t HB> __device__ __forceinline__ void wgmma_n88_ss(float (&d)[44], uint32_t da, uint32_t db, int sd) {
  asm volatile("{\n.reg .pred p;\n.reg .b64 da, db;\nsetp.ne.b32 p, %46, 0;\nmov.b64 da, {%44, %49};\nmov.b64 db, {%45, %50};\n"
    "wgmma.mma_async.sync.aligned.m64n88k16.f32.bf16.bf16 {%0, %1, %2, %3, %4, %5, %6, %7, %8, %9, %10, %11, %12, %13, %14, %15, %16, %17, %18, %19, %20, %21, %22, %23, %24, %25, %26, %27, %28, %29, %30, %31, %32, %33, %34, %35, %36, %37, %38, %39, %40, %41, %42, %43}, da, db, p, 1, 1, %47, %48;\n}\n"
    : "+f"(d[0]), "+f"(d[1]), "+f"(d[2]), "+f"(d[3]), "+f"(d[4]), "+f"(d[5]), "+f"(d[6]), "+f"(d[7]), "+f"(d[8]), "+f"(d[9]), "+f"(d[10]), "+f"(d[11]), "+f"(d[12]), "+f"(d[13]), "+f"(d[14]), "+f"(d[15]), "+f"(d[16]), "+f"(d[17]), "+f"(d[18]), "+f"(d[19]), "+f"(d[20]), "+f"(d[21]), "+f"(d[22]), "+f"(d[23]), "+f"(d[24]), "+f"(d[25]), "+f"(d[26]), "+f"(d[27]), "+f"(d[28]), "+f"(d[29]), "+f"(d[30]), "+f"(d[31]), "+f"(d[32]), "+f"(d[33]), "+f"(d[34]), "+f"(d[35]), "+f"(d[36]), "+f"(d[37]), "+f"(d[38]), "+f"(d[39]), "+f"(d[40]), "+f"(d[41]), "+f"(d[42]), "+f"(d[43]) : "r"(da), "r"(db), "r"(sd), "n"(TA), "n"(TB), "n"(HA), "n"(HB));
}
template<int TA, int TB, uint32_t HA, uint32_t HB> __device__ __forceinline__ void wgmma_n128_ss(float (&d)[64], uint32_t da, uint32_t db, int sd) {
  asm volatile("{\n.reg .pred p;\n.reg .b64 da, db;\nsetp.ne.b32 p, %66, 0;\nmov.b64 da, {%64, %69};\nmov.b64 db, {%65, %70};\n"
    "wgmma.mma_async.sync.aligned.m64n128k16.f32.bf16.bf16 {%0, %1, %2, %3, %4, %5, %6, %7, %8, %9, %10, %11, %12, %13, %14, %15, %16, %17, %18, %19, %20, %21, %22, %23, %24, %25, %26, %27, %28, %29, %30, %31, %32, %33, %34, %35, %36, %37, %38, %39, %40, %41, %42, %43, %44, %45, %46, %47, %48, %49, %50, %51, %52, %53, %54, %55, %56, %57, %58, %59, %60, %61, %62, %63}, da, db, p, 1, 1, %67, %68;\n}\n"
    : "+f"(d[0]), "+f"(d[1]), "+f"(d[2]), "+f"(d[3]), "+f"(d[4]), "+f"(d[5]), "+f"(d[6]), "+f"(d[7]), "+f"(d[8]), "+f"(d[9]), "+f"(d[10]), "+f"(d[11]), "+f"(d[12]), "+f"(d[13]), "+f"(d[14]), "+f"(d[15]), "+f"(d[16]), "+f"(d[17]), "+f"(d[18]), "+f"(d[19]), "+f"(d[20]), "+f"(d[21]), "+f"(d[22]), "+f"(d[23]), "+f"(d[24]), "+f"(d[25]), "+f"(d[26]), "+f"(d[27]), "+f"(d[28]), "+f"(d[29]), "+f"(d[30]), "+f"(d[31]), "+f"(d[32]), "+f"(d[33]), "+f"(d[34]), "+f"(d[35]), "+f"(d[36]), "+f"(d[37]), "+f"(d[38]), "+f"(d[39]), "+f"(d[40]), "+f"(d[41]), "+f"(d[42]), "+f"(d[43]), "+f"(d[44]), "+f"(d[45]), "+f"(d[46]), "+f"(d[47]), "+f"(d[48]), "+f"(d[49]), "+f"(d[50]), "+f"(d[51]), "+f"(d[52]), "+f"(d[53]), "+f"(d[54]), "+f"(d[55]), "+f"(d[56]), "+f"(d[57]), "+f"(d[58]), "+f"(d[59]), "+f"(d[60]), "+f"(d[61]), "+f"(d[62]), "+f"(d[63]) : "r"(da), "r"(db), "r"(sd), "n"(TA), "n"(TB), "n"(HA), "n"(HB));
}

constexpr int S_ = 2048, F_ = 1376, DF = 257;
constexpr int NCTA = 128;
constexpr int W_BYTES = 180224;
constexpr int RING_OFF = W_BYTES;
constexpr int NST = 6;
constexpr int BAR_OFF = RING_OFF + NST * 8192;
constexpr int SMEM_BYTES = BAR_OFF + 2048;
constexpr int FILT_OFF = RING_OFF;
constexpr int XCH_OFF = RING_OFF + 16384;
constexpr int TAB_OFF = XCH_OFF + 20992;
constexpr int ZROW = 328;
constexpr int MB_FULL = 0, MB_W2 = 54, MB_W1T = 76, MB_X1 = 108, MB_X2 = 109, MB_X1DONE = 110, MB_P3DONE = 111, MB_FILT = 112, MB_W1 = 113,
              MB_EMPTY = 114, MB_PEER1 = 168, MB_PEER2 = 169, MB_X = 171, MB_N = 179;
constexpr int BASE_OFF = BAR_OFF + MB_N * 8;
#define W2_START 24

struct Scratch {
  uint4 T1[NCTA * 1024], T2[NCTA * 1024], Hn[4 * 128 * 256], U[4 * 172 * 128];
  float2 st[S_];
  unsigned cnt[8 * 4 * 64];
};
__device__ __align__(1024) Scratch g_scr;
#define g_T1 (scr->T1)
#define g_T2 (scr->T2)
#define g_Hn (scr->Hn)
#define g_U (scr->U)
#define g_st (scr->st)
#define g_cnt (scr->cnt)
#define DUMP()
#define STAMP(i)

__device__ __forceinline__ void mbar_init(uint32_t b, int c) { asm volatile("mbarrier.init.shared::cta.b64 [%0], %1;" :: "r"(b), "r"(c) : "memory"); }
__device__ __forceinline__ void mbar_expect(uint32_t b, int bytes) { asm volatile("mbarrier.arrive.expect_tx.shared::cta.b64 _, [%0], %1;" :: "r"(b), "r"(bytes) : "memory"); }
__device__ __forceinline__ void mbar_arrive(uint32_t b) { asm volatile("mbarrier.arrive.shared::cta.b64 _, [%0];" :: "r"(b) : "memory"); }
__device__ __forceinline__ void mbar_arrive_cluster(uint32_t remote) { asm volatile("mbarrier.arrive.relaxed.cluster.shared::cluster.b64 _, [%0];" :: "r"(remote) : "memory"); }
__device__ __forceinline__ uint32_t mapa(uint32_t a, uint32_t cta) { uint32_t r; asm("mapa.shared::cluster.u32 %0, %1, %2;" : "=r"(r) : "r"(a), "r"(cta)); return r; }
__device__ __forceinline__ void mbar_wait(uint32_t b, int ph) {
  asm volatile("{\n.reg .pred p;\n.reg .u32 n;\nmov.u32 n, 0;\nL_W:\n"
               "mbarrier.try_wait.parity.shared::cta.b64 p, [%0], %1;\n@p bra L_D;\n"
               "add.u32 n, n, 1;\nsetp.lt.u32 p, n, 4000000;\n@p bra L_W;\ntrap;\nL_D:\n}" :: "r"(b), "r"(ph) : "memory");
}
__device__ __forceinline__ void mbar_wait_cluster(uint32_t b, int ph) {
  asm volatile("{\n.reg .pred p;\n.reg .u32 n;\nmov.u32 n, 0;\nL_W:\n"
               "mbarrier.try_wait.parity.acquire.cluster.shared::cta.b64 p, [%0], %1;\n@p bra L_D;\n"
               "add.u32 n, n, 1;\nsetp.lt.u32 p, n, 4000000;\n@p bra L_W;\ntrap;\nL_D:\n}" :: "r"(b), "r"(ph) : "memory");
}
__device__ __forceinline__ void bulk_ld(uint32_t dst, const void* src, int bytes, uint32_t bar) {
  asm volatile("cp.async.bulk.shared::cluster.global.mbarrier::complete_tx::bytes [%0], [%1], %2, [%3];" :: "r"(dst), "l"(src), "r"(bytes), "r"(bar) : "memory");
}
__device__ __forceinline__ void tma3d(uint32_t dst, const CUtensorMap* tm, int c0, int c1, int c2, uint32_t bar) {
  asm volatile("cp.async.bulk.tensor.3d.shared::cluster.global.mbarrier::complete_tx::bytes [%0], [%1, {%3, %4, %5}], [%2];"
               :: "r"(dst), "l"(tm), "r"(bar), "r"(c0), "r"(c1), "r"(c2) : "memory");
}
__device__ __forceinline__ bool elect() { uint32_t p; asm volatile("{.reg .pred p; elect.sync _|p, 0xffffffff; selp.b32 %0, 1, 0, p;}" : "=r"(p)); return p; }
__device__ __forceinline__ uint32_t desc_lo(uint32_t addr, uint32_t lbo) { return ((addr & 0x3FFFF) >> 4) | ((lbo >> 4) << 16); }
constexpr uint32_t HI_SW128 = (1024 >> 4) | (1u << 30), HI_NOSW = 128 >> 4;
__device__ __forceinline__ uint32_t pk(float lo, float hi) { uint32_t r; asm("cvt.rn.bf16x2.f32 %0, %1, %2;" : "=r"(r) : "f"(hi), "f"(lo)); return r; }
__device__ __forceinline__ float blo(uint32_t w) { return __uint_as_float(w << 16); }
__device__ __forceinline__ float bhi(uint32_t w) { return __uint_as_float(w & 0xffff0000u); }
__device__ __forceinline__ void mmac(float (&d)[4], const float (&c)[4], const uint32_t (&a)[4], uint32_t b0, uint32_t b1) {
  asm("mma.sync.aligned.m16n8k16.row.col.f32.bf16.bf16.f32 {%0,%1,%2,%3}, {%4,%5,%6,%7}, {%8,%9}, {%10,%11,%12,%13};"
      : "=f"(d[0]), "=f"(d[1]), "=f"(d[2]), "=f"(d[3]) : "r"(a[0]), "r"(a[1]), "r"(a[2]), "r"(a[3]), "r"(b0), "r"(b1), "f"(c[0]), "f"(c[1]), "f"(c[2]), "f"(c[3]));
}
__device__ __forceinline__ void mma0(float (&d)[4], const uint32_t (&a)[4], uint32_t b0, uint32_t b1) { const float z[4] = {0.f, 0.f, 0.f, 0.f}; mmac(d, z, a, b0, b1); }
__device__ __forceinline__ uint32_t pin(uint32_t v) { asm volatile("shfl.sync.bfly.b32 %0, %0, 0, 31, 0xffffffff;" : "+r"(v)); return v; }
__device__ __forceinline__ float pinf(float v) { return __uint_as_float(pin(__float_as_uint(v))); }
__device__ __forceinline__ void wbar() { asm volatile("bar.sync 1, 256;" ::: "memory"); }
__device__ __forceinline__ void sts32(uint32_t a, uint32_t v) { asm volatile("st.shared.b32 [%0], %1;" :: "r"(a), "r"(v) : "memory"); }
__device__ __forceinline__ void sts64(uint32_t a, uint32_t x, uint32_t y) { asm volatile("st.shared.v2.b32 [%0], {%1,%2};" :: "r"(a), "r"(x), "r"(y) : "memory"); }
__device__ __forceinline__ void sts128(uint32_t a, uint4 v) { asm volatile("st.shared.v4.b32 [%0], {%1,%2,%3,%4};" :: "r"(a), "r"(v.x), "r"(v.y), "r"(v.z), "r"(v.w) : "memory"); }
__device__ __forceinline__ uint32_t lds32(uint32_t a) { uint32_t v; asm volatile("ld.shared.b32 %0, [%1];" : "=r"(v) : "r"(a) : "memory"); return v; }
__device__ __forceinline__ uint2 lds64(uint32_t a) { uint2 v; asm volatile("ld.shared.v2.b32 {%0,%1}, [%2];" : "=r"(v.x), "=r"(v.y) : "r"(a) : "memory"); return v; }
__device__ __forceinline__ uint4 lds128(uint32_t a) { uint4 v; asm volatile("ld.shared.v4.b32 {%0,%1,%2,%3}, [%4];" : "=r"(v.x), "=r"(v.y), "=r"(v.z), "=r"(v.w) : "r"(a) : "memory"); return v; }
__device__ __forceinline__ void lds4(uint32_t (&d)[4], uint32_t a) { const uint4 v = lds128(a); d[0] = v.x; d[1] = v.y; d[2] = v.z; d[3] = v.w; }
__device__ __forceinline__ uint4 ldcg128(const void* p) { uint4 v; asm volatile("ld.global.cg.v4.b32 {%0,%1,%2,%3}, [%4];" : "=r"(v.x), "=r"(v.y), "=r"(v.z), "=r"(v.w) : "l"(p) : "memory"); return v; }
__device__ __forceinline__ void st_async4(uint32_t a, uint32_t x, uint32_t y, uint32_t z, uint32_t w, uint32_t bar) {
  asm volatile("st.async.weak.shared::cluster.mbarrier::complete_tx::bytes.v4.b32 [%0], {%1,%2,%3,%4}, [%5];" :: "r"(a), "r"(x), "r"(y), "r"(z), "r"(w), "r"(bar) : "memory");
}
constexpr int NREP = 4;
__device__ __forceinline__ void cnt_arrive(Scratch* scr, int i, int lane) {
  if (lane < NREP) asm volatile("red.relaxed.gpu.global.add.u32 [%0], 1;" :: "l"(&g_cnt[(i * NREP + lane) * 64]) : "memory");
}
template <bool ACQ> __device__ __forceinline__ void cnt_wait(Scratch* scr, int i, int rep, unsigned target) {
  unsigned v; int n = 0;
  do {
    if (ACQ) asm volatile("ld.acquire.gpu.global.u32 %0, [%1];" : "=r"(v) : "l"(&g_cnt[(i * NREP + rep) * 64]) : "memory");
    else asm volatile("ld.relaxed.gpu.global.u32 %0, [%1];" : "=r"(v) : "l"(&g_cnt[(i * NREP + rep) * 64]) : "memory");
    if (++n > 2000000) __trap(); } while ((int)(v - target) < 0);
}
__device__ __forceinline__ void fence_gpu() { asm volatile("fence.acq_rel.gpu;" ::: "memory"); }
__device__ __forceinline__ void tag_check(uint4& v, const uint4* p, uint32_t tag) {
  int n = 0;
  while ((v.x ^ tag) & 1) {
    asm volatile("ld.relaxed.gpu.global.v4.b32 {%0,%1,%2,%3}, [%4];" : "=r"(v.x), "=r"(v.y), "=r"(v.z), "=r"(v.w) : "l"(p) : "memory");
    if (++n > 2000000) __trap();
  }
}
template <int N> __device__ __forceinline__ void cs(int n, float& c, float& s) {
  n = ((n + N / 2) & (N - 1)) - N / 2;
  float a = (float)n * (6.283185307179586f / N);
  c = __cosf(a); s = __sinf(a);
}
constexpr float ALPHA = 1.13288f;
struct FftC { uint32_t a[4][4], b[8][2]; float tc[2][4], ts[2][4]; };
constexpr uint32_t NEG = 0x80008000u;

__device__ __forceinline__ void fft_s1(const FftC& K, const uint32_t (&in)[4][2], float (&cr)[2][4], float (&ci)[2][4]) {
#pragma unroll
  for (int h = 0; h < 2; h++) { mma0(cr[h], K.a[0], in[0][h], in[1][h]); mma0(ci[h], K.a[1], in[0][h], in[1][h]); }
#pragma unroll
  for (int h = 0; h < 2; h++) { mmac(cr[h], cr[h], K.a[2], in[2][h], in[3][h]); mmac(ci[h], ci[h], K.a[3], in[2][h], in[3][h]); }
}
__device__ __forceinline__ void fft_s2(const FftC& K, const float (&cr)[2][4], const float (&ci)[2][4], float (&o)[4][4]) {
  uint32_t a[2][4];
#pragma unroll
  for (int h = 0; h < 2; h++)
#pragma unroll
    for (int i = 0; i < 4; i++) {
      float xr = cr[i & 1][2 * h + (i >> 1)], xi = ci[i & 1][2 * h + (i >> 1)];
      a[i >> 1][2 * (i & 1) + h] = pk(xr * K.tc[h][i] + xi * K.ts[h][i], xi * K.tc[h][i] - xr * K.ts[h][i]);
    }
#pragma unroll
  for (int j = 0; j < 4; j++) mma0(o[j], a[0], K.b[j][0], K.b[j][1]);
#pragma unroll
  for (int j = 0; j < 4; j++) mmac(o[j], o[j], a[1], K.b[4 + j][0], K.b[4 + j][1]);
}
__device__ __forceinline__ int zphys(int k) { return k + 8 * (k >> 5); }
__device__ __forceinline__ float gelu(float u) {
  float z = u * (0.7978845608028654f + 0.035677408136300125f * u * u), th;
  asm("tanh.approx.f32 %0, %1;" : "=f"(th) : "f"(z));
  float hu = 0.5f * u;
  return fmaf(hu, th, hu);
}

extern "C" __global__ void __cluster_dims__(2, 1, 1) __launch_bounds__(384, 1)
fused_kernel(const uint2* __restrict__ x, Scratch* scr, const unsigned short* __restrict__ wr, const unsigned short* __restrict__ wi,
             const uint32_t* __restrict__ b1, const unsigned short* __restrict__ b2, uint4* __restrict__ out, const char* __restrict__ w2,
             const __grid_constant__ CUtensorMap tmW1, const __grid_constant__ CUtensorMap tmW2) {
  extern __shared__ __align__(1024) char smem[];
  const uint32_t sb = (uint32_t)__cvta_generic_to_shared(smem);
  const uint32_t mb = sb + BAR_OFF;
  const int b = blockIdx.x, rank = b & 1, pr = b >> 1, dt = pr & 3, ot = pr >> 2;
  const int warp = __shfl_sync(0xffffffffu, threadIdx.x >> 5, 0), lane = threadIdx.x & 31;
  const int g = lane >> 2, t = lane & 3;

  if (warp >= 8) {
    const int pw = warp - 8;
    if (pw < 3 && elect()) {
#pragma unroll
      for (int i = 0; i < 57; i++) mbar_init(mb + (pw * 57 + i) * 8, pw == 2 ? 2 : 1);
      if (pw == 1) { mbar_expect(mb + MB_X1 * 8, 12288); mbar_expect(mb + MB_X2 * 8, 16384); }
      asm volatile("fence.mbarrier_init.release.cluster;" ::: "memory");
    }
    __syncwarp();
    STAMP(0);
    asm volatile("bar.sync 2, 128;" ::: "memory");
    asm volatile("barrier.cluster.arrive.relaxed.aligned;" ::: "memory");
    auto w1_issue = [&](int i) {
      if (elect()) { mbar_expect(mb + (MB_W1T + i) * 8, 5632); tma3d(sb + i * 5632, &tmW1, 88 * ot, 0, 128 * rank + 4 * i, mb + (MB_W1T + i) * 8); }
      __syncwarp();
    };
    if (!W1_LATE && pw < W1_WARPS) for (int i = 0; i < W1_DEPTH; i++) w1_issue(pw + W1_WARPS * i);
    {
      const int j1 = b >> 4, q = b & 15, slot = lane & 15, h = lane >> 4;
      const bool hi = q >= 8;
      const int k = 16 * (q & 7) + slot, col = hi ? 256 - k : (k == 0 ? 128 : k);
      const int j0 = j1 + 8 * h + 512 * pw, o0 = (hi ? 2048 - 31 * 16 - j0 : j0) * DF + col, o31 = hi && j0 == 0 ? o0 - 2048 * DF : o0;
      uint32_t vr[32], vi[32];
      if (FILT_LATE) { asm volatile("bar.sync 3, 160;" ::: "memory"); asm volatile("" : "+l"(wr), "+l"(wi)); }
#pragma unroll
      for (int n = 0; n < 32; n++) { vr[n] = __ldg(wr + (n == 31 ? o31 : o0) + n * 16 * DF); vi[n] = __ldg(wi + (n == 31 ? o31 : o0) + n * 16 * DF); }
      const uint32_t f0 = sb + FILT_OFF + pw * 4096 + (hi ? 31 * 128 : 0) + h * 8 + (slot & 1) * 4, sw = ((slot >> 1) ^ (hi ? 7 : 0)) << 4;
      const int st = hi ? -128 : 128;
#pragma unroll
      for (int n = 0; n < 32; n++)
        sts32(f0 + n * st + (sw ^ ((((n >> 3) & 3) * 2 + (n & 1)) << 4)), __byte_perm(vr[n], vi[n], 0x5410) ^ (hi ? 0x80000000u : 0u));
      asm volatile("bar.sync 2, 128;" ::: "memory");
      if (threadIdx.x == 352) mbar_arrive(mb + MB_FILT * 8);
    }
    __syncwarp();
    STAMP(1);
    {
      if (W1_LATE && pw < W1_WARPS) for (int i = 0; i < W1_DEPTH; i++) w1_issue(pw + W1_WARPS * i);
      const uint32_t rd = ((lane & 7) * 11 + (lane >> 3)) * 16, wr = lane * 16;
#pragma unroll 1
      for (int box = pw < W1_WARPS ? pw : 32; box < W1_END; box += W1_WARPS) {
        mbar_wait(mb + (MB_W1T + box) * 8, 0);
        if (box + W1_WARPS * W1_DEPTH < 32) w1_issue(box + W1_WARPS * W1_DEPTH);
        const uint32_t p = sb + box * 5632;
        uint4 v[4][3];
#pragma unroll
        for (int n = 0; n < 4; n++) { v[n][0] = lds128(p + n * 1408 + rd); v[n][1] = lds128(p + n * 1408 + rd + 64); if (lane < 24) v[n][2] = lds128(p + n * 1408 + rd + 128); }
        __syncwarp();
#pragma unroll
        for (int n = 0; n < 4; n++) { sts128(p + n * 1408 + wr, v[n][0]); sts128(p + n * 1408 + wr + 512, v[n][1]); if (lane < 24) sts128(p + n * 1408 + wr + 1024, v[n][2]); }
      }
      if (lane == 0) asm volatile("cp.async.bulk.prefetch.L2.global [%0], %1;" :: "l"(w2 + (size_t)(b * 4 + pw) * 11008), "r"(11008) : "memory");
      asm volatile("fence.proxy.async.shared::cta;" ::: "memory");
      asm volatile("bar.sync 2, 128;" ::: "memory");
      if (threadIdx.x == 352) mbar_arrive(mb + MB_W1 * 8);
    }
    STAMP(2);
    asm volatile("barrier.cluster.wait.aligned;" ::: "memory");
    if (pw == 3) {
#pragma unroll 1
      for (int n = 0; n < 22; n++) {
        if (n < W2_PRE) mbar_wait(mb + (MB_EMPTY + min(31, max(((n + 4) * 16 + 10) / 11 - 1, W2_START + n * W2_NUM / W2_DEN))) * 8, 0);
        else { mbar_wait(mb + MB_X1DONE * 8, 0); if (W2_PACE) mbar_wait(mb + (MB_FULL + 32 - W2_PRE + n) * 8, 0); }
        if (elect()) { mbar_expect(mb + (MB_W2 + n) * 8, 8192); tma3d(sb + (n < 19 ? n + 3 : n - 19) * 8192, &tmW2, 0, 688 * rank + 32 * n, 2 * ot, mb + (MB_W2 + n) * 8); }
      }
    } else {
      int i = pw;
      uint32_t dst = sb + RING_OFF + pw * 8192;
      const uint32_t dsum = 2 * dst + 3 * 8192;
      const char* src = (const char*)g_Hn + ((size_t)dt * 128 + 64 * rank) * 4096;
#pragma unroll 1
      for (int gm = 0; gm < 2; gm++) {
        if (pw == 0) {
          mbar_wait(mb + (gm ? MB_X1DONE : MB_P3DONE) * 8, 0);
          STAMP(3 + 2 * gm);
          if (lane == 0) cnt_wait<true>(scr, gm ? 4 + dt : 2 + rank, ot & (NREP - 1), ((lds32(sb + BASE_OFF) >> 1) + 64) >> gm);
        }
        asm volatile("bar.sync 2, 96;" ::: "memory");
        STAMP(4 + 2 * gm);
        asm volatile("fence.proxy.async.global;" ::: "memory");
#pragma unroll 1
        for (; i < (gm ? 54 : 32); i += 3) {
          if (i >= NST) mbar_wait(mb + (MB_EMPTY - NST + i) * 8, 0);
          if (elect()) {
            const int bytes = i < 53 ? 8192 : 4096;
            mbar_expect(mb + (MB_FULL + i) * 8, bytes); bulk_ld(dst, src + i * 8192, bytes, mb + (MB_FULL + i) * 8);
          }
          dst = dsum - dst;
        }
        src = (const char*)g_U + ((size_t)dt * 172 + 86 * rank) * 2048 - 32 * 8192;
      }
      STAMP(7);
      DUMP();
    }
  } else {
    const int tid = threadIdx.x;
    uint32_t xw[2][4][2];
    const uint32_t zb = sb + XCH_OFF, zw = zb + warp * ZROW * 4;
    const int rep = ot & (NREP - 1);
    if (elect()) {
      const uint32_t xb = mb + (MB_X + warp) * 8;
      mbar_init(xb, 1);
      asm volatile("fence.proxy.async.shared::cta;" ::: "memory");
      mbar_expect(xb, 2064);
      bulk_ld(zw, x + (size_t)(256 * warp + 2 * b) * 128, 1024, xb);
      bulk_ld(zw + 8 * ZROW * 4, x + (size_t)(256 * warp + 2 * b + 1) * 128, 1024, xb);
      bulk_ld(zw + 1280, &g_cnt[(1 * NREP + rep) * 64], 16, xb);
    }
    __syncwarp();
    STAMP(0);
    asm volatile("barrier.cluster.arrive.relaxed.aligned;" ::: "memory");
    const uint32_t tab = sb + TAB_OFF + lane * 16;
    FftC K;
    {
      const int lg = pin(lane) >> 2, w3 = warp & 3, w1 = warp & 1, w2 = w3 >> 1;
      const bool lo4 = warp < 4;
      float c, s;
      cs<16>(lo4 ? (2 * lg + w1) * (t + 4 * w2) : (4 * t + w3) * (lg >> 1) + 4 * (lg & 1), c, s);
      const uint32_t P = pk(ALPHA * c, ALPHA * s), Q = pk(-ALPHA * s, ALPHA * c);
#pragma unroll
      for (int m = 0; m < 4; m++) {
        const int sel = lo4 ? (m & 1) | (m & 2 & (w1 << 1)) : w3 * m;
        sts32(tab + (lo4 ? m * 512 + w3 * 4 : (4 + 2 * w2 + (m >> 1)) * 512 + (2 * (m & 1) + w1) * 4), (sel & 1 ? Q : P) ^ (sel & 2 ? NEG : 0u));
      }
      cs<256>((2 * lg + (warp >> 2)) * (4 * t + w3), c, s);
      sts32(tab + (8 + (warp >> 2)) * 512 + w3 * 4, __float_as_uint(c * (1.f / (ALPHA * ALPHA))));
      sts32(tab + (10 + (warp >> 2)) * 512 + w3 * 4, __float_as_uint(s * (1.f / (ALPHA * ALPHA))));
      cs<2048>(256 * lg * (t + 4 * w2) + (lo4 ? lg : t + 4 * w2) * (2 * b + w1), c, s);
      const uint32_t e0 = pk(c, s), e1 = pk(-s, c), mk = lo4 ? 0x80000000u : NEG, at = tab + (lo4 ? 12 + 3 * w1 : 18 + 2 * w1) * 512 + w2 * 8;
      sts64(at, e0, e1);
      sts64(at + 512, e0 ^ mk, e1 ^ mk);
      if (lo4) sts64(at + 1024, e0 ^ 0x8000u, e1 ^ 0x8000u);
    }
    const int key = ((b >> 3) & 3) * 2 + (b & 1);
    float mean[2];
    uint32_t tag, base;
    {
      float vc[4], vs[4];
#pragma unroll
      for (int i = 0; i < 4; i++) { cs<512>(16 * warp + 8 * (i >> 1) + 2 * t + (i & 1) + 128, vc[i], vs[i]); vc[i] = pinf(vc[i]); vs[i] = pinf(vs[i]); }
      wbar();
#pragma unroll
      for (int m = 0; m < 4; m++) {
        lds4(K.a[m], tab + m * 512);
        const uint4 v = lds128(tab + (4 + m) * 512), w = lds128(tab + (8 + m) * 512);
        K.b[2 * m][0] = v.x; K.b[2 * m][1] = v.y; K.b[2 * m + 1][0] = v.z; K.b[2 * m + 1][1] = v.w;
        float* d = m < 2 ? K.tc[m] : K.ts[m - 2];
        d[0] = __uint_as_float(w.x); d[1] = __uint_as_float(w.y); d[2] = __uint_as_float(w.z); d[3] = __uint_as_float(w.w);
      }
      STAMP(13);
      mbar_wait(mb + (MB_X + warp) * 8, 0);
#pragma unroll
      for (int a = 0; a < 2; a++)
#pragma unroll
        for (int j = 0; j < 4; j++) { const uint2 v = lds64(zw + a * 8 * ZROW * 4 + j * 256 + (8 * t + g) * 8); xw[a][j][0] = v.x; xw[a][j][1] = v.y; }
      base = lds32(zw + 1280);
      __syncwarp();
      tag = (~base >> 7) & 1;
#pragma unroll
      for (int a = 0; a < 2; a++) {
        float cr[2][4], ci[2][4], o[4][4];
        if (a == 0) { if (xw[0][0][0] == 0x12345678u && xw[1][3][1] == 0x12345679u) STAMP(29); STAMP(14); }
        fft_s1(K, xw[a], cr, ci);
        if (FILT_LATE && a == 0 && warp == 0) asm volatile("bar.arrive 3, 160;" :: "f"(cr[0][0]) : "memory");
        float sm = ((cr[0][0] + cr[0][1]) + (cr[1][0] + cr[1][1])) + ((ci[0][0] + ci[0][1]) + (ci[1][0] + ci[1][1]));
        sm += __shfl_xor_sync(0xffffffffu, sm, 1); sm += __shfl_xor_sync(0xffffffffu, sm, 2);
        sm = g == 0 ? sm * (1.f / 32.f) : 0.f;
#pragma unroll
        for (int h = 0; h < 2; h++) { cr[h][0] -= sm; cr[h][1] -= sm; ci[h][0] -= sm; ci[h][1] -= sm; }
        mean[a] = __shfl_sync(0xffffffffu, sm, 0) * (1.f / (16.f * 1.1328125f));
        float q = 0.f, q2 = 0.f;
#pragma unroll
        for (int i = 0; i < 4; i++) { q = fmaf(cr[0][i], cr[0][i], q); q2 = fmaf(cr[1][i], cr[1][i], q2); q = fmaf(ci[0][i], ci[0][i], q); q2 = fmaf(ci[1][i], ci[1][i], q2); }
        q += q2;
#pragma unroll
        for (int m = 1; m < 32; m <<= 1) q += __shfl_xor_sync(0xffffffffu, q, m);
        float r = rsqrtf(q * (1.f / (512.f * 16.f * ALPHA * ALPHA)) + 1e-5f) * 4.76837158203125e-7f;
        fft_s2(K, cr, ci, o);
#pragma unroll
        for (int j = 0; j < 4; j++)
          sts64(zb + ((a * 8 + warp) * ZROW + zphys(16 * t + 64 * j) + 2 * g) * 4, pk(o[j][0] * r, o[j][1] * r), pk(o[j][2] * r, o[j][3] * r));
      }
      uint32_t a8[2][4], a8c[2][4], a8n[2][4];
#pragma unroll
      for (int a = 0; a < 2; a++) { lds4(a8[a], tab + (12 + 3 * a) * 512); lds4(a8c[a], tab + (13 + 3 * a) * 512); lds4(a8n[a], tab + (14 + 3 * a) * 512); }
      STAMP(15);
      wbar();
      uint4* tp = g_T1 + (size_t)(g * 16 + warp) * 1024 + b * 8;
#pragma unroll
      for (int nt = 0; nt < 2; nt++) {
        const int k = 16 * warp + 8 * nt + g, km = k == 0 ? 128 : 256 - k;
        uint32_t lo[4], hi[4];
#pragma unroll
        for (int a = 0; a < 2; a++) {
          const uint32_t rb = zb + (a * 8 + t) * ZROW * 4;
          float A[4], S[4], D[4];
          const uint32_t m0 = lds32(rb + zphys(km) * 4), m1 = lds32(rb + (4 * ZROW + zphys(km)) * 4);
          mma0(A, a8[a], lds32(rb + zphys(k) * 4), lds32(rb + (4 * ZROW + zphys(k)) * 4));
          mmac(S, A, a8c[a], m0, m1);
          mmac(D, A, a8n[a], m0, m1);
#pragma unroll
          for (int e = 0; e < 2; e++) {
            const float c = vc[2 * nt + e], s = vs[2 * nt + e];
            float lr = fmaf(D[2 + e], s, fmaf(D[e], c, S[e])), li = fmaf(-D[e], s, fmaf(D[2 + e], c, S[2 + e]));
            float hr = fmaf(2.f, S[e], -lr), hii = fmaf(2.f, S[2 + e], -li);
            if (nt == 0 && e == 0) {
              const bool sp = warp == 0 && t == 0;
              lr = sp ? S[0] - D[0] : lr; li = sp ? S[2] - D[2] : li;
              hr = sp ? 2.f * (A[0] - A[2]) : hr; hii = sp ? 2.f * (A[0] + A[2]) : hii;
            }
            lo[2 * a + e] = pk(lr, li); hi[2 * a + e] = pk(hr, hii);
          }
        }
        const int w = (t + 4 * nt) ^ key;
        tp[w] = make_uint4((lo[0] & ~1u) | tag, lo[1], lo[2], lo[3]);
        tp[8 * 1024 + w] = make_uint4((hi[0] & ~1u) | tag, hi[1], hi[2], hi[3]);
      }
      wbar();
      STAMP(1);
      if (warp == 0) cnt_arrive(scr, 0, lane);
    }
    {
      const uint32_t off = (8 * t + g) * 128 + ((warp ^ (2 * t + (g & 1))) << 4);
      asm volatile("barrier.cluster.wait.aligned;" ::: "memory");
      mbar_wait(mb + MB_FILT * 8, 0);
      if (tid == 0) cnt_wait<false>(scr, 0, rep, base + NCTA);
      wbar();
#pragma unroll
      for (int j = 0; j < 4; j++)
        asm volatile("cp.async.cg.shared.global [%0], [%1], 16;" :: "r"(zb + j * 4096 + tid * 16), "l"(g_T1 + (size_t)b * 1024 + j * 256 + tid) : "memory");
      STAMP(2);
      uint32_t in[2][4][2], fw[2][4][2];
#pragma unroll
      for (int j = 0; j < 4; j++) {
        uint4 v = lds128(sb + FILT_OFF + off + j * 4096);
        fw[0][j][0] = v.x; fw[1][j][0] = v.y; fw[0][j][1] = v.z; fw[1][j][1] = v.w;
      }
      asm volatile("cp.async.wait_all;" ::: "memory");
      wbar();
      STAMP(3);
      uint4 iv[4];
#pragma unroll
      for (int j = 0; j < 4; j++) iv[j] = lds128(zb + off + j * 4096);
      if (((iv[0].x ^ tag) | (iv[1].x ^ tag) | (iv[2].x ^ tag) | (iv[3].x ^ tag)) & 1) {
#pragma unroll
        for (int j = 0; j < 4; j++) tag_check(iv[j], g_T1 + (size_t)b * 1024 + j * 256 + (off >> 4), tag);
      }
      __syncwarp();
#pragma unroll
      for (int j = 0; j < 4; j++) { in[0][j][0] = iv[j].x; in[1][j][0] = iv[j].y; in[0][j][1] = iv[j].z; in[1][j][1] = iv[j].w; }
#pragma unroll
      for (int sg = 0; sg < 2; sg++) {
        float cr[2][4], ci[2][4], o[4][4];
        fft_s1(K, in[sg], cr, ci);
        fft_s2(K, cr, ci, o);
#pragma unroll
        for (int j = 0; j < 4; j++)
#pragma unroll
          for (int h = 0; h < 2; h++) {
            float fr = blo(fw[sg][j][h]), fi = bhi(fw[sg][j][h]), xr = o[j][2 * h], xi = o[j][2 * h + 1];
            in[sg][j][h] = pk(xr * fi + xi * fr, xr * fr - xi * fi);
          }
        fft_s1(K, in[sg], cr, ci);
        fft_s2(K, cr, ci, o);
#pragma unroll
        for (int j = 0; j < 4; j++) { in[sg][j][0] = pk(o[j][0], o[j][1]); in[sg][j][1] = pk(o[j][2], o[j][3]); }
      }
#pragma unroll
      for (int j = 0; j < 4; j++) sts128(zb + off + j * 4096, make_uint4((in[0][j][0] & ~1u) | tag, in[1][j][0], in[0][j][1], in[1][j][1]));
      STAMP(16);
      wbar();
#pragma unroll
      for (int j = 0; j < 4; j++) g_T2[(size_t)b * 1024 + j * 256 + tid] = lds128(zb + j * 4096 + tid * 16);
      wbar();
      STAMP(4);
      if (warp == 0) cnt_arrive(scr, 1, lane);
    }
    {
      uint32_t a8[2][4], a8n[2][4]; float vc[4], vs[4];
#pragma unroll
      for (int a = 0; a < 2; a++) { lds4(a8[a], tab + (18 + 2 * a) * 512); lds4(a8n[a], tab + (19 + 2 * a) * 512); }
#pragma unroll
      for (int i = 0; i < 4; i++) { cs<512>(16 * warp + 4 * t + i + 128, vc[i], vs[i]); vc[i] = pinf(vc[i]); vs[i] = pinf(vs[i]); }
      if (tid == 0) cnt_wait<false>(scr, 1, rep, base + NCTA);
      wbar();
      STAMP(5);
      const uint4* tp = g_T2 + (size_t)(t * 16 + warp) * 1024 + b * 8 + (g ^ key);
      uint4 L0 = ldcg128(tp), L1 = ldcg128(tp + 64 * 1024), H0 = ldcg128(tp + 8 * 1024), H1 = ldcg128(tp + 72 * 1024);
      if (((L0.x ^ tag) | (L1.x ^ tag) | (H0.x ^ tag) | (H1.x ^ tag)) & 1) {
        tag_check(L0, tp, tag); tag_check(L1, tp + 64 * 1024, tag); tag_check(H0, tp + 8 * 1024, tag); tag_check(H1, tp + 72 * 1024, tag);
      }
      __syncwarp();
      STAMP(17);
      const uint32_t l0[4] = {L0.x, L0.y, L0.z, L0.w}, l1[4] = {L1.x, L1.y, L1.z, L1.w}, h0[4] = {H0.x, H0.y, H0.z, H0.w}, h1[4] = {H1.x, H1.y, H1.z, H1.w};
#pragma unroll
      for (int a = 0; a < 2; a++) {
        uint32_t zf[4], zm[4];
#pragma unroll
        for (int sg = 0; sg < 2; sg++) {
          float A[4], S[4], D[4];
          mma0(A, a8[a], l0[2 * a + sg], l1[2 * a + sg]);
          mmac(S, A, a8[a], h0[2 * a + sg], h1[2 * a + sg]);
          mmac(D, A, a8n[a], h0[2 * a + sg], h1[2 * a + sg]);
#pragma unroll
          for (int e = 0; e < 2; e++) {
            const int i = 2 * e + sg;
            float fr = fmaf(-D[e], vs[i], fmaf(D[2 + e], vc[i], S[2 + e])), fi = fmaf(D[2 + e], vs[i], fmaf(D[e], vc[i], S[e]));
            float mr = fmaf(2.f, S[2 + e], -fr), mi = fmaf(-2.f, S[e], fi);
            if (i == 0) {
              const bool sp = warp == 0 && t == 0;
              fr = sp ? S[2] - A[2] : fr; fi = sp ? A[2] - S[2] : fi;
              mr = sp ? 2.f * A[2] : mr; mi = sp ? -2.f * A[0] : mi;
            }
            zf[i] = pk(fi, fr); zm[i] = pk(mi, mr);
          }
        }
        const uint32_t rb = zb + (a * 8 + g) * ZROW * 4;
        const int k0 = 16 * warp + 4 * t;
        sts128(rb + zphys(k0) * 4, make_uint4(zf[0], zf[1], zf[2], zf[3]));
        sts32(rb + zphys(k0 == 0 ? 128 : 256 - k0) * 4, zm[0]);
        sts32(rb + zphys(255 - k0) * 4, zm[1]);
        sts32(rb + zphys(254 - k0) * 4, zm[2]);
        sts32(rb + zphys(253 - k0) * 4, zm[3]);
      }
      STAMP(18);
      wbar();
      float o[2][4][4], s2[2];
#pragma unroll
      for (int a = 0; a < 2; a++) {
        uint32_t in[4][2];
#pragma unroll
        for (int j = 0; j < 4; j++) { uint2 v = lds64(zb + ((a * 8 + warp) * ZROW + zphys(16 * t + 64 * j) + 2 * g) * 4); in[j][0] = v.x; in[j][1] = v.y; }
        float cr[2][4], ci[2][4], s1 = 0.f;
        fft_s1(K, in, cr, ci);
        fft_s2(K, cr, ci, o[a]);
        s2[a] = 0.f;
#pragma unroll
        for (int j = 0; j < 4; j++)
#pragma unroll
          for (int h = 0; h < 2; h++) {
            uint32_t hw;
            asm("add.rn.bf16x2 %0, %1, %2;" : "=r"(hw) : "r"(xw[a][j][h]), "r"(pk(o[a][j][2 * h + 1], o[a][j][2 * h])));
            const float u0 = blo(hw) - mean[a], u1 = bhi(hw) - mean[a];
            o[a][j][2 * h] = u0; o[a][j][2 * h + 1] = u1;
            s1 = fmaf(u0, u0, s1); s2[a] = fmaf(u1, u1, s2[a]);
          }
        s2[a] += s1;
      }
      float sv = (lane < 16 ? s2[0] : s2[1]) + __shfl_xor_sync(0xffffffffu, lane < 16 ? s2[1] : s2[0], 16);
#pragma unroll
      for (int m = 1; m < 16; m <<= 1) sv += __shfl_xor_sync(0xffffffffu, sv, m);
      const float var = sv * (1.f / 512.f), r1 = rsqrtf(var + 1e-5f);
      const float rr = r1 * rsqrtf(var * r1 * r1 + 1e-5f);
      const float ro = __shfl_xor_sync(0xffffffffu, rr, 16);
      char* np = (char*)g_Hn + (size_t)b * 4096 + (t >> 1) * 2048 + warp * 128 + ((((t & 1) * 4 + (g >> 1)) ^ warp ^ (b >> 6)) << 4) + (g & 1) * 8;
#pragma unroll
      for (int a = 0; a < 2; a++) {
        const float r = (lane >> 4) == a ? rr : ro;
#pragma unroll
        for (int j = 0; j < 4; j++)
          *(uint2*)(np + a * 1024 + (size_t)j * 128 * 4096) = make_uint2(pk(o[a][j][0] * r, o[a][j][1] * r), pk(o[a][j][2] * r, o[a][j][3] * r));
      }
      if ((lane & 15) == 0) g_st[256 * warp + 2 * b + (lane >> 4)] = make_float2(__fdividef(1.f, rr), lane ? mean[1] : mean[0]);
      STAMP(19);
      asm volatile("fence.proxy.async.shared::cta;" ::: "memory");
      wbar();
      STAMP(6);
      if (warp == 0) { fence_gpu(); cnt_arrive(scr, 2 + (b >> 6), lane); STAMP(25); }
      if (tid == 32) { sts32(sb + BASE_OFF, base); mbar_arrive(mb + MB_P3DONE * 8); }
    }
    const int wg = warp >> 2;
    const uint32_t peer_sb = mapa(sb, rank ^ 1);
    {
      float acc[44];
#pragma unroll
      for (int j = 0; j < 11; j++) {
        const uint32_t bw = __ldg(b1 + min(11 * ot + j, 171) * 4 + t);
        acc[4 * j] = blo(bw); acc[4 * j + 1] = bhi(bw); acc[4 * j + 2] = 0.f; acc[4 * j + 3] = 0.f;
      }
      const uint32_t da0 = desc_lo(sb + RING_OFF + wg * 2048, 0);
      uint32_t da = da0, db = desc_lo(sb, 1408), bar = mb;
      mbar_wait(mb + MB_W1 * 8, 0);
#pragma unroll 1
      for (int i = 0; i < 32; i++) {
        mbar_wait(bar + MB_FULL * 8, 0);
        if (i == 0) STAMP(7);
        asm volatile("wgmma.fence.sync.aligned;" ::: "memory");
        wgmma_n88_ss<1, 1, HI_SW128, HI_NOSW>(acc, da, db, 1);
        wgmma_n88_ss<1, 1, HI_SW128, HI_NOSW>(acc, da + 256, db + 176, 1);
        asm volatile("wgmma.commit_group.sync.aligned;" ::: "memory");
        da = da == da0 + 5 * 512 ? da0 : da + 512; db += 352;
        asm volatile("wgmma.wait_group.sync.aligned 1;" ::: "memory");
        if ((tid & 127) == 0) { if (i > 0) mbar_arrive(bar + (MB_EMPTY - 1) * 8); if (i == 4) mbar_arrive_cluster(peer_sb + BAR_OFF + MB_PEER1 * 8); }
        bar += 8;
      }
      asm volatile("wgmma.wait_group.sync.aligned 0;" ::: "memory");
#pragma unroll
      for (int i = 0; i < 44; i++) asm volatile("" : "+f"(acc[i]) :: "memory");
      if ((tid & 127) == 0) mbar_arrive(mb + (MB_EMPTY + 31) * 8);
      STAMP(8);
      mbar_wait_cluster(mb + MB_PEER1 * 8, 0);
#pragma unroll
      for (int j = 0; j < 3; j++)
        st_async4(peer_sb + j * 4096 + tid * 16, pk(acc[16 * j + 2], acc[16 * j + 3]), pk(acc[16 * j + 6], acc[16 * j + 7]), pk(acc[16 * j + 10], acc[16 * j + 11]),
                  j < 2 ? pk(acc[16 * j + 14], acc[16 * j + 15]) : 0u, peer_sb + BAR_OFF + MB_X1 * 8);
      const int uo = (4 * (warp >> 1) + (g >> 1)) * 32 + (2 * (2 * (warp & 1) + rank) + (g & 1)) * 4 + t;
      uint32_t* const ub = (uint32_t*)g_U + ((size_t)dt * 172 + 11 * ot) * 512;
      uint32_t *upa = ub + (uo ^ (ot >= 8 ? 256 : 0)), *upb = ub + (uo ^ (ot >= 7 ? 256 : 0));
      STAMP(20);
      mbar_wait_cluster(mb + MB_X1 * 8, 0);
      STAMP(21);
      uint32_t pv[12];
#pragma unroll
      for (int j = 0; j < 3; j++) { const uint4 v = lds128(sb + j * 4096 + tid * 16); pv[4 * j] = v.x; pv[4 * j + 1] = v.y; pv[4 * j + 2] = v.z; pv[4 * j + 3] = v.w; }
#pragma unroll
      for (int j = 0; j < 11; j++) {
        uint32_t v = pk(gelu(acc[4 * j] + blo(pv[j])), gelu(acc[4 * j + 1] + bhi(pv[j])));
        if (j < 7 || ot < 15) (j < 9 ? upa : upb)[j * 512] = v;
      }
      STAMP(22);
      asm volatile("fence.proxy.async.shared::cta;" ::: "memory");
      wbar();
      STAMP(9);
      if (warp == 0) { fence_gpu(); cnt_arrive(scr, 4 + dt, lane); STAMP(26); }
      if (tid == 32) mbar_arrive(mb + MB_X1DONE * 8);
    }
    {
      const int srow = 128 * ot + 16 * warp + g, oo = srow * 64 + dt * 16 + 8 * rank + t;
      float acc[64];
      const uint32_t da0 = desc_lo(sb + wg * 4096, 0), db0 = desc_lo(sb + RING_OFF, 2048);
      uint32_t da = da0 + 3 * 512, db = db0 + (32 % NST) * 512, bar = mb;
#pragma unroll
      for (int u = 0; u < 2; u++) {
        const int sr = srow + 8 * u, s1 = ot >> 1;
        const float2 st = __ldcg(g_st + sr);
        const float off = st.y + __uint_as_float((uint32_t)__ldg(b2 + sr) << 16);
#pragma unroll
        for (int jj = 0; jj < 2; jj++) {
          const uint4 v = ldcg128(g_Hn + (dt * 128 + ((sr & 255) >> 1)) * 256 + rank * 128 + (sr & 1) * 64 + s1 * 8 + ((4 * jj + t) ^ s1 ^ (ot & 1)));
          const uint32_t w[4] = {v.x, v.y, v.z, v.w};
#pragma unroll
          for (int j = 0; j < 4; j++) { acc[16 * jj + 4 * j + 2 * u] = fmaf(blo(w[j]), st.x, off); acc[16 * jj + 4 * j + 2 * u + 1] = fmaf(bhi(w[j]), st.x, off); }
        }
      }
#pragma unroll
      for (int j = 32; j < 64; j++) acc[j] = 0.f;
#pragma unroll 1
      for (int i = 0; i < 21; i++) {
        mbar_wait(bar + MB_W2 * 8, 0);
        mbar_wait(bar + (MB_FULL + 32) * 8, 0);
        if (i == 0) STAMP(10);
        asm volatile("wgmma.fence.sync.aligned;" ::: "memory");
        wgmma_n128_ss<1, 0, HI_SW128, HI_NOSW>(acc, da, db, 1);
        wgmma_n128_ss<1, 0, HI_SW128, HI_NOSW>(acc, da + 128, db + 256, 1);
        asm volatile("wgmma.commit_group.sync.aligned;" ::: "memory");
        da = i == 18 ? da0 : da + 512; db = db == db0 + 5 * 512 ? db0 : db + 512;
        asm volatile("wgmma.wait_group.sync.aligned 1;" ::: "memory");
        if ((tid & 127) == 0) { if (i > 0) mbar_arrive(bar + (MB_EMPTY + 31) * 8); if (i == 4) mbar_arrive_cluster(peer_sb + BAR_OFF + MB_PEER2 * 8); }
        bar += 8;
      }
      mbar_wait(bar + MB_W2 * 8, 0);
      mbar_wait(bar + (MB_FULL + 32) * 8, 0);
      asm volatile("wgmma.fence.sync.aligned;" ::: "memory");
      wgmma_n128_ss<1, 0, HI_SW128, HI_NOSW>(acc, da, db, 1);
      asm volatile("wgmma.commit_group.sync.aligned;" ::: "memory");
      asm volatile("wgmma.wait_group.sync.aligned 0;" ::: "memory");
#pragma unroll
      for (int i = 0; i < 64; i++) asm volatile("" : "+f"(acc[i]) :: "memory");
      STAMP(11);
      mbar_wait_cluster(mb + MB_PEER2 * 8, 0);
#pragma unroll
      for (int j = 0; j < 4; j++) {
        const int o = 32 + 16 * (j >> 1) + 2 * (j & 1);
        st_async4(peer_sb + 3 * 8192 + j * 4096 + tid * 16, pk(acc[o], acc[o + 1]), pk(acc[o + 4], acc[o + 5]), pk(acc[o + 8], acc[o + 9]), pk(acc[o + 12], acc[o + 13]),
                  peer_sb + BAR_OFF + MB_X2 * 8);
      }
      STAMP(23);
      mbar_wait_cluster(mb + MB_X2 * 8, 0);
      STAMP(24);
#pragma unroll
      for (int j = 0; j < 4; j++) {
        const int o = 16 * (j >> 1) + 2 * (j & 1);
        const uint4 v = lds128(sb + 3 * 8192 + j * 4096 + tid * 16);
        out[oo + 4 * (j >> 1) + 512 * (j & 1)] = make_uint4(pk(acc[o] + blo(v.x), acc[o + 1] + bhi(v.x)), pk(acc[o + 4] + blo(v.y), acc[o + 5] + bhi(v.y)),
                                                            pk(acc[o + 8] + blo(v.z), acc[o + 9] + bhi(v.z)), pk(acc[o + 12] + blo(v.w), acc[o + 13] + bhi(v.w)));
      }
      STAMP(12);
      DUMP();
    }
  }
}

typedef CUresult (*EncodeFn)(CUtensorMap*, CUtensorMapDataType, cuuint32_t, void*, const cuuint64_t*, const cuuint64_t*, const cuuint32_t*,
                             const cuuint32_t*, CUtensorMapInterleave, CUtensorMapSwizzle, CUtensorMapL2promotion, CUtensorMapFloatOOBfill);

extern "C" void kernel_launch(void* const* d_in, const int* in_sizes, int n_in, void* d_out, int out_size) {
  static EncodeFn enc = nullptr;
  static void* scr = nullptr;
  if (!enc) {
    void* fn = nullptr; cudaDriverEntryPointQueryResult st;
    cudaGetDriverEntryPoint("cuTensorMapEncodeTiled", &fn, cudaEnableDefault, &st);
    enc = (EncodeFn)fn;
    cudaGetSymbolAddress(&scr, g_scr);
    cudaFuncSetAttribute(fused_kernel, cudaFuncAttributeMaxDynamicSharedMemorySize, SMEM_BYTES);
  }
  CUtensorMap tm, tm1;
  {
    cuuint64_t dims[3] = {(cuuint64_t)F_, 8, 256}, strides[2] = {(cuuint64_t)256 * F_ * 2, F_ * 2};
    cuuint32_t box[3] = {88, 8, 4}, es[3] = {1, 1, 1};
    enc(&tm1, CU_TENSOR_MAP_DATA_TYPE_BFLOAT16, 3, d_in[4], dims, strides, box, es, CU_TENSOR_MAP_INTERLEAVE_NONE, CU_TENSOR_MAP_SWIZZLE_NONE,
        W1_PROMO, CU_TENSOR_MAP_FLOAT_OOB_FILL_NONE);
  }
  {
    cuuint64_t dims[3] = {64, (cuuint64_t)F_, S_ / 64}, strides[2] = {S_ * 2, 128};
    cuuint32_t box[3] = {64, 32, 2}, es[3] = {1, 1, 1};
    enc(&tm, CU_TENSOR_MAP_DATA_TYPE_BFLOAT16, 3, d_in[6], dims, strides, box, es, CU_TENSOR_MAP_INTERLEAVE_NONE, CU_TENSOR_MAP_SWIZZLE_128B,
        CU_TENSOR_MAP_L2_PROMOTION_L2_256B, CU_TENSOR_MAP_FLOAT_OOB_FILL_NONE);
  }
  fused_kernel<<<NCTA, 384, SMEM_BYTES, cudaStreamPerThread>>>((const uint2*)d_in[0], (Scratch*)scr, (const unsigned short*)d_in[1], (const unsigned short*)d_in[2],
                                          (const uint32_t*)d_in[5], (const unsigned short*)d_in[7], (uint4*)d_out, (const char*)d_in[6], tm1, tm);
}
```

```cpp
#include <cuda_runtime.h>
#include <cuda.h>
#include <cuda_bf16.h>
#include <stdint.h>
template<int TA, int TB, uint32_t HA, uint32_t HB> __device__ __forceinline__ void wgmma_n88_ss(float (&d)[44], uint32_t da, uint32_t db, int sd) {
  asm volatile("{\n.reg .pred p;\n.reg .b64 da, db;\nsetp.ne.b32 p, %46, 0;\nmov.b64 da, {%44, %49};\nmov.b64 db, {%45, %50};\n"
    "wgmma.mma_async.sync.aligned.m64n88k16.f32.bf16.bf16 {%0, %1, %2, %3, %4, %5, %6, %7, %8, %9, %10, %11, %12, %13, %14, %15, %16, %17, %18, %19, %20, %21, %22, %23, %24, %25, %26, %27, %28, %29, %30, %31, %32, %33, %34, %35, %36, %37, %38, %39, %40, %41, %42, %43}, da, db, p, 1, 1, %47, %48;\n}\n"
    : "+f"(d[0]), "+f"(d[1]), "+f"(d[2]), "+f"(d[3]), "+f"(d[4]), "+f"(d[5]), "+f"(d[6]), "+f"(d[7]), "+f"(d[8]), "+f"(d[9]), "+f"(d[10]), "+f"(d[11]), "+f"(d[12]), "+f"(d[13]), "+f"(d[14]), "+f"(d[15]), "+f"(d[16]), "+f"(d[17]), "+f"(d[18]), "+f"(d[19]), "+f"(d[20]), "+f"(d[21]), "+f"(d[22]), "+f"(d[23]), "+f"(d[24]), "+f"(d[25]), "+f"(d[26]), "+f"(d[27]), "+f"(d[28]), "+f"(d[29]), "+f"(d[30]), "+f"(d[31]), "+f"(d[32]), "+f"(d[33]), "+f"(d[34]), "+f"(d[35]), "+f"(d[36]), "+f"(d[37]), "+f"(d[38]), "+f"(d[39]), "+f"(d[40]), "+f"(d[41]), "+f"(d[42]), "+f"(d[43]) : "r"(da), "r"(db), "r"(sd), "n"(TA), "n"(TB), "n"(HA), "n"(HB));
}
template<int TA, int TB, uint32_t HA, uint32_t HB> __device__ __forceinline__ void wgmma_n128_ss(float (&d)[64], uint32_t da, uint32_t db, int sd) {
  asm volatile("{\n.reg .pred p;\n.reg .b64 da, db;\nsetp.ne.b32 p, %66, 0;\nmov.b64 da, {%64, %69};\nmov.b64 db, {%65, %70};\n"
    "wgmma.mma_async.sync.aligned.m64n128k16.f32.bf16.bf16 {%0, %1, %2, %3, %4, %5, %6, %7, %8, %9, %10, %11, %12, %13, %14, %15, %16, %17, %18, %19, %20, %21, %22, %23, %24, %25, %26, %27, %28, %29, %30, %31, %32, %33, %34, %35, %36, %37, %38, %39, %40, %41, %42, %43, %44, %45, %46, %47, %48, %49, %50, %51, %52, %53, %54, %55, %56, %57, %58, %59, %60, %61, %62, %63}, da, db, p, 1, 1, %67, %68;\n}\n"
    : "+f"(d[0]), "+f"(d[1]), "+f"(d[2]), "+f"(d[3]), "+f"(d[4]), "+f"(d[5]), "+f"(d[6]), "+f"(d[7]), "+f"(d[8]), "+f"(d[9]), "+f"(d[10]), "+f"(d[11]), "+f"(d[12]), "+f"(d[13]), "+f"(d[14]), "+f"(d[15]), "+f"(d[16]), "+f"(d[17]), "+f"(d[18]), "+f"(d[19]), "+f"(d[20]), "+f"(d[21]), "+f"(d[22]), "+f"(d[23]), "+f"(d[24]), "+f"(d[25]), "+f"(d[26]), "+f"(d[27]), "+f"(d[28]), "+f"(d[29]), "+f"(d[30]), "+f"(d[31]), "+f"(d[32]), "+f"(d[33]), "+f"(d[34]), "+f"(d[35]), "+f"(d[36]), "+f"(d[37]), "+f"(d[38]), "+f"(d[39]), "+f"(d[40]), "+f"(d[41]), "+f"(d[42]), "+f"(d[43]), "+f"(d[44]), "+f"(d[45]), "+f"(d[46]), "+f"(d[47]), "+f"(d[48]), "+f"(d[49]), "+f"(d[50]), "+f"(d[51]), "+f"(d[52]), "+f"(d[53]), "+f"(d[54]), "+f"(d[55]), "+f"(d[56]), "+f"(d[57]), "+f"(d[58]), "+f"(d[59]), "+f"(d[60]), "+f"(d[61]), "+f"(d[62]), "+f"(d[63]) : "r"(da), "r"(db), "r"(sd), "n"(TA), "n"(TB), "n"(HA), "n"(HB));
}

constexpr int S_ = 2048, F_ = 1376, DF = 257;
constexpr int NCTA = 128;
constexpr int W_BYTES = 180224;
constexpr int RING_OFF = W_BYTES;
constexpr int NST = 6;
constexpr int BAR_OFF = RING_OFF + NST * 8192;
constexpr int SMEM_BYTES = BAR_OFF + 2048;
constexpr int FILT_OFF = RING_OFF;
constexpr int XCH_OFF = RING_OFF + 16384;
constexpr int TAB_OFF = XCH_OFF + 20992;
constexpr int RAW_OFF = W_BYTES - 49152;
constexpr int ZROW = 328;
constexpr int MB_FULL = 0, MB_W2 = 54, MB_W1T = 76, MB_X1DONE = 110, MB_P3DONE = 111, MB_FILT = 112, MB_W1 = 113,
              MB_EMPTY = 114, MB_PEER1 = 168, MB_PEER2 = 169, MB_X = 171, MB_G = 179, MB_RAW = 183, MB_N = 184;
constexpr int BASE_OFF = BAR_OFF + MB_N * 8;
constexpr int W2_START = 24, W2_PRE = 10;

struct Scratch {
  uint4 T1[NCTA * 1024], Hn[4 * 128 * 256], U[4 * 172 * 128];
  float2 st[S_];
  unsigned cnt[8 * 4 * 64];
};
__device__ __align__(1024) Scratch g_scr;
#define g_T1 (scr->T1)
#define g_Hn (scr->Hn)
#define g_U (scr->U)
#define g_st (scr->st)
#define g_cnt (scr->cnt)
#define DUMP()
#define STAMP(i)

__device__ __forceinline__ void mbar_init(uint32_t b, int c) { asm volatile("mbarrier.init.shared::cta.b64 [%0], %1;" :: "r"(b), "r"(c) : "memory"); }
__device__ __forceinline__ void mbar_expect(uint32_t b, int bytes) { asm volatile("mbarrier.arrive.expect_tx.shared::cta.b64 _, [%0], %1;" :: "r"(b), "r"(bytes) : "memory"); }
__device__ __forceinline__ void mbar_arrive(uint32_t b) { asm volatile("mbarrier.arrive.shared::cta.b64 _, [%0];" :: "r"(b) : "memory"); }
__device__ __forceinline__ void mbar_arrive_cluster(uint32_t remote) { asm volatile("mbarrier.arrive.relaxed.cluster.shared::cluster.b64 _, [%0];" :: "r"(remote) : "memory"); }
__device__ __forceinline__ uint32_t mapa(uint32_t a, uint32_t cta) { uint32_t r; asm("mapa.shared::cluster.u32 %0, %1, %2;" : "=r"(r) : "r"(a), "r"(cta)); return r; }
__device__ __forceinline__ void mbar_wait(uint32_t b, int ph) {
  asm volatile("{\n.reg .pred p;\n.reg .u32 n;\nmov.u32 n, 0;\nL_W:\n"
               "mbarrier.try_wait.parity.shared::cta.b64 p, [%0], %1;\n@p bra L_D;\n"
               "add.u32 n, n, 1;\nsetp.lt.u32 p, n, 4000000;\n@p bra L_W;\ntrap;\nL_D:\n}" :: "r"(b), "r"(ph) : "memory");
}
__device__ __forceinline__ void mbar_wait_cluster(uint32_t b, int ph) {
  asm volatile("{\n.reg .pred p;\n.reg .u32 n;\nmov.u32 n, 0;\nL_W:\n"
               "mbarrier.try_wait.parity.acquire.cluster.shared::cta.b64 p, [%0], %1;\n@p bra L_D;\n"
               "add.u32 n, n, 1;\nsetp.lt.u32 p, n, 4000000;\n@p bra L_W;\ntrap;\nL_D:\n}" :: "r"(b), "r"(ph) : "memory");
}
__device__ __forceinline__ void bulk_ld(uint32_t dst, const void* src, int bytes, uint32_t bar) {
  asm volatile("cp.async.bulk.shared::cluster.global.mbarrier::complete_tx::bytes [%0], [%1], %2, [%3];" :: "r"(dst), "l"(src), "r"(bytes), "r"(bar) : "memory");
}
__device__ __forceinline__ void tma3d(uint32_t dst, const CUtensorMap* tm, int c0, int c1, int c2, uint32_t bar) {
  asm volatile("cp.async.bulk.tensor.3d.shared::cluster.global.mbarrier::complete_tx::bytes [%0], [%1, {%3, %4, %5}], [%2];"
               :: "r"(dst), "l"(tm), "r"(bar), "r"(c0), "r"(c1), "r"(c2) : "memory");
}
__device__ __forceinline__ bool elect() { uint32_t p; asm volatile("{.reg .pred p; elect.sync _|p, 0xffffffff; selp.b32 %0, 1, 0, p;}" : "=r"(p)); return p; }
__device__ __forceinline__ uint32_t desc_lo(uint32_t addr, uint32_t lbo) { return ((addr & 0x3FFFF) >> 4) | ((lbo >> 4) << 16); }
constexpr uint32_t HI_SW128 = (1024 >> 4) | (1u << 30), HI_NOSW = 128 >> 4;
__device__ __forceinline__ uint32_t pk(float lo, float hi) { uint32_t r; asm("cvt.rn.bf16x2.f32 %0, %1, %2;" : "=r"(r) : "f"(hi), "f"(lo)); return r; }
__device__ __forceinline__ float blo(uint32_t w) { return __uint_as_float(w << 16); }
__device__ __forceinline__ float bhi(uint32_t w) { return __uint_as_float(w & 0xffff0000u); }
__device__ __forceinline__ void mmac(float (&d)[4], const float (&c)[4], const uint32_t (&a)[4], uint32_t b0, uint32_t b1) {
  asm("mma.sync.aligned.m16n8k16.row.col.f32.bf16.bf16.f32 {%0,%1,%2,%3}, {%4,%5,%6,%7}, {%8,%9}, {%10,%11,%12,%13};"
      : "=f"(d[0]), "=f"(d[1]), "=f"(d[2]), "=f"(d[3]) : "r"(a[0]), "r"(a[1]), "r"(a[2]), "r"(a[3]), "r"(b0), "r"(b1), "f"(c[0]), "f"(c[1]), "f"(c[2]), "f"(c[3]));
}
__device__ __forceinline__ void mma0(float (&d)[4], const uint32_t (&a)[4], uint32_t b0, uint32_t b1) { const float z[4] = {0.f, 0.f, 0.f, 0.f}; mmac(d, z, a, b0, b1); }
__device__ __forceinline__ uint32_t pin(uint32_t v) { asm volatile("shfl.sync.bfly.b32 %0, %0, 0, 31, 0xffffffff;" : "+r"(v)); return v; }
template <class T> __device__ __forceinline__ T* pinp(T* p) { const uint64_t a = (uint64_t)p; return (T*)(((uint64_t)pin((uint32_t)(a >> 32)) << 32) | pin((uint32_t)a)); }
__device__ __forceinline__ float pinf(float v) { return __uint_as_float(pin(__float_as_uint(v))); }
__device__ __forceinline__ void wbar() { asm volatile("bar.sync 1, 256;" ::: "memory"); }
__device__ __forceinline__ void sts32(uint32_t a, uint32_t v) { asm volatile("st.shared.b32 [%0], %1;" :: "r"(a), "r"(v) : "memory"); }
__device__ __forceinline__ void sts64(uint32_t a, uint32_t x, uint32_t y) { asm volatile("st.shared.v2.b32 [%0], {%1,%2};" :: "r"(a), "r"(x), "r"(y) : "memory"); }
__device__ __forceinline__ void sts128(uint32_t a, uint4 v) { asm volatile("st.shared.v4.b32 [%0], {%1,%2,%3,%4};" :: "r"(a), "r"(v.x), "r"(v.y), "r"(v.z), "r"(v.w) : "memory"); }
__device__ __forceinline__ uint32_t lds32(uint32_t a) { uint32_t v; asm volatile("ld.shared.b32 %0, [%1];" : "=r"(v) : "r"(a) : "memory"); return v; }
__device__ __forceinline__ uint2 lds64(uint32_t a) { uint2 v; asm volatile("ld.shared.v2.b32 {%0,%1}, [%2];" : "=r"(v.x), "=r"(v.y) : "r"(a) : "memory"); return v; }
__device__ __forceinline__ uint4 lds128(uint32_t a) { uint4 v; asm volatile("ld.shared.v4.b32 {%0,%1,%2,%3}, [%4];" : "=r"(v.x), "=r"(v.y), "=r"(v.z), "=r"(v.w) : "r"(a) : "memory"); return v; }
__device__ __forceinline__ void lds4(uint32_t (&d)[4], uint32_t a) { const uint4 v = lds128(a); d[0] = v.x; d[1] = v.y; d[2] = v.z; d[3] = v.w; }
__device__ __forceinline__ uint4 ldcg128(const void* p) { uint4 v; asm volatile("ld.global.cg.v4.b32 {%0,%1,%2,%3}, [%4];" : "=r"(v.x), "=r"(v.y), "=r"(v.z), "=r"(v.w) : "l"(p) : "memory"); return v; }
__device__ __forceinline__ void st_async4(uint32_t a, uint32_t x, uint32_t y, uint32_t z, uint32_t w, uint32_t bar) {
  asm volatile("st.async.weak.shared::cluster.mbarrier::complete_tx::bytes.v4.b32 [%0], {%1,%2,%3,%4}, [%5];" :: "r"(a), "r"(x), "r"(y), "r"(z), "r"(w), "r"(bar) : "memory");
}
constexpr int NREP = 2;
__device__ __forceinline__ void cnt_arrive(unsigned* c, int lane) {
  if (lane < NREP) asm volatile("red.relaxed.gpu.global.add.u32 [%0], 1;" :: "l"(c) : "memory");
}
template <bool ACQ> __device__ __forceinline__ void cnt_wait(Scratch* scr, int i, int rep, unsigned target) {
  unsigned v; int n = 0;
  do {
    if (ACQ) asm volatile("ld.acquire.gpu.global.u32 %0, [%1];" : "=r"(v) : "l"(&g_cnt[(i * NREP + rep) * 64]) : "memory");
    else asm volatile("ld.relaxed.gpu.global.u32 %0, [%1];" : "=r"(v) : "l"(&g_cnt[(i * NREP + rep) * 64]) : "memory");
    if (++n > 2000000) __trap(); } while ((int)(v - target) < 0);
}
__device__ __forceinline__ void fence_gpu() { asm volatile("fence.acq_rel.gpu;" ::: "memory"); }
__device__ __forceinline__ void tag_check(uint4& v, const uint4* p, uint32_t tag) {
  int n = 0;
  while ((v.x ^ tag) & 1) {
    asm volatile("ld.relaxed.gpu.global.v4.b32 {%0,%1,%2,%3}, [%4];" : "=r"(v.x), "=r"(v.y), "=r"(v.z), "=r"(v.w) : "l"(p) : "memory");
    if (++n > 2000000) __trap();
  }
}
template <int N> __device__ __forceinline__ void cs(int n, float& c, float& s) {
  n = ((n + N / 2) & (N - 1)) - N / 2;
  float a = (float)n * (6.283185307179586f / N);
  c = __cosf(a); s = __sinf(a);
}
constexpr float ALPHA = 1.13288f;
struct FftC { uint32_t a[4][4], b[8][2]; float tc[2][4], ts[2][4]; };
constexpr uint32_t NEG = 0x80008000u;

__device__ __forceinline__ void fft_s1(const FftC& K, const uint32_t (&in)[4][2], float (&cr)[2][4], float (&ci)[2][4]) {
#pragma unroll
  for (int h = 0; h < 2; h++) { mma0(cr[h], K.a[0], in[0][h], in[1][h]); mma0(ci[h], K.a[1], in[0][h], in[1][h]); }
#pragma unroll
  for (int h = 0; h < 2; h++) { mmac(cr[h], cr[h], K.a[2], in[2][h], in[3][h]); mmac(ci[h], ci[h], K.a[3], in[2][h], in[3][h]); }
}
__device__ __forceinline__ void fft_s2(const FftC& K, const float (&cr)[2][4], const float (&ci)[2][4], float (&o)[4][4]) {
  uint32_t a[2][4];
#pragma unroll
  for (int h = 0; h < 2; h++)
#pragma unroll
    for (int i = 0; i < 4; i++) {
      float xr = cr[i & 1][2 * h + (i >> 1)], xi = ci[i & 1][2 * h + (i >> 1)];
      a[i >> 1][2 * (i & 1) + h] = pk(xr * K.tc[h][i] + xi * K.ts[h][i], xi * K.tc[h][i] - xr * K.ts[h][i]);
    }
#pragma unroll
  for (int j = 0; j < 4; j++) mma0(o[j], a[0], K.b[j][0], K.b[j][1]);
#pragma unroll
  for (int j = 0; j < 4; j++) mmac(o[j], o[j], a[1], K.b[4 + j][0], K.b[4 + j][1]);
}
__device__ __forceinline__ int zphys(int k) { return k + 8 * (k >> 5); }
__device__ __forceinline__ float gelu(float u) {
  float z = u * (0.7978845608028654f + 0.035677408136300125f * u * u), th;
  asm("tanh.approx.f32 %0, %1;" : "=f"(th) : "f"(z));
  float hu = 0.5f * u;
  return fmaf(hu, th, hu);
}

extern "C" __global__ void __cluster_dims__(2, 1, 1) __launch_bounds__(384, 1)
fused_kernel(const uint2* __restrict__ x, Scratch* scr,
             const uint32_t* __restrict__ b1, const unsigned short* __restrict__ b2, uint4* __restrict__ out, const char* __restrict__ w2,
             const __grid_constant__ CUtensorMap tmWr, const __grid_constant__ CUtensorMap tmWi, const __grid_constant__ CUtensorMap tmW1, const __grid_constant__ CUtensorMap tmW2) {
  extern __shared__ __align__(1024) char smem[];
  const uint32_t sb = (uint32_t)__cvta_generic_to_shared(smem);
  const uint32_t mb = sb + BAR_OFF;
  const int b = blockIdx.x, rank = b & 1, pr = ((b >> 1) - 4) & 63;
  const int pq = (pr - 32) * 37 >> 8;
  const int dt = pr < 32 ? pr >> 3 : pr < 60 ? pq : pr - 60, ot = pr < 32 ? pr & 7 : pr < 60 ? pr - 24 - 7 * pq : 15;
  const int warp = __shfl_sync(0xffffffffu, threadIdx.x >> 5, 0), lane = threadIdx.x & 31;
  const int g = lane >> 2, t = lane & 3;

  if (warp >= 8) {
    const int pw = warp - 8;
    if (pw < 3 && elect()) {
#pragma unroll
      for (int i = 0; i < 57; i++) mbar_init(mb + (pw * 57 + i) * 8, pw == 2 ? 2 : 1);
      asm volatile("fence.mbarrier_init.release.cluster;" ::: "memory");
    }
    if (pw == 3 && elect()) {
#pragma unroll
      for (int i = 0; i < 5; i++) mbar_init(mb + (MB_G + i) * 8, 1);
      mbar_expect(mb + MB_RAW * 8, b & 15 ? 24576 : 49152);
      asm volatile("fence.mbarrier_init.release.cluster;" ::: "memory");
    }
    __syncwarp();
    STAMP(0);
    asm volatile("bar.sync 2, 128;" ::: "memory");
    asm volatile("barrier.cluster.arrive.relaxed.aligned;" ::: "memory");
    auto w1_issue = [&](int w0, int w1) {
      const int i = w0 + pw + 4 * lane;
      if (i < w1) { mbar_expect(mb + (MB_W1T + i) * 8, 6144); tma3d(sb + i * 6144 - w0 * 512, &tmW1, 88 * ot & ~15, 0, 128 * rank + 4 * i, mb + (MB_W1T + i) * 8); }
      __syncwarp();
    };
    {
      const int j1 = b >> 4, q = b & 15, slot = lane & 15, h = lane >> 4;
      const bool hi = q >= 8;
      const int k = 16 * (q & 7) + slot, col = hi ? 256 - k : (k == 0 ? 128 : k);
      const int j0 = j1 + 8 * h + 512 * pw, r0 = hi ? 2048 - 31 * 16 - j0 : j0, c0 = (r0 & 7) * DF;
      const int ca = (c0 + (hi ? 241 - 16 * (q & 7) : 16 * q)) & ~7, cb = (c0 + 128) & ~7;
      if ((pw < 2 || q == 0) && elect())
        asm volatile("cp.async.bulk.tensor.2d.shared::cluster.global.mbarrier::complete_tx::bytes [%0], [%1, {%3, %4}], [%2];"
                     :: "r"(sb + RAW_OFF + pw * 12288), "l"(pw & 1 ? &tmWi : &tmWr), "r"(mb + MB_RAW * 8), "r"(pw < 2 ? ca : cb), "r"(0) : "memory");
      __syncwarp();
      const uint32_t o0 = sb + RAW_OFF + (r0 >> 3) * 48 + (k == 0 && !hi ? 24576 + (c0 + col - cb) * 2 : (c0 + col - ca) * 2), o31 = hi && j0 == 0 ? o0 - 256 * 48 : o0;
      uint32_t vr[32], vi[32];
      mbar_wait(mb + MB_RAW * 8, 0);
      asm volatile("bar.sync 3, 160;" ::: "memory");
#pragma unroll
      for (int n = 0; n < 32; n++) {
        asm volatile("ld.shared.u16 %0, [%1];" : "=r"(vr[n]) : "r"((n == 31 ? o31 : o0) + n * 96) : "memory");
        asm volatile("ld.shared.u16 %0, [%1];" : "=r"(vi[n]) : "r"((n == 31 ? o31 : o0) + n * 96 + 12288) : "memory");
      }
      const uint32_t f0 = sb + FILT_OFF + pw * 4096 + (hi ? 31 * 128 : 0) + h * 8 + (slot & 1) * 4, sw = ((slot >> 1) ^ (hi ? 7 : 0)) << 4;
      const int st = hi ? -128 : 128;
#pragma unroll
      for (int n = 0; n < 32; n++)
        sts32(f0 + n * st + (sw ^ ((((n >> 3) & 3) * 2 + (n & 1)) << 4)), __byte_perm(vr[n], vi[n], 0x5410) ^ (hi ? 0x80000000u : 0u));
      asm volatile("bar.sync 2, 128;" ::: "memory");
      if (threadIdx.x == 352) mbar_arrive(mb + MB_FILT * 8);
    }
    __syncwarp();
    STAMP(1);
    if (pw == 3 && lane < 4) asm volatile("prefetch.global.L2 [%0];" :: "l"(lane < 2 ? (const char*)b1 + min(176 * ot + 128 * lane, 2750) : (const char*)b2 + 256 * ot + 128 * (lane - 2)));
    {
      const int oc = ((lane >> 3) + (lane >> 1)) & 3;
      const uint32_t rd = sb + (lane & 7) * 192 + (oc + (ot & 1)) * 16, wr = sb + oc * 128 + (lane & 7) * 16;
      int box = pw;
#pragma unroll 1
      for (int win = 0; win < 2; win++) {
        const int w0 = box - pw, w1 = w0 + 16;
        mbar_wait(mb + (MB_G + win) * 8, 0);
        w1_issue(w0, w1);
        mbar_wait(mb + (win ? MB_P3DONE : MB_G + 3) * 8, 0);
#pragma unroll 1
        for (; box < w1; box += 4) {
          mbar_wait(mb + (MB_W1T + box) * 8, 0);
          const uint32_t p = rd + box * 6144 - w0 * 512, q = wr + box * 5632;
          uint4 v[4][3];
#pragma unroll
          for (int n = 0; n < 4; n++) { v[n][0] = lds128(p + n * 1536); v[n][1] = lds128(p + n * 1536 + 64); if (oc < 3) v[n][2] = lds128(p + n * 1536 + 128); }
          asm volatile("bar.sync 2, 128;" ::: "memory");
#pragma unroll
          for (int n = 0; n < 4; n++) { sts128(q + n * 1408, v[n][0]); sts128(q + n * 1408 + 512, v[n][1]); if (oc < 3) sts128(q + n * 1408 + 1024, v[n][2]); }
        }
        asm volatile("fence.proxy.async.shared::cta;" ::: "memory");
        if (win == 0) STAMP(0);
      }
      asm volatile("bar.sync 2, 128;" ::: "memory");
      if (threadIdx.x == 352) mbar_arrive(mb + MB_W1 * 8);
      if (pw == 3) {
        mbar_wait(mb + MB_FULL * 8, 0);
        if (lane < 4) asm volatile("cp.async.bulk.prefetch.L2.global [%0], %1;" :: "l"(w2 + (size_t)(b * 4 + lane) * 11008), "r"(11008) : "memory");
        __syncwarp();
      }
    }
    STAMP(2);
    asm volatile("barrier.cluster.wait.aligned;" ::: "memory");
    if (pw == 3) {
#pragma unroll 1
      for (int n = 0; n < 22; n++) {
        if (elect()) mbar_expect(mb + (MB_W2 + n) * 8, 8192);
        if (n < W2_PRE) mbar_wait(mb + (MB_EMPTY + min(31, max(((n + 4) * 16 + 10) / 11 - 1, W2_START + n))) * 8, 0);
        else { mbar_wait(mb + MB_X1DONE * 8, 0); mbar_wait(mb + (MB_FULL + 32 - W2_PRE + n) * 8, 0); }
        if (elect()) { tma3d(sb + (n < 19 ? n + 3 : n - 19) * 8192, &tmW2, 0, 688 * rank + 32 * n, 2 * ot, mb + (MB_W2 + n) * 8); }
      }
    } else {
      int i = pw;
      uint32_t dst = sb + RING_OFF + pw * 8192;
      const uint32_t dsum = 2 * dst + 3 * 8192;
      const char* src = (const char*)g_Hn + ((size_t)dt * 128 + 64 * rank + 2 * pw) * 4096;
#pragma unroll 1
      for (int gm = 0; gm < 2; gm++) {
        if (gm == 0) mbar_wait(mb + (MB_G + 2) * 8, 0);
        else {
          if (pw == 0) {
            mbar_wait(mb + MB_X1DONE * 8, 0);
            if (lane == 0) cnt_wait<true>(scr, 4 + dt, ot & (NREP - 1), (lds32(sb + BASE_OFF) >> 2) + 32);
          }
          asm volatile("bar.sync 2, 96;" ::: "memory");
        }
        STAMP(4 + 2 * gm);
        asm volatile("fence.proxy.async.global;" ::: "memory");
#pragma unroll 1
        for (; i < (gm ? 54 : 32); i += 3) {
          const int bytes = i < 53 ? 8192 : 4096;
          if (elect()) mbar_expect(mb + (MB_FULL + i) * 8, bytes);
          if (i >= NST) mbar_wait(mb + (MB_EMPTY - NST + i) * 8, 0);
          if (elect()) bulk_ld(dst, src, bytes, mb + (MB_FULL + i) * 8);
          src += 3 * 8192;
          dst = dsum - dst;
        }
        src = (const char*)g_U + ((size_t)dt * 172 + 86 * rank) * 2048 + (i - 32) * 8192;
      }
      STAMP(7);
      DUMP();
    }
  } else {
    const int tid = threadIdx.x;
    uint32_t xw[2][4][2];
    const uint32_t zb = sb + XCH_OFF, zw = zb + warp * ZROW * 4;
    const int rep = ot & (NREP - 1);
    if (elect()) {
      const uint32_t xb = mb + (MB_X + warp) * 8;
      mbar_init(xb, 1);
      asm volatile("fence.proxy.async.shared::cta;" ::: "memory");
      mbar_expect(xb, 2064);
      bulk_ld(zw, x + (size_t)(256 * warp + 2 * b) * 128, 1024, xb);
      bulk_ld(zw + 8 * ZROW * 4, x + (size_t)(256 * warp + 2 * b + 1) * 128, 1024, xb);
      bulk_ld(zw + 1280, &g_cnt[(1 * NREP + rep) * 64], 16, xb);
    }
    __syncwarp();
    STAMP(0);
    const uint32_t tab = sb + TAB_OFF + lane * 16;
    FftC K;
    {
      const int lg = pin(lane) >> 2, w3 = warp & 3, w1 = warp & 1, w2 = w3 >> 1;
      const bool lo4 = warp < 4;
      float c, s;
      cs<16>(lo4 ? (2 * lg + w1) * (t + 4 * w2) : (4 * t + w3) * (lg >> 1) + 4 * (lg & 1), c, s);
      const uint32_t P = pk(ALPHA * c, ALPHA * s), Q = pk(-ALPHA * s, ALPHA * c);
#pragma unroll
      for (int m = 0; m < 4; m++) {
        const int sel = lo4 ? (m & 1) | (m & 2 & (w1 << 1)) : w3 * m;
        sts32(tab + (lo4 ? m * 512 + w3 * 4 : (4 + 2 * w2 + (m >> 1)) * 512 + (2 * (m & 1) + w1) * 4), (sel & 1 ? Q : P) ^ (sel & 2 ? NEG : 0u));
      }
      cs<256>((2 * lg + (warp >> 2)) * (4 * t + w3), c, s);
      sts32(tab + (8 + (warp >> 2)) * 512 + w3 * 4, __float_as_uint(c * (1.f / (ALPHA * ALPHA))));
      sts32(tab + (10 + (warp >> 2)) * 512 + w3 * 4, __float_as_uint(s * (1.f / (ALPHA * ALPHA))));
      cs<2048>(256 * lg * (t + 4 * w2) + (lo4 ? lg : t + 4 * w2) * (2 * b + w1), c, s);
      const uint32_t e0 = pk(c, s), e1 = pk(-s, c), mk = lo4 ? 0x80000000u : NEG, at = tab + (lo4 ? 12 + 3 * w1 : 18 + 2 * w1) * 512 + w2 * 8;
      sts64(at, e0, e1);
      sts64(at + 512, e0 ^ mk, e1 ^ mk);
      if (lo4) sts64(at + 1024, e0 ^ 0x8000u, e1 ^ 0x8000u);
    }
    const int key = ((b >> 3) & 3) * 2 + (b & 1);
    float mean[2];
    unsigned* cp;
    uint32_t tag, base;
    {
      float vc[4], vs[4];
#pragma unroll
      for (int i = 0; i < 4; i++) { cs<512>(16 * warp + 8 * (i >> 1) + 2 * t + (i & 1) + 128, vc[i], vs[i]); vc[i] = pinf(vc[i]); vs[i] = pinf(vs[i]); }
      wbar();
#pragma unroll
      for (int m = 0; m < 4; m++) {
        lds4(K.a[m], tab + m * 512);
        const uint4 v = lds128(tab + (4 + m) * 512), w = lds128(tab + (8 + m) * 512);
        K.b[2 * m][0] = v.x; K.b[2 * m][1] = v.y; K.b[2 * m + 1][0] = v.z; K.b[2 * m + 1][1] = v.w;
        float* d = m < 2 ? K.tc[m] : K.ts[m - 2];
        d[0] = __uint_as_float(w.x); d[1] = __uint_as_float(w.y); d[2] = __uint_as_float(w.z); d[3] = __uint_as_float(w.w);
      }
      cp = pinp(g_cnt + lane * 64);
      asm volatile("fence.mbarrier_init.release.cluster;" ::: "memory");
      asm volatile("barrier.cluster.arrive.relaxed.aligned;" ::: "memory");
      STAMP(13);
      mbar_wait(mb + (MB_X + warp) * 8, 0);
#pragma unroll
      for (int a = 0; a < 2; a++)
#pragma unroll
        for (int j = 0; j < 4; j++) { const uint2 v = lds64(zw + a * 8 * ZROW * 4 + j * 256 + (8 * t + g) * 8); xw[a][j][0] = v.x; xw[a][j][1] = v.y; }
      base = lds32(zw + 1280);
      __syncwarp();
      tag = 1;
#pragma unroll
      for (int a = 0; a < 2; a++) {
        float cr[2][4], ci[2][4], o[4][4];
        if (a == 0) { if (xw[0][0][0] == 0x12345678u && xw[1][3][1] == 0x12345679u) STAMP(29); STAMP(14); }
        fft_s1(K, xw[a], cr, ci);
        float sm = ((cr[0][0] + cr[0][1]) + (cr[1][0] + cr[1][1])) + ((ci[0][0] + ci[0][1]) + (ci[1][0] + ci[1][1]));
        sm += __shfl_xor_sync(0xffffffffu, sm, 1); sm += __shfl_xor_sync(0xffffffffu, sm, 2);
        sm = g == 0 ? sm * (1.f / 32.f) : 0.f;
#pragma unroll
        for (int h = 0; h < 2; h++) { cr[h][0] -= sm; cr[h][1] -= sm; ci[h][0] -= sm; ci[h][1] -= sm; }
        mean[a] = __shfl_sync(0xffffffffu, sm, 0) * (1.f / (16.f * 1.1328125f));
        float q = 0.f, q2 = 0.f;
#pragma unroll
        for (int i = 0; i < 4; i++) { q = fmaf(cr[0][i], cr[0][i], q); q2 = fmaf(cr[1][i], cr[1][i], q2); q = fmaf(ci[0][i], ci[0][i], q); q2 = fmaf(ci[1][i], ci[1][i], q2); }
        q += q2;
#pragma unroll
        for (int m = 1; m < 32; m <<= 1) q += __shfl_xor_sync(0xffffffffu, q, m);
        float r = rsqrtf(q * (1.f / (512.f * 16.f * ALPHA * ALPHA)) + 1e-5f) * 4.76837158203125e-7f;
        fft_s2(K, cr, ci, o);
#pragma unroll
        for (int j = 0; j < 4; j++)
          sts64(zb + ((a * 8 + warp) * ZROW + zphys(16 * t + 64 * j) + 2 * g) * 4, pk(o[j][0] * r, o[j][1] * r), pk(o[j][2] * r, o[j][3] * r));
      }
      uint32_t a8[2][4], a8c[2][4], a8n[2][4];
#pragma unroll
      for (int a = 0; a < 2; a++) { lds4(a8[a], tab + (12 + 3 * a) * 512); lds4(a8c[a], tab + (13 + 3 * a) * 512); lds4(a8n[a], tab + (14 + 3 * a) * 512); }
      STAMP(15);
      wbar();
      uint4* tp = g_T1 + (size_t)(g * 16 + warp) * 1024 + b * 8;
#pragma unroll
      for (int nt = 0; nt < 2; nt++) {
        const int k = 16 * warp + 8 * nt + g, km = k == 0 ? 128 : 256 - k;
        uint32_t lo[4], hi[4];
#pragma unroll
        for (int a = 0; a < 2; a++) {
          const uint32_t rb = zb + (a * 8 + t) * ZROW * 4;
          float A[4], S[4], D[4];
          const uint32_t m0 = lds32(rb + zphys(km) * 4), m1 = lds32(rb + (4 * ZROW + zphys(km)) * 4);
          mma0(A, a8[a], lds32(rb + zphys(k) * 4), lds32(rb + (4 * ZROW + zphys(k)) * 4));
          mmac(S, A, a8c[a], m0, m1);
          mmac(D, A, a8n[a], m0, m1);
#pragma unroll
          for (int e = 0; e < 2; e++) {
            const float c = vc[2 * nt + e], s = vs[2 * nt + e];
            float lr = fmaf(D[2 + e], s, fmaf(D[e], c, S[e])), li = fmaf(-D[e], s, fmaf(D[2 + e], c, S[2 + e]));
            float hr = fmaf(2.f, S[e], -lr), hii = fmaf(2.f, S[2 + e], -li);
            if (nt == 0 && e == 0) {
              const bool sp = warp == 0 && t == 0;
              lr = sp ? S[0] - D[0] : lr; li = sp ? S[2] - D[2] : li;
              hr = sp ? 2.f * (A[0] - A[2]) : hr; hii = sp ? 2.f * (A[0] + A[2]) : hii;
            }
            lo[2 * a + e] = pk(lr, li); hi[2 * a + e] = pk(hr, hii);
          }
        }
        const int w = (t + 4 * nt) ^ key;
        tp[w] = make_uint4((lo[0] & ~1u) | tag, lo[1], lo[2], lo[3]);
        tp[8 * 1024 + w] = make_uint4((hi[0] & ~1u) | tag, hi[1], hi[2], hi[3]);
      }
      wbar();
      STAMP(1);
      if (warp == 0) cnt_arrive(cp, lane);
      if (warp == 1) asm volatile("bar.arrive 3, 160;" ::: "memory");
    }
    {
      const uint32_t off = (8 * t + g) * 128 + ((warp ^ (2 * t + (g & 1))) << 4);
      asm volatile("barrier.cluster.wait.aligned;" ::: "memory");
      uint4* const tb = pinp(g_T1 + b * 1024 + tid);
      const uint32_t ts = pin(zb + tid * 16);
      if (tid == 0) cnt_wait<false>(scr, 0, rep, base + NCTA);
      wbar();
#pragma unroll
      for (int j = 0; j < 4; j++)
        asm volatile("cp.async.cg.shared.global [%0], [%1], 16;" :: "r"(ts + j * 4096), "l"(tb + j * 256) : "memory");
      STAMP(2);
      if (tid == 32) { sts32(sb + BASE_OFF, base); mbar_arrive(mb + MB_G * 8); }
      uint32_t in[2][4][2], fw[2][4][2];
      mbar_wait(mb + MB_FILT * 8, 0);
#pragma unroll
      for (int j = 0; j < 4; j++) {
        uint4 v = lds128(sb + FILT_OFF + off + j * 4096);
        fw[0][j][0] = v.x; fw[1][j][0] = v.y; fw[0][j][1] = v.z; fw[1][j][1] = v.w;
      }
      asm volatile("cp.async.wait_all;" ::: "memory");
      wbar();
      STAMP(3);
      uint4 iv[4];
#pragma unroll
      for (int j = 0; j < 4; j++) iv[j] = lds128(zb + off + j * 4096);
      if (((iv[0].x ^ tag) | (iv[1].x ^ tag) | (iv[2].x ^ tag) | (iv[3].x ^ tag)) & 1) {
#pragma unroll
        for (int j = 0; j < 4; j++) tag_check(iv[j], g_T1 + (size_t)b * 1024 + j * 256 + (off >> 4), tag);
      }
      __syncwarp();
#pragma unroll
      for (int j = 0; j < 4; j++) { in[0][j][0] = iv[j].x; in[1][j][0] = iv[j].y; in[0][j][1] = iv[j].z; in[1][j][1] = iv[j].w; }
#pragma unroll
      for (int sg = 0; sg < 2; sg++) {
        float cr[2][4], ci[2][4], o[4][4];
        fft_s1(K, in[sg], cr, ci);
        fft_s2(K, cr, ci, o);
#pragma unroll
        for (int j = 0; j < 4; j++)
#pragma unroll
          for (int h = 0; h < 2; h++) {
            float fr = blo(fw[sg][j][h]), fi = bhi(fw[sg][j][h]), xr = o[j][2 * h], xi = o[j][2 * h + 1];
            in[sg][j][h] = pk(xr * fi + xi * fr, xr * fr - xi * fi);
          }
        fft_s1(K, in[sg], cr, ci);
        fft_s2(K, cr, ci, o);
#pragma unroll
        for (int j = 0; j < 4; j++) { in[sg][j][0] = pk(o[j][0], o[j][1]); in[sg][j][1] = pk(o[j][2], o[j][3]); }
      }
      tag = 0;
#pragma unroll
      for (int j = 0; j < 4; j++) sts128(zb + off + j * 4096, make_uint4((in[0][j][0] & ~1u) | tag, in[1][j][0], in[0][j][1], in[1][j][1]));
      STAMP(16);
      wbar();
#pragma unroll
      for (int j = 0; j < 4; j++) tb[j * 256] = lds128(ts + j * 4096);
      wbar();
      STAMP(4);
      if (warp == 0) cnt_arrive(cp + NREP * 64, lane);
      if (tid == 32) mbar_arrive(mb + (MB_G + 3) * 8);
    }
    {
      uint32_t a8[2][4], a8n[2][4]; float vc[4], vs[4];
#pragma unroll
      for (int a = 0; a < 2; a++) { lds4(a8[a], tab + (18 + 2 * a) * 512); lds4(a8n[a], tab + (19 + 2 * a) * 512); }
#pragma unroll
      for (int i = 0; i < 4; i++) { cs<512>(16 * warp + 4 * t + i + 128, vc[i], vs[i]); vc[i] = pinf(vc[i]); vs[i] = pinf(vs[i]); }
      cp = pinp(g_cnt + ((2 + (b >> 6)) * NREP + lane) * 64);
      float2* const sp = pinp(g_st + 256 * warp + 2 * b + (lane >> 4));
      if (tid == 0) cnt_wait<false>(scr, 1, rep, base + NCTA);
      wbar();
      STAMP(5);
      constexpr int TS = 1024;
      const uint4* tp = g_T1 + (t * 16 + warp) * TS + b * (8192 / TS) + (g ^ key);
      uint4 L0 = ldcg128(tp), L1 = ldcg128(tp + 64 * TS), H0 = ldcg128(tp + 8 * TS), H1 = ldcg128(tp + 72 * TS);
      if (tid == 32) mbar_arrive(mb + (MB_G + 1) * 8);
      if (((L0.x ^ tag) | (L1.x ^ tag) | (H0.x ^ tag) | (H1.x ^ tag)) & 1) {
        tag_check(L0, tp, tag); tag_check(L1, tp + 64 * TS, tag); tag_check(H0, tp + 8 * TS, tag); tag_check(H1, tp + 72 * TS, tag);
      }
      __syncwarp();
      STAMP(17);
      const uint32_t l0[4] = {L0.x, L0.y, L0.z, L0.w}, l1[4] = {L1.x, L1.y, L1.z, L1.w}, h0[4] = {H0.x, H0.y, H0.z, H0.w}, h1[4] = {H1.x, H1.y, H1.z, H1.w};
#pragma unroll
      for (int a = 0; a < 2; a++) {
        uint32_t zf[4], zm[4];
#pragma unroll
        for (int sg = 0; sg < 2; sg++) {
          float A[4], S[4], D[4];
          mma0(A, a8[a], l0[2 * a + sg], l1[2 * a + sg]);
          mmac(S, A, a8[a], h0[2 * a + sg], h1[2 * a + sg]);
          mmac(D, A, a8n[a], h0[2 * a + sg], h1[2 * a + sg]);
#pragma unroll
          for (int e = 0; e < 2; e++) {
            const int i = 2 * e + sg;
            float fr = fmaf(-D[e], vs[i], fmaf(D[2 + e], vc[i], S[2 + e])), fi = fmaf(D[2 + e], vs[i], fmaf(D[e], vc[i], S[e]));
            float mr = fmaf(2.f, S[2 + e], -fr), mi = fmaf(-2.f, S[e], fi);
            if (i == 0) {
              const bool sp = warp == 0 && t == 0;
              fr = sp ? S[2] - A[2] : fr; fi = sp ? A[2] - S[2] : fi;
              mr = sp ? 2.f * A[2] : mr; mi = sp ? -2.f * A[0] : mi;
            }
            zf[i] = pk(fi, fr); zm[i] = pk(mi, mr);
          }
        }
        const uint32_t rb = zb + (a * 8 + g) * ZROW * 4;
        const int k0 = 16 * warp + 4 * t;
        sts128(rb + zphys(k0) * 4, make_uint4(zf[0], zf[1], zf[2], zf[3]));
        sts32(rb + zphys(k0 == 0 ? 128 : 256 - k0) * 4, zm[0]);
        sts32(rb + zphys(255 - k0) * 4, zm[1]);
        sts32(rb + zphys(254 - k0) * 4, zm[2]);
        sts32(rb + zphys(253 - k0) * 4, zm[3]);
      }
      STAMP(18);
      wbar();
      float o[2][4][4], s2[2];
#pragma unroll
      for (int a = 0; a < 2; a++) {
        uint32_t in[4][2];
#pragma unroll
        for (int j = 0; j < 4; j++) { uint2 v = lds64(zb + ((a * 8 + warp) * ZROW + zphys(16 * t + 64 * j) + 2 * g) * 4); in[j][0] = v.x; in[j][1] = v.y; }
        float cr[2][4], ci[2][4], s1 = 0.f;
        fft_s1(K, in, cr, ci);
        fft_s2(K, cr, ci, o[a]);
        s2[a] = 0.f;
#pragma unroll
        for (int j = 0; j < 4; j++)
#pragma unroll
          for (int h = 0; h < 2; h++) {
            uint32_t hw;
            asm("add.rn.bf16x2 %0, %1, %2;" : "=r"(hw) : "r"(xw[a][j][h]), "r"(pk(o[a][j][2 * h + 1], o[a][j][2 * h])));
            const float u0 = blo(hw) - mean[a], u1 = bhi(hw) - mean[a];
            o[a][j][2 * h] = u0; o[a][j][2 * h + 1] = u1;
            s1 = fmaf(u0, u0, s1); s2[a] = fmaf(u1, u1, s2[a]);
          }
        s2[a] += s1;
      }
      float sv = (lane < 16 ? s2[0] : s2[1]) + __shfl_xor_sync(0xffffffffu, lane < 16 ? s2[1] : s2[0], 16);
#pragma unroll
      for (int m = 1; m < 16; m <<= 1) sv += __shfl_xor_sync(0xffffffffu, sv, m);
      const float var = sv * (1.f / 512.f), r1 = rsqrtf(var + 1e-5f);
      const float rr = r1 * rsqrtf(var * r1 * r1 + 1e-5f);
      const float ro = __shfl_xor_sync(0xffffffffu, rr, 16);
      float ri;
      asm("rcp.approx.ftz.f32 %0, %1;" : "=f"(ri) : "f"(rr));
      if ((lane & 15) == 0) asm volatile("st.global.v2.f32 [%0], {%1, %2};" :: "l"(sp), "f"(ri), "f"(lane ? mean[1] : mean[0]) : "memory");
      char* np = (char*)g_Hn + (size_t)b * 4096 + (t >> 1) * 2048 + warp * 128 + ((((t & 1) * 4 + (g >> 1)) ^ warp ^ (b >> 6)) << 4) + (g & 1) * 8;
#pragma unroll
      for (int a = 0; a < 2; a++) {
        const float r = (lane >> 4) == a ? rr : ro;
#pragma unroll
        for (int j = 0; j < 4; j++)
          *(uint2*)(np + a * 1024 + (size_t)j * 128 * 4096) = make_uint2(pk(o[a][j][0] * r, o[a][j][1] * r), pk(o[a][j][2] * r, o[a][j][3] * r));
      }
      STAMP(19);
      asm volatile("fence.proxy.async.shared::cta;" ::: "memory");
      wbar();
      STAMP(6);
      if (warp == 0) { fence_gpu(); cnt_arrive(cp, lane); STAMP(25); }
      if (tid == 32) mbar_arrive(mb + MB_P3DONE * 8);
      wbar();
      asm volatile("" : "+l"(b1) :: "memory");
    }
    const int wg = warp >> 2;
    const uint32_t peer_sb = mapa(sb, rank ^ 1);
    {
      float acc[44];
      cp = pinp(g_cnt + ((4 + dt) * NREP + lane) * 64);
      if (lane == 0) mbar_expect(mb + (MB_X + warp) * 8, 1536);
#pragma unroll
      for (int j = 0; j < 11; j++) {
        const uint32_t bw = __ldg(b1 + min(11 * ot + j, 171) * 4 + t);
        acc[4 * j] = blo(bw); acc[4 * j + 1] = bhi(bw); acc[4 * j + 2] = 0.f; acc[4 * j + 3] = 0.f;
      }
      const uint32_t da0 = desc_lo(sb + RING_OFF + wg * 2048, 0);
      uint32_t da = da0, db = desc_lo(sb, 1408), bar = mb;
#pragma unroll
      for (int j = 0; j < 11; j++) asm volatile("" : "+f"(acc[4 * j]), "+f"(acc[4 * j + 1]) :: "memory");
      if (warp == 1) {
        if (lane == 0) { cnt_wait<true>(scr, 2 + rank, rep, (base >> 1) + 64); mbar_arrive(mb + (MB_G + 2) * 8); }
        __syncwarp();
      }
      mbar_wait(mb + MB_W1 * 8, 0);
#pragma unroll 1
      for (int i = 0; i < 32; i++) {
        mbar_wait(bar + MB_FULL * 8, 0);
        if (i == 0) STAMP(7);
        asm volatile("wgmma.fence.sync.aligned;" ::: "memory");
        wgmma_n88_ss<1, 1, HI_SW128, HI_NOSW>(acc, da, db, 1);
        wgmma_n88_ss<1, 1, HI_SW128, HI_NOSW>(acc, da + 256, db + 176, 1);
        asm volatile("wgmma.commit_group.sync.aligned;" ::: "memory");
        da = da == da0 + 5 * 512 ? da0 : da + 512; db += 352;
        asm volatile("wgmma.wait_group.sync.aligned 1;" ::: "memory");
        if ((tid & 127) == 0) { if (i > 0) mbar_arrive(bar + (MB_EMPTY - 1) * 8); if (i == 4) mbar_arrive_cluster(peer_sb + BAR_OFF + MB_PEER1 * 8); }
        bar += 8;
      }
      asm volatile("wgmma.wait_group.sync.aligned 0;" ::: "memory");
#pragma unroll
      for (int i = 0; i < 44; i++) asm volatile("" : "+f"(acc[i]) :: "memory");
      if ((tid & 127) == 0) mbar_arrive(mb + (MB_EMPTY + 31) * 8);
      STAMP(8);
      mbar_wait_cluster(mb + MB_PEER1 * 8, 0);
#pragma unroll
      for (int j = 0; j < 3; j++)
        st_async4(peer_sb + j * 4096 + tid * 16, pk(acc[16 * j + 2], acc[16 * j + 3]), pk(acc[16 * j + 6], acc[16 * j + 7]), pk(acc[16 * j + 10], acc[16 * j + 11]),
                  j < 2 ? pk(acc[16 * j + 14], acc[16 * j + 15]) : 0u, peer_sb + BAR_OFF + (MB_X + warp) * 8);
      const int uo = (4 * (warp >> 1) + (g >> 1)) * 32 + (2 * (2 * (warp & 1) + rank) + (g & 1)) * 4 + t;
      uint32_t* const ub = (uint32_t*)g_U + ((size_t)dt * 172 + 11 * ot) * 512;
      uint32_t *upa = ub + (uo ^ (ot >= 8 ? 256 : 0)), *upb = ub + (uo ^ (ot >= 7 ? 256 : 0));
      STAMP(20);
      mbar_wait_cluster(mb + (MB_X + warp) * 8, 1);
      STAMP(21);
      uint32_t pv[12];
#pragma unroll
      for (int j = 0; j < 3; j++) { const uint4 v = lds128(sb + j * 4096 + tid * 16); pv[4 * j] = v.x; pv[4 * j + 1] = v.y; pv[4 * j + 2] = v.z; pv[4 * j + 3] = v.w; }
#pragma unroll
      for (int j = 0; j < 11; j++) {
        uint32_t v = pk(gelu(acc[4 * j] + blo(pv[j])), gelu(acc[4 * j + 1] + bhi(pv[j])));
        if (j < 7 || ot < 15) (j < 9 ? upa : upb)[j * 512] = v;
      }
      STAMP(22);
      asm volatile("fence.proxy.async.shared::cta;" ::: "memory");
      wbar();
      STAMP(9);
      if (warp == 0) { fence_gpu(); cnt_arrive(cp, lane); STAMP(26); }
      if (tid == 32) mbar_arrive(mb + MB_X1DONE * 8);
      wbar();
      asm volatile("" : "+l"(b2), "+l"(scr) :: "memory");
    }
    {
      const int srow = 128 * ot + 16 * warp + g, oo = srow * 64 + dt * 16 + 8 * rank + t;
      float acc[64];
      if (lane == 0) mbar_expect(mb + (MB_X + warp) * 8, 2048);
      const uint32_t da0 = desc_lo(sb + wg * 4096, 0), db0 = desc_lo(sb + RING_OFF, 2048);
      uint32_t da = da0 + 3 * 512, db = db0 + (32 % NST) * 512, bar = mb;
#pragma unroll
      for (int u = 0; u < 2; u++) {
        const int sr = srow + 8 * u, s1 = ot >> 1;
        const float2 st = __ldcg(g_st + sr);
        const float off = st.y + __uint_as_float((uint32_t)__ldg(b2 + sr) << 16);
#pragma unroll
        for (int jj = 0; jj < 2; jj++) {
          const uint4 v = ldcg128(g_Hn + (dt * 128 + ((sr & 255) >> 1)) * 256 + rank * 128 + (sr & 1) * 64 + s1 * 8 + ((4 * jj + t) ^ s1 ^ (ot & 1)));
          const uint32_t w[4] = {v.x, v.y, v.z, v.w};
#pragma unroll
          for (int j = 0; j < 4; j++) { acc[16 * jj + 4 * j + 2 * u] = fmaf(blo(w[j]), st.x, off); acc[16 * jj + 4 * j + 2 * u + 1] = fmaf(bhi(w[j]), st.x, off); }
        }
      }
#pragma unroll
      for (int j = 32; j < 64; j++) acc[j] = 0.f;
#pragma unroll 1
      for (int i = 0; i < 21; i++) {
        mbar_wait(bar + MB_W2 * 8, 0);
        mbar_wait(bar + (MB_FULL + 32) * 8, 0);
        if (i == 0) STAMP(10);
        asm volatile("wgmma.fence.sync.aligned;" ::: "memory");
        wgmma_n128_ss<1, 0, HI_SW128, HI_NOSW>(acc, da, db, 1);
        wgmma_n128_ss<1, 0, HI_SW128, HI_NOSW>(acc, da + 128, db + 256, 1);
        asm volatile("wgmma.commit_group.sync.aligned;" ::: "memory");
        da = i == 18 ? da0 : da + 512; db = db == db0 + 5 * 512 ? db0 : db + 512;
        asm volatile("wgmma.wait_group.sync.aligned 1;" ::: "memory");
        if ((tid & 127) == 0) { if (i > 0) mbar_arrive(bar + (MB_EMPTY + 31) * 8); if (i == 4) mbar_arrive_cluster(peer_sb + BAR_OFF + MB_PEER2 * 8); }
        bar += 8;
      }
      mbar_wait(bar + MB_W2 * 8, 0);
      mbar_wait(bar + (MB_FULL + 32) * 8, 0);
      asm volatile("wgmma.fence.sync.aligned;" ::: "memory");
      wgmma_n128_ss<1, 0, HI_SW128, HI_NOSW>(acc, da, db, 1);
      asm volatile("wgmma.commit_group.sync.aligned;" ::: "memory");
      asm volatile("wgmma.wait_group.sync.aligned 0;" ::: "memory");
#pragma unroll
      for (int i = 0; i < 64; i++) asm volatile("" : "+f"(acc[i]) :: "memory");
      STAMP(11);
      mbar_wait_cluster(mb + MB_PEER2 * 8, 0);
#pragma unroll
      for (int j = 0; j < 4; j++) {
        const int o = 32 + 16 * (j >> 1) + 2 * (j & 1);
        st_async4(peer_sb + 3 * 8192 + j * 4096 + tid * 16, pk(acc[o], acc[o + 1]), pk(acc[o + 4], acc[o + 5]), pk(acc[o + 8], acc[o + 9]), pk(acc[o + 12], acc[o + 13]),
                  peer_sb + BAR_OFF + (MB_X + warp) * 8);
      }
      STAMP(23);
      mbar_wait_cluster(mb + (MB_X + warp) * 8, 0);
      STAMP(24);
#pragma unroll
      for (int j = 0; j < 4; j++) {
        const int o = 16 * (j >> 1) + 2 * (j & 1);
        const uint4 v = lds128(sb + 3 * 8192 + j * 4096 + tid * 16);
        out[oo + 4 * (j >> 1) + 512 * (j & 1)] = make_uint4(pk(acc[o] + blo(v.x), acc[o + 1] + bhi(v.x)), pk(acc[o + 4] + blo(v.y), acc[o + 5] + bhi(v.y)),
                                                            pk(acc[o + 8] + blo(v.z), acc[o + 9] + bhi(v.z)), pk(acc[o + 12] + blo(v.w), acc[o + 13] + bhi(v.w)));
      }
      STAMP(12);
      DUMP();
    }
  }
}

typedef CUresult (*EncodeFn)(CUtensorMap*, CUtensorMapDataType, cuuint32_t, void*, const cuuint64_t*, const cuuint64_t*, const cuuint32_t*,
                             const cuuint32_t*, CUtensorMapInterleave, CUtensorMapSwizzle, CUtensorMapL2promotion, CUtensorMapFloatOOBfill);

extern "C" void kernel_launch(void* const* d_in, const int* in_sizes, int n_in, void* d_out, int out_size) {
  static EncodeFn enc = nullptr;
  static void* scr = nullptr;
  if (!enc) {
    void* fn = nullptr; cudaDriverEntryPointQueryResult st;
    cudaGetDriverEntryPoint("cuTensorMapEncodeTiled", &fn, cudaEnableDefault, &st);
    enc = (EncodeFn)fn;
    cudaGetSymbolAddress(&scr, g_scr);
    cudaFuncSetAttribute(fused_kernel, cudaFuncAttributeMaxDynamicSharedMemorySize, SMEM_BYTES);
  }
  CUtensorMap tm, tm1, tf[2];
  for (int i = 0; i < 2; i++) {
    cuuint64_t dims[2] = {8 * DF, S_ / 8}, strides[1] = {8 * DF * 2};
    cuuint32_t box[2] = {24, 256}, es[2] = {1, 1};
    enc(&tf[i], CU_TENSOR_MAP_DATA_TYPE_BFLOAT16, 2, d_in[1 + i], dims, strides, box, es, CU_TENSOR_MAP_INTERLEAVE_NONE, CU_TENSOR_MAP_SWIZZLE_NONE,
        CU_TENSOR_MAP_L2_PROMOTION_NONE, CU_TENSOR_MAP_FLOAT_OOB_FILL_NONE);
  }
  {
    cuuint64_t dims[3] = {(cuuint64_t)F_, 8, 256}, strides[2] = {(cuuint64_t)256 * F_ * 2, F_ * 2};
    cuuint32_t box[3] = {96, 8, 4}, es[3] = {1, 1, 1};
    enc(&tm1, CU_TENSOR_MAP_DATA_TYPE_BFLOAT16, 3, d_in[4], dims, strides, box, es, CU_TENSOR_MAP_INTERLEAVE_NONE, CU_TENSOR_MAP_SWIZZLE_NONE,
        CU_TENSOR_MAP_L2_PROMOTION_NONE, CU_TENSOR_MAP_FLOAT_OOB_FILL_NONE);
  }
  {
    cuuint64_t dims[3] = {64, (cuuint64_t)F_, S_ / 64}, strides[2] = {S_ * 2, 128};
    cuuint32_t box[3] = {64, 32, 2}, es[3] = {1, 1, 1};
    enc(&tm, CU_TENSOR_MAP_DATA_TYPE_BFLOAT16, 3, d_in[6], dims, strides, box, es, CU_TENSOR_MAP_INTERLEAVE_NONE, CU_TENSOR_MAP_SWIZZLE_128B,
        CU_TENSOR_MAP_L2_PROMOTION_L2_256B, CU_TENSOR_MAP_FLOAT_OOB_FILL_NONE);
  }
  fused_kernel<<<NCTA, 384, SMEM_BYTES, cudaStreamPerThread>>>((const uint2*)d_in[0], (Scratch*)scr,
                                          (const uint32_t*)d_in[5], (const unsigned short*)d_in[7], (uint4*)d_out, (const char*)d_in[6], tf[0], tf[1], tm1, tm);
}
```
